```python
import torch

def _softmax(x, axis=-1):
    return torch.softmax(x, dim=axis)

def _gelu(x):
    return torch.nn.functional.gelu(x, approximate='tanh')

def _silu(x):
    return torch.nn.functional.silu(x)

def _sigmoid(x):
    return torch.sigmoid(x)

def _layernorm(x, axis=-1, eps=1e-05):
    m = x.mean(dim=axis, keepdim=True)
    v = x.var(dim=axis, keepdim=True, unbiased=False)
    return (x - m) / torch.sqrt(v + eps)

def _scatter_add(tgt, idx, src, axis=0):
    return tgt.clone().index_add_(axis, idx, src)

def _segment_sum(src, seg, n):
    out = torch.zeros((n,) + src.shape[1:], dtype=src.dtype)
    return out.index_add_(0, seg, src)

def _pad(x, pw):
    flat = tuple((v for pair in reversed(pw) for v in pair))
    return torch.nn.functional.pad(x, flat)
kernel_name = 'interleave_layers__sliding_local_dilated__memory_aug_recurrent_mem_tr__prompt'

def setup_inputs():

    _w = lambda a: (lambda t: t.to(torch.bfloat16) if t.is_floating_point() else t)(torch.as_tensor(a))

    def _A_setup():
        B, S, D = (1, 2048, 576)
        return {'x': _w((lambda *s: torch.randn(*s, dtype=torch.bfloat16) * 0.05)(B, S, D)), 'wqkv': _w((lambda *s: torch.randn(*s, dtype=torch.bfloat16) * 0.05)(D, 3 * D)), 'wo': _w((lambda *s: torch.randn(*s, dtype=torch.bfloat16) * 0.05)(D, D))}
    _A_in = _A_setup()

    def _B_setup():
        B, S, Dm = (1, 2048, 576)
        H, Dh = (32, 128)
        M, seg = (8, 32)
        seg = min(seg, S)
        S = S // seg * seg
        return {'x': _w((lambda *s: torch.randn(*s, dtype=torch.bfloat16) * 0.05)(B, S, Dm)), 'mem0': _w((lambda *s: torch.randn(*s, dtype=torch.bfloat16) * 0.8)(B, M, Dm)), 'Wq': _w((lambda *s: torch.randn(*s, dtype=torch.bfloat16) * 1.6)(Dm, H, Dh) * Dm ** (-0.5)), 'Wk': _w((lambda *s: torch.randn(*s, dtype=torch.bfloat16) * 1.6)(Dm, H, Dh) * Dm ** (-0.5)), 'Wv': _w((lambda *s: torch.randn(*s, dtype=torch.bfloat16) * 0.8)(Dm, H, Dh) * Dm ** (-0.5)), 'Wo': _w((lambda *s: torch.randn(*s, dtype=torch.bfloat16) * 0.8)(H, Dh, Dm) * (H * Dh) ** (-0.5)), 'seg_len': seg}
    _B_in = _B_setup()
    return {'A_x': _A_in['x'], 'A_wqkv': _A_in['wqkv'], 'A_wo': _A_in['wo'], 'B_x': _B_in['x'], 'B_mem0': _B_in['mem0'], 'B_Wq': _B_in['Wq'], 'B_Wk': _B_in['Wk'], 'B_Wv': _B_in['Wv'], 'B_Wo': _B_in['Wo'], 'B_seg_len': _B_in['seg_len']}

def reference(A_x, A_wqkv, A_wo, B_x, B_mem0, B_Wq, B_Wk, B_Wv, B_Wo, B_seg_len):

    def _A_ref(x, wqkv, wo):
        B, S, D = x.shape
        H = 32
        Dh = D // H
        W, dil = (8, 2)
        qkv = (lambda x, *d: x.permute(*d))((x @ wqkv).reshape(B, S, 3, H, Dh), 2, 0, 3, 1, 4)
        q, k, v = (qkv[0], qkv[1], qkv[2])
        scale = Dh ** (-0.5)
        pos = torch.arange(S)
        off = torch.arange(W) * dil
        idx = pos[:, None] - off[None, :]
        mask = idx >= 0
        idx_c = torch.where(mask, idx, 0).reshape(-1)
        kg = k[:, :, idx_c, :].reshape(B, H, S, W, Dh)
        vg = v[:, :, idx_c, :].reshape(B, H, S, W, Dh)
        logits = torch.einsum('bhsd,bhswd->bhsw', q, kg) * scale
        logits = torch.where(mask[None, None, :, :], logits, -1000000000.0)
        attn = _softmax(logits, axis=-1)
        o = torch.einsum('bhsw,bhswd->bhsd', attn, vg)
        return (lambda x, *d: x.permute(*d))(o, 0, 2, 1, 3).reshape(B, S, D) @ wo

    def _B_ref(x, mem0, Wq, Wk, Wv, Wo, seg_len):
        B, S, Dm = x.shape
        H, Dh = (Wq.shape[1], Wq.shape[2])
        M = mem0.shape[1]
        scale = Dh ** (-0.5)
        n_seg = S // seg_len
        L = M + seg_len
        idx = torch.arange(L)
        mask = (idx[:, None] < M) | (idx[:, None] >= idx[None, :])
        mem = mem0
        outs = []
        for s in range(n_seg):
            xs = x[:, s * seg_len:(s + 1) * seg_len, :].clone()
            h = torch.concatenate([mem, xs], axis=1)
            q = torch.einsum('btd,dhe->bhte', h, Wq)
            k = torch.einsum('btd,dhe->bhte', h, Wk)
            v = torch.einsum('btd,dhe->bhte', h, Wv)
            scores = torch.einsum('bhqe,bhke->bhqk', q, k) * scale
            scores = torch.where(mask[None, None], scores, -1000000000.0)
            p = _softmax(scores, axis=-1)
            o = torch.einsum('bhqk,bhke->bhqe', p, v)
            o = torch.einsum('bhte,hed->btd', o, Wo)
            mem = o[:, :M, :].clone()
            outs.append(o[:, M:, :])
        return torch.concatenate(outs, axis=1)
    x = A_x
    x = x + _A_ref(_layernorm(x, axis=-1), A_wqkv, A_wo)
    x = x + _B_ref(_layernorm(x, axis=-1), B_mem0, B_Wq, B_Wk, B_Wv, B_Wo, B_seg_len)
    x = x + _A_ref(_layernorm(x, axis=-1), A_wqkv, A_wo)
    x = x + _B_ref(_layernorm(x, axis=-1), B_mem0, B_Wq, B_Wk, B_Wv, B_Wo, B_seg_len)
    return x
```

```cpp
#include <cuda_runtime.h>
#include <cuda_bf16.h>
#include <stdint.h>

#define LAG 5
constexpr int NSEG = 64;
constexpr int NT = NSEG + LAG;
#define RING_ 8
constexpr int RING = RING_;
constexpr int DM = 576;

__device__ __align__(1024) uint4 g_xt[NT * 2 * 9 * 256];
__device__ __align__(1024) uint4 g_o[RING * 4 * 256 * 32];
__device__ __align__(1024) uint4 g_mp[96 * 3 * 128];
__device__ __align__(1024) uint4 g_mem[NT * 1152];
__device__ __align__(1024) uint4 g_pb[RING * 64 * 8 * 72];
__device__ __align__(1024) uint4 g_pa[RING * 64 * 8 * 72];
__device__ __align__(1024) uint32_t g_oa[RING * 4 * 80 * 64];
__device__ __align__(1024) uint4 g_xn[2 * 2048 * 72];
__device__ __align__(1024) uint4 g_x[3 * 2048 * 72];

constexpr int C_X = 0;
constexpr int C_O = C_X + NT;
constexpr int C_WB = C_O + NT * 8;
constexpr int C_RB = C_WB + NT;
constexpr int C_A = C_RB + NT;
constexpr int C_WA = C_A + NT;
constexpr int C_N0 = C_WA + NT;
constexpr int C_DONE = C_N0 + NSEG;
constexpr int C_TOTAL = C_DONE + 1;
__device__ __align__(1024) unsigned g_cnt[C_TOTAL * 8];

#define TR(i)
#define TR1(i)
#define TR_ON(t)
#define TR_INIT(base)
#define TR_DUMP(slot)
constexpr int TR_BYTES = 0;

#define DEVI __device__ __forceinline__
DEVI uint32_t smem_u32(const void* p) { return (uint32_t)__cvta_generic_to_shared(p); }
DEVI uint32_t pk(float lo, float hi) { uint32_t r; asm("cvt.rn.bf16x2.f32 %0, %1, %2;" : "=r"(r) : "f"(hi), "f"(lo)); return r; }
DEVI float bf_lo(uint32_t u) { return __uint_as_float(u << 16); }
DEVI float bf_hi(uint32_t u) { return __uint_as_float(u & 0xffff0000u); }
DEVI uint32_t movm(uint32_t a) { uint32_t d; asm volatile("movmatrix.sync.aligned.m8n8.trans.b16 %0, %1;" : "=r"(d) : "r"(a)); return d; }
DEVI float ex2(float x) { float y; asm("ex2.approx.ftz.f32 %0, %1;" : "=f"(y) : "f"(x)); return y; }
DEVI float rcp(float x) { float y; asm("rcp.approx.ftz.f32 %0, %1;" : "=f"(y) : "f"(x)); return y; }
DEVI void mma16(float (&d)[4], uint32_t a0, uint32_t a1, uint32_t a2, uint32_t a3, uint32_t b0, uint32_t b1) {
    asm volatile("mma.sync.aligned.m16n8k16.row.col.f32.bf16.bf16.f32 {%0,%1,%2,%3}, {%4,%5,%6,%7}, {%8,%9}, {%0,%1,%2,%3};"
        : "+f"(d[0]), "+f"(d[1]), "+f"(d[2]), "+f"(d[3]) : "r"(a0), "r"(a1), "r"(a2), "r"(a3), "r"(b0), "r"(b1));
}
DEVI void mma8(float (&d)[4], uint32_t a0, uint32_t a1, uint32_t b0) {
    asm volatile("mma.sync.aligned.m16n8k8.row.col.f32.bf16.bf16.f32 {%0,%1,%2,%3}, {%4,%5}, {%6}, {%0,%1,%2,%3};"
        : "+f"(d[0]), "+f"(d[1]), "+f"(d[2]), "+f"(d[3]) : "r"(a0), "r"(a1), "r"(b0));
}
DEVI uint4 lds128(uint32_t a) { uint4 v; asm volatile("ld.shared.v4.u32 {%0,%1,%2,%3}, [%4];" : "=r"(v.x), "=r"(v.y), "=r"(v.z), "=r"(v.w) : "r"(a) : "memory"); return v; }
DEVI uint2 lds64(uint32_t a) { uint2 v; asm volatile("ld.shared.v2.u32 {%0,%1}, [%2];" : "=r"(v.x), "=r"(v.y) : "r"(a) : "memory"); return v; }
DEVI uint32_t lds32(uint32_t a) { uint32_t v; asm volatile("ld.shared.u32 %0, [%1];" : "=r"(v) : "r"(a) : "memory"); return v; }
DEVI uint32_t lds32v(uint32_t a) { uint32_t v; asm volatile("ld.volatile.shared.u32 %0, [%1];" : "=r"(v) : "r"(a) : "memory"); return v; }
DEVI uint4 lds128v(uint32_t a) { uint4 v; asm volatile("ld.volatile.shared.v4.u32 {%0,%1,%2,%3}, [%4];" : "=r"(v.x), "=r"(v.y), "=r"(v.z), "=r"(v.w) : "r"(a) : "memory"); return v; }
DEVI uint32_t lds16(uint32_t a) { uint32_t v; asm volatile("ld.shared.u16 %0, [%1];" : "=r"(v) : "r"(a) : "memory"); return v; }
DEVI uint4 ldsm4(uint32_t a) { uint4 v; asm volatile("ldmatrix.sync.aligned.m8n8.x4.shared.b16 {%0,%1,%2,%3}, [%4];" : "=r"(v.x), "=r"(v.y), "=r"(v.z), "=r"(v.w) : "r"(a) : "memory"); return v; }
DEVI uint2 ldsm2(uint32_t a) { uint2 v; asm volatile("ldmatrix.sync.aligned.m8n8.x2.shared.b16 {%0,%1}, [%2];" : "=r"(v.x), "=r"(v.y) : "r"(a) : "memory"); return v; }
DEVI void stsm4t(uint32_t a, uint32_t x, uint32_t y, uint32_t z, uint32_t w) { asm volatile("stmatrix.sync.aligned.m8n8.x4.trans.shared.b16 [%0], {%1,%2,%3,%4};" :: "r"(a), "r"(x), "r"(y), "r"(z), "r"(w) : "memory"); }
DEVI void sts128(uint32_t a, uint32_t x, uint32_t y, uint32_t z, uint32_t w) { asm volatile("st.shared.v4.u32 [%0], {%1,%2,%3,%4};" :: "r"(a), "r"(x), "r"(y), "r"(z), "r"(w) : "memory"); }
DEVI void sts64(uint32_t a, uint32_t x, uint32_t y) { asm volatile("st.shared.v2.u32 [%0], {%1,%2};" :: "r"(a), "r"(x), "r"(y) : "memory"); }
DEVI void sts32(uint32_t a, uint32_t x) { asm volatile("st.shared.u32 [%0], %1;" :: "r"(a), "r"(x) : "memory"); }
DEVI void sta128(uint32_t a, uint32_t x, uint32_t y, uint32_t z, uint32_t w, uint32_t bar) {
    asm volatile("st.async.weak.shared::cluster.mbarrier::complete_tx::bytes.v4.b32 [%0], {%1,%2,%3,%4}, [%5];" :: "r"(a), "r"(x), "r"(y), "r"(z), "r"(w), "r"(bar) : "memory");
}
DEVI void sta128p(uint32_t a, uint32_t x, uint32_t y, uint32_t z, uint32_t w, uint32_t bar, bool pred) {
    asm volatile("{.reg .pred p; setp.ne.u32 p, %6, 0; @p st.async.weak.shared::cluster.mbarrier::complete_tx::bytes.v4.b32 [%0], {%1,%2,%3,%4}, [%5];}" :: "r"(a), "r"(x), "r"(y), "r"(z), "r"(w), "r"(bar), "r"((uint32_t)pred) : "memory");
}
DEVI void sta64(uint32_t a, uint32_t x, uint32_t y, uint32_t bar) {
    asm volatile("st.async.weak.shared::cluster.mbarrier::complete_tx::bytes.v2.b32 [%0], {%1,%2}, [%3];" :: "r"(a), "r"(x), "r"(y), "r"(bar) : "memory");
}
DEVI void sta32(uint32_t a, uint32_t x, uint32_t bar) {
    asm volatile("st.async.weak.shared::cluster.mbarrier::complete_tx::bytes.b32 [%0], %1, [%2];" :: "r"(a), "r"(x), "r"(bar) : "memory");
}
DEVI uint4 ldg_pkt(const void* p) {
    uint4 v;
    asm volatile("ld.relaxed.gpu.global.v4.u32 {%0,%1,%2,%3}, [%4];" : "=r"(v.x), "=r"(v.y), "=r"(v.z), "=r"(v.w) : "l"(p) : "memory");
    return v;
}
DEVI void ldg_pkt_if(uint4& v, const void* p, bool pred) {
    asm volatile("{.reg .pred p; setp.ne.u32 p, %5, 0; @p ld.relaxed.gpu.global.v4.u32 {%0,%1,%2,%3}, [%4];}"
        : "+r"(v.x), "+r"(v.y), "+r"(v.z), "+r"(v.w) : "l"(p), "r"((uint32_t)pred) : "memory");
}
DEVI void stg_pkt(void* p, uint32_t x, uint32_t y, uint32_t z, uint32_t w) {
    asm volatile("st.relaxed.gpu.global.v4.u32 [%0], {%1,%2,%3,%4};" :: "l"(p), "r"(x), "r"(y), "r"(z), "r"(w) : "memory");
}
DEVI void stg_pkt8(void* p, uint32_t x, uint32_t y, bool pred) {
    asm volatile("{.reg .b64 t; .reg .pred p; setp.ne.u32 p, %3, 0; mov.b64 t, {%1,%2}; @p st.relaxed.gpu.global.b64 [%0], t;}" :: "l"(p), "r"(x), "r"(y), "r"((uint32_t)pred) : "memory");
}
DEVI uint4 ldg128(const void* p) { uint4 v; asm volatile("ld.global.cg.v4.u32 {%0,%1,%2,%3}, [%4];" : "=r"(v.x), "=r"(v.y), "=r"(v.z), "=r"(v.w) : "l"(p) : "memory"); return v; }
DEVI uint2 ldg64(const void* p) { uint2 v; asm volatile("ld.global.cg.v2.u32 {%0,%1}, [%2];" : "=r"(v.x), "=r"(v.y) : "l"(p) : "memory"); return v; }
DEVI uint32_t ldg32(const void* p) { uint32_t v; asm volatile("ld.global.cg.u32 %0, [%1];" : "=r"(v) : "l"(p) : "memory"); return v; }
DEVI void stg128(void* p, uint32_t x, uint32_t y, uint32_t z, uint32_t w) { asm volatile("st.global.cg.v4.u32 [%0], {%1,%2,%3,%4};" :: "l"(p), "r"(x), "r"(y), "r"(z), "r"(w) : "memory"); }
DEVI void stg128p(void* p, uint32_t x, uint32_t y, uint32_t z, uint32_t w, bool pred) { asm volatile("{.reg .pred p; setp.ne.u32 p, %5, 0; @p st.global.cg.v4.u32 [%0], {%1,%2,%3,%4};}" :: "l"(p), "r"(x), "r"(y), "r"(z), "r"(w), "r"((uint32_t)pred) : "memory"); }
DEVI void stg64(void* p, uint32_t x, uint32_t y) { asm volatile("st.global.cg.v2.u32 [%0], {%1,%2};" :: "l"(p), "r"(x), "r"(y) : "memory"); }
DEVI void stg32(void* p, uint32_t x) { asm volatile("st.global.cg.u32 [%0], %1;" :: "l"(p), "r"(x) : "memory"); }
DEVI void cp16(uint32_t dst, const void* src) { asm volatile("cp.async.cg.shared.global [%0], [%1], 16;" :: "r"(dst), "l"(src) : "memory"); }
DEVI void cp4(uint32_t dst, const void* src) { asm volatile("cp.async.ca.shared.global [%0], [%1], 4;" :: "r"(dst), "l"(src) : "memory"); }
DEVI void cp_wait_all() { asm volatile("cp.async.wait_all;" ::: "memory"); }
DEVI void bar_sync(int id, int n) { asm volatile("bar.sync %0, %1;" :: "r"(id), "r"(n) : "memory"); }
DEVI void bar_arrive(int id, int n) { asm volatile("bar.arrive %0, %1;" :: "r"(id), "r"(n) : "memory"); }
DEVI void fence_async_smem() { asm volatile("fence.proxy.async.shared::cta;" ::: "memory"); }
DEVI void mbar_init(uint32_t b, int n) { asm volatile("mbarrier.init.shared.b64 [%0], %1;" :: "r"(b), "r"(n) : "memory"); }
DEVI void mbar_expect(uint32_t b, uint32_t bytes, bool pred) {
    asm volatile("{.reg .pred p; setp.ne.u32 p, %2, 0; @p mbarrier.arrive.expect_tx.shared.b64 _, [%0], %1;}" :: "r"(b), "r"(bytes), "r"((uint32_t)pred) : "memory");
}
DEVI void mbar_arrive_all3(uint32_t b, uint32_t lane) {
    asm volatile("{.reg .pred p; .reg .u32 a; setp.lt.u32 p, %1, 3; @p mapa.shared::cluster.u32 a, %0, %1; @p mbarrier.arrive.relaxed.cluster.shared::cluster.b64 _, [a];}" :: "r"(b), "r"(lane) : "memory");
}
DEVI void mbar_wait(uint32_t b, uint32_t parity) {
    asm volatile("{.reg .pred p; .reg .u32 n;\n"
        "mbarrier.try_wait.parity.shared::cta.b64 p, [%0], %1;\n"
        "@p bra.uni D%=;\n"
        "mov.u32 n, 0;\n"
        "W%=: mbarrier.try_wait.parity.shared::cta.b64 p, [%0], %1;\n"
        "@p bra.uni D%=;\n"
        "add.u32 n, n, 1; setp.lt.u32 p, n, 400000; @p bra.uni W%=;\n"
        "trap;\n"
        "D%=:}" :: "r"(b), "r"(parity) : "memory");
}
constexpr int POLL_LIMIT = 2000000;
DEVI void cnt_wait(const unsigned* c, unsigned target) {
    asm volatile("{.reg .pred p; .reg .u32 n, v;\n"
        "mov.u32 n, 0;\n"
        "W%=: ld.acquire.gpu.global.u32 v, [%0];\n"
        "setp.ge.u32 p, v, %1; vote.sync.all.pred p, p, 0xffffffff; @p bra.uni D%=;\n"
        "add.u32 n, n, 1; setp.lt.u32 p, n, 2000000; @p bra.uni W%=;\n"
        "trap;\n"
        "D%=:}" :: "l"(c), "r"(target) : "memory");
}
DEVI void cnt_add(unsigned* c, int lane) {
    asm volatile("{.reg .pred p; setp.eq.u32 p, %1, 0; fence.acq_rel.gpu; bar.warp.sync 0xffffffff; @p red.relaxed.gpu.global.add.u32 [%0], 1;}" :: "l"(c), "r"(lane) : "memory");
}
DEVI void sched_fence(uint32_t zero, uint32_t id) { asm volatile("{.reg .pred p; setp.ne.u32 p, %0, %1; @p bra.uni D%=; trap; D%=:}" :: "r"(zero), "r"(id) : "memory"); }
DEVI uint32_t clk() { uint32_t c; asm volatile("mov.u32 %0, %%clock;" : "=r"(c) :: "memory"); return c; }
DEVI void delay(uint32_t n) {
    if (n) asm volatile("{.reg .pred p; .reg .u32 c, e; mov.u32 e, %%clock;\n W%=: mov.u32 c, %%clock; sub.u32 c, c, e; setp.lt.u32 p, c, %0; @p bra.uni W%=;}" :: "r"(n) : "memory");
}
DEVI void wg_fence() { asm volatile("wgmma.fence.sync.aligned;" ::: "memory"); }
DEVI void wg_commit() { asm volatile("wgmma.commit_group.sync.aligned;" ::: "memory"); }
template <int N> DEVI void wg_wait() { asm volatile("wgmma.wait_group.sync.aligned %0;" :: "n"(N) : "memory"); }
DEVI uint64_t mkdesc(uint32_t lo, uint32_t hi) { uint64_t d; asm("mov.b64 %0, {%1,%2};" : "=l"(d) : "r"(lo), "r"(hi)); return d; }
DEVI void cluster_sync() { asm volatile("barrier.cluster.arrive.aligned;\n barrier.cluster.wait.aligned;" ::: "memory"); }
DEVI void wgmma_ss16(float (&d)[8], uint64_t da, uint64_t db, int acc) {
    asm volatile("{.reg .pred p; setp.ne.b32 p, %10, 0;\n"
        "wgmma.mma_async.sync.aligned.m64n16k16.f32.bf16.bf16 {%0,%1,%2,%3,%4,%5,%6,%7}, %8, %9, p, 1, 1, 0, 0;}"
        : "+f"(d[0]), "+f"(d[1]), "+f"(d[2]), "+f"(d[3]), "+f"(d[4]), "+f"(d[5]), "+f"(d[6]), "+f"(d[7])
        : "l"(da), "l"(db), "r"(acc));
}
DEVI void wgmma_ss64(float (&d)[32], uint64_t da, uint64_t db, int acc) {
    asm volatile("{.reg .pred p; setp.ne.b32 p, %34, 0;\n"
        "wgmma.mma_async.sync.aligned.m64n64k16.f32.bf16.bf16 {%0,%1,%2,%3,%4,%5,%6,%7,%8,%9,%10,%11,%12,%13,%14,%15,%16,%17,%18,%19,%20,%21,%22,%23,%24,%25,%26,%27,%28,%29,%30,%31}, %32, %33, p, 1, 1, 0, 0;}"
        : "+f"(d[0]), "+f"(d[1]), "+f"(d[2]), "+f"(d[3]), "+f"(d[4]), "+f"(d[5]), "+f"(d[6]), "+f"(d[7]), "+f"(d[8]), "+f"(d[9]), "+f"(d[10]), "+f"(d[11]), "+f"(d[12]), "+f"(d[13]), "+f"(d[14]), "+f"(d[15]), "+f"(d[16]), "+f"(d[17]), "+f"(d[18]), "+f"(d[19]), "+f"(d[20]), "+f"(d[21]), "+f"(d[22]), "+f"(d[23]), "+f"(d[24]), "+f"(d[25]), "+f"(d[26]), "+f"(d[27]), "+f"(d[28]), "+f"(d[29]), "+f"(d[30]), "+f"(d[31])
        : "l"(da), "l"(db), "r"(acc));
}
DEVI void wgmma_rs16(float (&d)[8], uint32_t a0, uint32_t a1, uint32_t a2, uint32_t a3, uint64_t db, int acc) {
    asm volatile("{.reg .pred p; setp.ne.b32 p, %13, 0;\n"
        "wgmma.mma_async.sync.aligned.m64n16k16.f32.bf16.bf16 {%0,%1,%2,%3,%4,%5,%6,%7}, {%8,%9,%10,%11}, %12, p, 1, 1, 0;}"
        : "+f"(d[0]), "+f"(d[1]), "+f"(d[2]), "+f"(d[3]), "+f"(d[4]), "+f"(d[5]), "+f"(d[6]), "+f"(d[7])
        : "r"(a0), "r"(a1), "r"(a2), "r"(a3), "l"(db), "r"(acc));
}
DEVI void wgmma_rs64(float (&d)[32], uint32_t a0, uint32_t a1, uint32_t a2, uint32_t a3, uint64_t db, int acc) {
    asm volatile("{.reg .pred p; setp.ne.b32 p, %37, 0;\n"
        "wgmma.mma_async.sync.aligned.m64n64k16.f32.bf16.bf16 {%0,%1,%2,%3,%4,%5,%6,%7,%8,%9,%10,%11,%12,%13,%14,%15,%16,%17,%18,%19,%20,%21,%22,%23,%24,%25,%26,%27,%28,%29,%30,%31}, {%32,%33,%34,%35}, %36, p, 1, 1, 0;}"
        : "+f"(d[0]), "+f"(d[1]), "+f"(d[2]), "+f"(d[3]), "+f"(d[4]), "+f"(d[5]), "+f"(d[6]), "+f"(d[7]), "+f"(d[8]), "+f"(d[9]), "+f"(d[10]), "+f"(d[11]), "+f"(d[12]), "+f"(d[13]), "+f"(d[14]), "+f"(d[15]), "+f"(d[16]), "+f"(d[17]), "+f"(d[18]), "+f"(d[19]), "+f"(d[20]), "+f"(d[21]), "+f"(d[22]), "+f"(d[23]), "+f"(d[24]), "+f"(d[25]), "+f"(d[26]), "+f"(d[27]), "+f"(d[28]), "+f"(d[29]), "+f"(d[30]), "+f"(d[31])
        : "r"(a0), "r"(a1), "r"(a2), "r"(a3), "l"(db), "r"(acc));
}
DEVI void wgmma_rs168t(float (&d)[84], uint32_t a0, uint32_t a1, uint32_t a2, uint32_t a3, uint64_t db, int acc) {
    asm volatile("{.reg .pred p; setp.ne.b32 p, %89, 0;\n"
        "wgmma.mma_async.sync.aligned.m64n168k16.f32.bf16.bf16 {%0,%1,%2,%3,%4,%5,%6,%7,%8,%9,%10,%11,%12,%13,%14,%15,%16,%17,%18,%19,%20,%21,%22,%23,%24,%25,%26,%27,%28,%29,%30,%31,%32,%33,%34,%35,%36,%37,%38,%39,%40,%41,%42,%43,%44,%45,%46,%47,%48,%49,%50,%51,%52,%53,%54,%55,%56,%57,%58,%59,%60,%61,%62,%63,%64,%65,%66,%67,%68,%69,%70,%71,%72,%73,%74,%75,%76,%77,%78,%79,%80,%81,%82,%83}, {%84,%85,%86,%87}, %88, p, 1, 1, 1;}"
        : "+f"(d[0]), "+f"(d[1]), "+f"(d[2]), "+f"(d[3]), "+f"(d[4]), "+f"(d[5]), "+f"(d[6]), "+f"(d[7]), "+f"(d[8]), "+f"(d[9]), "+f"(d[10]), "+f"(d[11]), "+f"(d[12]), "+f"(d[13]), "+f"(d[14]), "+f"(d[15]), "+f"(d[16]), "+f"(d[17]), "+f"(d[18]), "+f"(d[19]), "+f"(d[20]), "+f"(d[21]), "+f"(d[22]), "+f"(d[23]), "+f"(d[24]), "+f"(d[25]), "+f"(d[26]), "+f"(d[27]), "+f"(d[28]), "+f"(d[29]), "+f"(d[30]), "+f"(d[31]), "+f"(d[32]), "+f"(d[33]), "+f"(d[34]), "+f"(d[35]), "+f"(d[36]), "+f"(d[37]), "+f"(d[38]), "+f"(d[39]), "+f"(d[40]), "+f"(d[41]), "+f"(d[42]), "+f"(d[43]), "+f"(d[44]), "+f"(d[45]), "+f"(d[46]), "+f"(d[47]), "+f"(d[48]), "+f"(d[49]), "+f"(d[50]), "+f"(d[51]), "+f"(d[52]), "+f"(d[53]), "+f"(d[54]), "+f"(d[55]), "+f"(d[56]), "+f"(d[57]), "+f"(d[58]), "+f"(d[59]), "+f"(d[60]), "+f"(d[61]), "+f"(d[62]), "+f"(d[63]), "+f"(d[64]), "+f"(d[65]), "+f"(d[66]), "+f"(d[67]), "+f"(d[68]), "+f"(d[69]), "+f"(d[70]), "+f"(d[71]), "+f"(d[72]), "+f"(d[73]), "+f"(d[74]), "+f"(d[75]), "+f"(d[76]), "+f"(d[77]), "+f"(d[78]), "+f"(d[79]), "+f"(d[80]), "+f"(d[81]), "+f"(d[82]), "+f"(d[83])
        : "r"(a0), "r"(a1), "r"(a2), "r"(a3), "l"(db), "r"(acc));
}
DEVI void wgmma_rs192t(float (&d)[96], uint32_t a0, uint32_t a1, uint32_t a2, uint32_t a3, uint64_t db, int acc) {
    asm volatile("{.reg .pred p; setp.ne.b32 p, %101, 0;\n"
        "wgmma.mma_async.sync.aligned.m64n192k16.f32.bf16.bf16 {%0,%1,%2,%3,%4,%5,%6,%7,%8,%9,%10,%11,%12,%13,%14,%15,%16,%17,%18,%19,%20,%21,%22,%23,%24,%25,%26,%27,%28,%29,%30,%31,%32,%33,%34,%35,%36,%37,%38,%39,%40,%41,%42,%43,%44,%45,%46,%47,%48,%49,%50,%51,%52,%53,%54,%55,%56,%57,%58,%59,%60,%61,%62,%63,%64,%65,%66,%67,%68,%69,%70,%71,%72,%73,%74,%75,%76,%77,%78,%79,%80,%81,%82,%83,%84,%85,%86,%87,%88,%89,%90,%91,%92,%93,%94,%95}, {%96,%97,%98,%99}, %100, p, 1, 1, 1;}"
        : "+f"(d[0]), "+f"(d[1]), "+f"(d[2]), "+f"(d[3]), "+f"(d[4]), "+f"(d[5]), "+f"(d[6]), "+f"(d[7]), "+f"(d[8]), "+f"(d[9]), "+f"(d[10]), "+f"(d[11]), "+f"(d[12]), "+f"(d[13]), "+f"(d[14]), "+f"(d[15]), "+f"(d[16]), "+f"(d[17]), "+f"(d[18]), "+f"(d[19]), "+f"(d[20]), "+f"(d[21]), "+f"(d[22]), "+f"(d[23]), "+f"(d[24]), "+f"(d[25]), "+f"(d[26]), "+f"(d[27]), "+f"(d[28]), "+f"(d[29]), "+f"(d[30]), "+f"(d[31]), "+f"(d[32]), "+f"(d[33]), "+f"(d[34]), "+f"(d[35]), "+f"(d[36]), "+f"(d[37]), "+f"(d[38]), "+f"(d[39]), "+f"(d[40]), "+f"(d[41]), "+f"(d[42]), "+f"(d[43]), "+f"(d[44]), "+f"(d[45]), "+f"(d[46]), "+f"(d[47]), "+f"(d[48]), "+f"(d[49]), "+f"(d[50]), "+f"(d[51]), "+f"(d[52]), "+f"(d[53]), "+f"(d[54]), "+f"(d[55]), "+f"(d[56]), "+f"(d[57]), "+f"(d[58]), "+f"(d[59]), "+f"(d[60]), "+f"(d[61]), "+f"(d[62]), "+f"(d[63]), "+f"(d[64]), "+f"(d[65]), "+f"(d[66]), "+f"(d[67]), "+f"(d[68]), "+f"(d[69]), "+f"(d[70]), "+f"(d[71]), "+f"(d[72]), "+f"(d[73]), "+f"(d[74]), "+f"(d[75]), "+f"(d[76]), "+f"(d[77]), "+f"(d[78]), "+f"(d[79]), "+f"(d[80]), "+f"(d[81]), "+f"(d[82]), "+f"(d[83]), "+f"(d[84]), "+f"(d[85]), "+f"(d[86]), "+f"(d[87]), "+f"(d[88]), "+f"(d[89]), "+f"(d[90]), "+f"(d[91]), "+f"(d[92]), "+f"(d[93]), "+f"(d[94]), "+f"(d[95])
        : "r"(a0), "r"(a1), "r"(a2), "r"(a3), "l"(db), "r"(acc));
}

#define PT_STEPS 36
namespace km {
constexpr int H_KB = 10240;
constexpr int O_H = 0;
constexpr int O_WOF = 92160;
constexpr int O_VX = 141312;
constexpr int O_KX = 157696;
constexpr int O_QX = 163840;
constexpr int O_VM = 169984;
constexpr int O_KM = 174080;
constexpr int O_QM = 175616;
constexpr int O_SM = 177152;
constexpr int O_ST = 182272;
constexpr int O_OX = 192512;
constexpr int O_STG_WO = 147456;
constexpr int O_WS = 199680;
constexpr int O_BAR = O_WS + 6 * 4096;
constexpr int SMEM = O_BAR + 128 + 1024 + TR_BYTES;
enum { B_X = 0, B_XFREE = 8, B_WIN = 16, B_VX = 24, B_SM = 32, B_ST = 40, B_SU = 48, B_EP = 56 };
#define RG "184"
#define RW "136"
#define DLY1 (200 + 100 * w)
#define DLY2 500
#define XON 1
#define GON 1
constexpr uint32_t DESC_HI = (1024 >> 4) | (1u << 30);
constexpr float SC = 0.08838834764831845f * 1.4426950408889634f;
}

__global__ void __cluster_dims__(3, 1, 1) __launch_bounds__(384, 1)
k_main(const __nv_bfloat16* __restrict__ mem0, const __nv_bfloat16* __restrict__ Wq, const __nv_bfloat16* __restrict__ Wk,
       const __nv_bfloat16* __restrict__ Wv, const __nv_bfloat16* __restrict__ Wo) {
    using namespace km;
    extern __shared__ unsigned char smem_raw[];
    const uint32_t sb = (smem_u32(smem_raw) + 1023) & ~1023u;
    const int tid = threadIdx.x, lane = tid & 31, warp = __shfl_sync(~0u, tid >> 5, 0), g = lane >> 2, c = lane & 3;
    uint32_t l16 = __shfl_sync(~0u, lane * 16, lane);
#define OPQ() asm volatile("" : "+r"(l16))
    const int b = blockIdx.x, h = b / 3, r = b % 3;
    const int nq = r == 2 ? 2 : 3;
    const uint32_t bar = sb + O_BAR;
    asm volatile("griddepcontrol.launch_dependents;");
    TR_INIT(bar + 128);

    {
        const int ci = tid & 15, slot = ci >> 1;
        const __nv_bfloat16* src = slot < nq ? Wq + (3 * r + slot) * 16 : slot < 2 * nq ? Wk + (3 * r + slot - nq) * 16 : Wv + (2 * r + slot - 2 * nq) * 16;
        src += h * 128 + (ci & 1) * 8;
#pragma unroll 4
        for (int d = tid >> 4; d < DM; d += 24) cp16(sb + d * 256 + ((ci ^ (d & 7)) << 4), src + (size_t)d * 4096);
        for (int i = tid; i < 128 * 24; i += 384) {
            const int e = i / 24, q = i % 24;
            cp16(sb + O_STG_WO + e * 400 + q * 16, Wo + (size_t)(h * 128 + e) * DM + (q >> 3) * 192 + r * 64 + (q & 7) * 8);
        }
        if (tid == 0) {
            mbar_init(bar + B_X, 1); mbar_init(bar + B_XFREE, 24); mbar_init(bar + B_WIN, 3);
            mbar_init(bar + B_VX, 1); mbar_init(bar + B_SM, 1); mbar_init(bar + B_ST, 1); mbar_init(bar + B_SU, 1); mbar_init(bar + B_EP, 8);
            asm volatile("fence.mbarrier_init.release.cluster;" ::: "memory");
        }
        TR1(1);
        cp_wait_all();
        __syncthreads();
        TR1(2);
    }
    uint32_t roff0, roff1;
    {
        uint32_t x0, x1;
        asm("mapa.shared::cluster.u32 %0, %1, %2;" : "=r"(x0) : "r"(sb), "r"((r + 1) % 3));
        asm("mapa.shared::cluster.u32 %0, %1, %2;" : "=r"(x1) : "r"(sb), "r"((r + 2) % 3));
        roff0 = x0 - sb; roff1 = x1 - sb;
    }
#define LSWAP ((l16 & 0x70) | ((l16 & 0x80) << 1) | ((l16 & 0x100) >> 1))
    const uint32_t nv_remote = 8 - (8 - 2 * nq);

    if (warp < 8) {
        asm volatile("setmaxnreg.inc.sync.aligned.u32 " RG ";");
        uint32_t a[120];
#define AI(kk) (4 * ((kk) - ((kk) + 2) / 6))
        {
            const int mi = lane >> 3;
#pragma unroll
            for (int kk = 0; kk < 36; kk++) {
                const int d = 16 * kk + (mi >> 1) * 8 + (lane & 7);
                const uint32_t ad = sb + d * 256 + (((warp * 2 + (mi & 1)) ^ (lane & 7)) << 4);
                uint32_t f0, f1, f2, f3;
                asm volatile("ldmatrix.sync.aligned.m8n8.x4.trans.shared.b16 {%0,%1,%2,%3}, [%4];" : "=r"(f0), "=r"(f1), "=r"(f2), "=r"(f3) : "r"(ad) : "memory");
                if (kk % 6 == 3) {
                    const uint32_t o0 = sb + O_WS + (kk / 6) * 4096 + warp * 512 + lane * 4;
                    sts32(o0, f0); sts32(o0 + 256, f1); sts32(o0 + 128, f2); sts32(o0 + 384, f3);
                } else { a[AI(kk)] = f0; a[AI(kk) + 1] = f1; a[AI(kk) + 2] = f2; a[AI(kk) + 3] = f3; }
            }
        }
        bar_sync(9, 384);
        for (int i = tid; i < 9 * 640; i += 256) {
            const int kb = i / 640, rem = i % 640, row = rem >> 3, ch = rem & 7;
            uint4 v = make_uint4(0, 0, 0, 0);
            if (row < 16) v = *reinterpret_cast<const uint4*>(mem0 + (row & 7) * DM + kb * 64 + ch * 8);
            sts128(sb + O_H + kb * H_KB + row * 128 + ((ch ^ (row & 7)) << 4), v.x, v.y, v.z, v.w);
        }
        fence_async_smem();
        cluster_sync();

        TR1(3);
        const int kind = warp < nq ? 0 : warp < 2 * nq ? 1 : 2;
        const int sl = kind == 0 ? warp : kind == 1 ? warp - nq : 2 * r + warp - 2 * nq;
        const uint32_t adX0 = sb + (kind == 0 ? O_QX : kind == 1 ? O_KX : O_VX) + sl * 2048;
        const uint32_t adM0 = sb + (kind == 0 ? O_QM : kind == 1 ? O_KM : O_VM) + sl * 512;
        const uint32_t hlo = (((sb + O_H) >> 4) & 0x3fff) | (1u << 16);
        const uint32_t wlo = (((sb + O_WS + (warp >> 2) * 2048) >> 4) & 0x3fff) | (8u << 16);
        const int L = (warp >> 1) & 1, qh = warp & 1;
        const uint32_t st = sb + O_ST + warp * 1280;
        float s[5][4];
        unsigned* const ocnt = g_cnt + (C_O + (h >> 2)) * 8;

#pragma unroll 1
        for (int t = -1;; t++) {
            TR_ON(t);
            OPQ();
            const uint32_t adX = adX0 + l16, adM = adM0 + l16, l8 = l16 >> 1;
            const uint32_t lq = LSWAP;
            if (t >= 0) {
                {
                    float d0[8], d1[8];
#pragma unroll
                    for (int G = 0; G < 3; G++) {
                        bar_sync(1 + G, 288);
                        if (G == 0) { wg_fence(); TR(0); }
#pragma unroll
                        for (int q = 0; q < 12; q++) {
                            const int kk = 12 * G + q;
                            const uint64_t db = mkdesc(hlo + ((kk >> 2) * H_KB + (kk & 3) * 32) / 16, DESC_HI);
                            if (kk % 6 == 3) wgmma_ss16((kk & 1) ? d1 : d0, mkdesc(wlo + (kk / 6) * 256, 16), db, 1);
                            else wgmma_rs16((kk & 1) ? d1 : d0, a[AI(kk)], a[AI(kk) + 1], a[AI(kk) + 2], a[AI(kk) + 3], db, kk >= 2);
                        }
                    }
                    wg_commit(); wg_wait<0>();
                    TR(1);
                    const uint32_t p0 = pk(d0[0] + d1[0], d0[1] + d1[1]), p1 = pk(d0[2] + d1[2], d0[3] + d1[3]);
                    const uint32_t p2 = pk(d0[4] + d1[4], d0[5] + d1[5]), p3 = pk(d0[6] + d1[6], d0[7] + d1[7]);
                    if (kind == 2) {
                        sts128(adM, p0, p1, p2, p3);
                        bar_arrive(4, 384);
                        sta128(adM + roff0, p0, p1, p2, p3, bar + B_SM + roff0);
                        sta128(adM + roff1, p0, p1, p2, p3, bar + B_SM + roff1);
                    } else {
                        stsm4t(adM, p0, p1, p2, p3);
                        bar_arrive(4, 384);
                    }
                }
                if (warp < 4) {
                    mbar_wait(bar + B_ST, t & 1);
#pragma unroll
                    for (int src = 0; src < 2; src++) {
                        const uint4 u = lds128(st + src * 5120 + l16), v = lds128(st + src * 5120 + 512 + l16);
                        s[0][0] += bf_lo(u.x); s[0][1] += bf_hi(u.x); s[0][2] += bf_lo(u.y); s[0][3] += bf_hi(u.y);
                        s[1][0] += bf_lo(u.z); s[1][1] += bf_hi(u.z); s[1][2] += bf_lo(u.w); s[1][3] += bf_hi(u.w);
                        s[2][0] += bf_lo(v.x); s[2][1] += bf_hi(v.x); s[2][2] += bf_lo(v.y); s[2][3] += bf_hi(v.y);
                        s[3][0] += bf_lo(v.z); s[3][1] += bf_hi(v.z); s[3][2] += bf_lo(v.w); s[3][3] += bf_hi(v.w);
                    }
                    {
                        uint4 q[3];
#pragma unroll
                        for (int m = 0; m < 3; m++) q[m] = ldsm4(sb + O_QX + m * 2048 + warp * 512 + lq);
                        s[4][0] = s[4][1] = s[4][2] = s[4][3] = 0.f;
                        bar_sync(5, 256);
#pragma unroll
                        for (int m = 0; m < 3; m++) {
                            const uint2 km_ = ldsm2(sb + O_KM + m * 512 + L * 256 + l16);
                            mma16(s[4], q[m].x, q[m].y, q[m].z, q[m].w, km_.x, km_.y);
                        }
                        const uint32_t w0 = pk(s[4][0], s[4][1]), w1 = pk(s[4][2], s[4][3]);
                        sta64(st + l8 + 5120 + 1024 + roff0, w0, w1, bar + B_SU + roff0);
                        sta64(st + l8 + 1024 + roff1, w0, w1, bar + B_SU + roff1);
                    }
                    TR(2);
                    uint4 v0[3], v1[3];
#pragma unroll
                    for (int m = 0; m < 3; m++) {
                        v0[m] = lds128(sb + O_VX + (3 * r + m) * 2048 + L * 1024 + l16);
                    }
                    mbar_wait(bar + B_SM, t & 1);
                    mbar_wait(bar + B_SU, t & 1);
                    TR(3);
                    {
                        const uint2 x = lds64(st + 1024 + l8), y = lds64(st + 5120 + 1024 + l8);
                        s[4][0] += bf_lo(x.x) + bf_lo(y.x); s[4][1] += bf_hi(x.x) + bf_hi(y.x); s[4][2] += bf_lo(x.y) + bf_lo(y.y); s[4][3] += bf_hi(x.y) + bf_hi(y.y);
                    }
                    float mx0 = fmaxf(s[4][0], s[4][1]), mx1 = fmaxf(s[4][2], s[4][3]);
#pragma unroll
                    for (int n = 0; n < 4; n++) { mx0 = fmaxf(mx0, fmaxf(s[n][0], s[n][1])); mx1 = fmaxf(mx1, fmaxf(s[n][2], s[n][3])); }
#pragma unroll
                    for (int o = 1; o < 4; o <<= 1) { mx0 = fmaxf(mx0, __shfl_xor_sync(~0u, mx0, o)); mx1 = fmaxf(mx1, __shfl_xor_sync(~0u, mx1, o)); }
                    mx0 *= -SC; mx1 *= -SC;
                    float l0 = 0.f, l1 = 0.f;
                    uint32_t p[10];
#pragma unroll
                    for (int n = 0; n < 5; n++) {
                        const float e0 = ex2(fmaf(s[n][0], SC, mx0)), e1 = ex2(fmaf(s[n][1], SC, mx0));
                        const float e2 = ex2(fmaf(s[n][2], SC, mx1)), e3 = ex2(fmaf(s[n][3], SC, mx1));
                        l0 += e0 + e1; l1 += e2 + e3;
                        p[2 * n] = pk(e0, e1); p[2 * n + 1] = pk(e2, e3);
                    }
#pragma unroll
                    for (int o = 1; o < 4; o <<= 1) { l0 += __shfl_xor_sync(~0u, l0, o); l1 += __shfl_xor_sync(~0u, l1, o); }
                    l0 = rcp(l0); l1 = rcp(l1);
                    char* dst = reinterpret_cast<char*>(g_o + (((t & (RING - 1)) * 4 + warp) * 256 + h * 8 + 3 * r) * 32) + l16;
#pragma unroll
                    for (int m = 0; m < 3; m++) {
                        float o0[4] = {0, 0, 0, 0}, o1[4] = {0, 0, 0, 0};
                        v1[m] = lds128(sb + O_VX + (3 * r + m) * 2048 + L * 1024 + 512 + l16);
                        const uint2 vm = lds64(sb + O_VM + (3 * r + m) * 512 + l16 + L * 8);
                        mma8(o0, p[0], p[1], v0[m].x); mma8(o1, p[0], p[1], v0[m].y); mma8(o0, p[2], p[3], v0[m].z); mma8(o1, p[2], p[3], v0[m].w);
                        mma8(o0, p[4], p[5], v1[m].x); mma8(o1, p[4], p[5], v1[m].y); mma8(o0, p[6], p[7], v1[m].z); mma8(o1, p[6], p[7], v1[m].w);
                        mma8(o0, p[8], p[9], vm.x); mma8(o1, p[8], p[9], vm.y);
                        stg128p(dst + m * 512, pk(o0[0] * l0, o0[1] * l0), pk(o0[2] * l1, o0[3] * l1), pk(o1[0] * l0, o1[1] * l0), pk(o1[2] * l1, o1[3] * l1), m < nq && GON);
                    }
                    TR(4);
                }
            }
            if (t + 1 >= NT) break;
            {
                float d[32];
                mbar_wait(bar + B_X, (t + 1) & 1);
                bar_sync(7, 384);
                wg_fence();
                TR(6);
#pragma unroll
                for (int kk = 0; kk < PT_STEPS; kk++) {
                    const uint64_t db = mkdesc(hlo + ((kk >> 2) * H_KB + 2048 + (kk & 3) * 32) / 16, DESC_HI);
                    if (kk % 6 == 3) wgmma_ss64(d, mkdesc(wlo + (kk / 6) * 256, 16), db, 1);
                    else wgmma_rs64(d, a[AI(kk)], a[AI(kk) + 1], a[AI(kk) + 2], a[AI(kk) + 3], db, kk > 0);
                }
                wg_commit();
                asm volatile("{.reg .pred p, q; setp.ne.u32 p, %2, 0; setp.eq.and.u32 q, %1, 0, p; @p fence.acq_rel.gpu; bar.warp.sync 0xffffffff; @q red.relaxed.gpu.global.add.u32 [%0], 1;}"
                    :: "l"(ocnt + t * 64), "r"(l16), "r"((uint32_t)(t >= 0 && warp == 7)) : "memory");
                TR(5);
                mbar_wait(bar + B_WIN, (t + 1) & 1);
                wg_wait<0>();
                TR(7);
                mbar_arrive_all3(bar + B_XFREE, l16 >> 4);
                uint32_t p[16];
#pragma unroll
                for (int u = 0; u < 16; u++) p[u] = pk(d[2 * u], d[2 * u + 1]);
                if (kind == 2) {
#pragma unroll
                    for (int u = 0; u < 4; u++) sts128(adX + u * 512, p[4 * u], p[4 * u + 1], p[4 * u + 2], p[4 * u + 3]);
                } else {
#pragma unroll
                    for (int u = 0; u < 4; u++) stsm4t(adX + u * 512, p[4 * u], p[4 * u + 1], p[4 * u + 2], p[4 * u + 3]);
                }
                __syncwarp();
                asm volatile("{.reg .pred p; setp.eq.u32 p, %1, 0; @p mbarrier.arrive.shared.b64 _, [%0];}" :: "r"(bar + B_EP), "r"(l16) : "memory");
                if (kind == 2) {
                    fence_async_smem();
                    __syncwarp();
                    asm volatile("{.reg .pred p; setp.eq.u32 p, %5, 0;\n"
                        "@p cp.async.bulk.shared::cluster.shared::cta.mbarrier::complete_tx::bytes [%0], [%2], 2048, [%3];\n"
                        "@p cp.async.bulk.shared::cluster.shared::cta.mbarrier::complete_tx::bytes [%1], [%2], 2048, [%4];}"
                        :: "r"(adX0 + roff0), "r"(adX0 + roff1), "r"(adX0), "r"(bar + B_VX + roff0), "r"(bar + B_VX + roff1), "r"(l16) : "memory");
                }
                TR(8);
                {
                    const int lim = 16 * qh + (int)(l16 >> 6) - (int)((l16 >> 3) & 6);
#pragma unroll
                    for (int n = 0; n < 4; n++)
#pragma unroll
                        for (int j = 0; j < 4; j++) s[n][j] = (n == 0 && j >= 2) || 8 * (n - (j >> 1)) + (j & 1) <= lim ? 0.f : -1e30f;
                }
                if (warp < 4) {
                    mbar_wait(bar + B_EP, (t + 1) & 1);
#pragma unroll
                    for (int m = 0; m < 3; m++) {
                        const uint4 q = ldsm4(sb + O_QX + m * 2048 + warp * 512 + lq);
                        const uint4 k0 = ldsm4(sb + O_KX + m * 2048 + L * 1024 + l16);
                        const uint4 k1 = ldsm4(sb + O_KX + m * 2048 + L * 1024 + 512 + l16);
                        mma16(s[0], q.x, q.y, q.z, q.w, k0.x, k0.y);
                        mma16(s[1], q.x, q.y, q.z, q.w, k0.z, k0.w);
                        mma16(s[2], q.x, q.y, q.z, q.w, k1.x, k1.y);
                        mma16(s[3], q.x, q.y, q.z, q.w, k1.z, k1.w);
                    }
                    uint32_t w0 = pk(s[0][0], s[0][1]), w1 = pk(s[0][2], s[0][3]), w2 = pk(s[1][0], s[1][1]), w3 = pk(s[1][2], s[1][3]);
                    sta128(st + l16 + 5120 + roff0, w0, w1, w2, w3, bar + B_ST + roff0);
                    sta128(st + l16 + roff1, w0, w1, w2, w3, bar + B_ST + roff1);
                    w0 = pk(s[2][0], s[2][1]); w1 = pk(s[2][2], s[2][3]); w2 = pk(s[3][0], s[3][1]); w3 = pk(s[3][2], s[3][3]);
                    sta128p(st + l16 + 5120 + 512 + roff0, w0, w1, w2, w3, bar + B_ST + roff0, qh);
                    sta128p(st + l16 + 512 + roff1, w0, w1, w2, w3, bar + B_ST + roff1, qh);
                    TR(9);
                }
            }
        }
        bar_sync(7, 384);
        if (warp == 7) cnt_add(ocnt + (NT - 1) * 64, lane);
        cluster_sync();
    } else {
        asm volatile("setmaxnreg.dec.sync.aligned.u32 " RW ";");
        const int w = warp - 8;
        bar_sync(9, 384);
#pragma unroll 1
        for (int i = 0; i < 24; i++) {
            const int G = i >> 3, kk = i & 7;
            const uint32_t s = sb + O_STG_WO + (16 * kk + 2 * c) * 400 + (G * 64 + 16 * w + 4 * (g >> 1) + (g & 1)) * 2;
            uint32_t v[4];
#pragma unroll
            for (int q = 0; q < 4; q++) {
                const uint32_t s2 = s + (q & 1) * 3200 + (q >> 1) * 4;
                v[q] = lds16(s2) | (lds16(s2 + 400) << 16);
            }
            sts128(sb + O_WOF + (w * 24 + i) * 512 + lane * 16, v[0], v[1], v[2], v[3]);
        }
        bar_sync(6, 128);
        for (int i = tid - 256; i < (O_OX - O_KX) / 16; i += 128) sts128(sb + O_KX + i * 16, 0, 0, 0, 0);
        auto arm = [&]() {
            const uint32_t ln = l16 >> 4;
            mbar_expect(bar + B_VX + (ln & 3) * 8, ln == 0 ? nv_remote * 2048 : ln == 1 ? nv_remote * 512 + 2560 : ln == 2 ? 6144 : 2048, ln < 4);
        };
        if (w == 3) arm();
        cluster_sync();
        TR1(3);
        const int L = w >> 1, hf = w & 1;
        const uint32_t rd = hf ? roff1 : roff0;
        const uint32_t rzero = __shfl_sync(~0u, lds32(sb + O_ST + 512), 0);

        auto fetch_tile = [&](int u) {
            const bool a0 = u < NSEG && (XON || u < 8), a1 = u >= LAG && (XON || u < 8);
            mbar_expect(bar + B_X, ((int)a0 + (int)a1) * 36864, l16 == 0);
            const int kb = (l16 >> 5) * 3 + r, hl = (l16 >> 4) & 1;
            asm volatile("{.reg .pred p; setp.ne.u32 p, %4, 0; fence.proxy.async.global;\n"
                "@p cp.async.bulk.shared::cluster.global.mbarrier::complete_tx::bytes.multicast::cluster [%0], [%1], 4096, [%2], %3;}"
                :: "r"(sb + O_H + kb * H_KB + 2048 + hl * 4096), "l"(g_xt + ((u * 2 + hl) * 9 + kb) * 256), "r"(bar + B_X), "h"((uint16_t)7),
                   "r"((uint32_t)(l16 < 96 && (hl ? a1 : a0))) : "memory");
        };
        bar_arrive(7, 384);
        if (w < 3) bar_arrive(1 + w, 288);
        else {
            mbar_arrive_all3(bar + B_WIN, l16 >> 4);
            cnt_wait(g_cnt + C_X * 8, 64);
            fetch_tile(0);
            cnt_wait(g_cnt + (C_X + 1) * 8, 64);
        }
#pragma unroll 1
        for (int t = 0; t < NT; t++) {
            TR_ON(t);
            OPQ();
            if (w == 3 && t + 1 < NT) { mbar_wait(bar + B_XFREE, t & 1); TR(6); fetch_tile(t + 1); TR(7); }
            mbar_wait(bar + B_EP, t & 1);
            uint4 kx[3][2], vx[4][2];
            const uint32_t lp = LSWAP;
#pragma unroll
            for (int m = 0; m < 3; m++) {
                kx[m][0] = ldsm4(sb + O_KX + m * 2048 + L * 1024 + lp);
                kx[m][1] = ldsm4(sb + O_KX + m * 2048 + L * 1024 + 512 + lp);
            }
            mbar_wait(bar + B_VX, t & 1);
#pragma unroll
            for (int m = 0; m < 8; m++) vx[m >> 1][m & 1] = lds128(sb + O_VX + (hf * 4 + (m >> 1)) * 2048 + L * 1024 + (m & 1) * 512 + l16);
            TR(0);
            bar_sync(4, 384);
            float s0[4] = {0, 0, 0, 0}, s1[4] = {0, 0, 0, 0}, sm[4] = {0, 0, 0, 0};
            {
                uint2 q[3]; uint4 km_[3];
#pragma unroll
                for (int m = 0; m < 3; m++) q[m] = ldsm2(sb + O_QM + m * 512 + L * 256 + l16);
#pragma unroll
                for (int m = 0; m < 3; m++) km_[m] = ldsm4(sb + O_KM + m * 512 + (lp ^ (L << 8)));
                bar_arrive(5, 256);
#pragma unroll
                for (int m = 0; m < 3; m++) {
                    mma16(s0, kx[m][0].x, kx[m][0].y, kx[m][0].z, kx[m][0].w, q[m].x, q[m].y);
                    mma16(s1, kx[m][1].x, kx[m][1].y, kx[m][1].z, kx[m][1].w, q[m].x, q[m].y);
                    mma16(sm, km_[m].x, km_[m].y, km_[m].z, km_[m].w, q[m].x, q[m].y);
                }
                const uint32_t ad = sb + O_SM + (1 - hf) * 1280 + L * 640 + rd;
                sta128(ad + l16, pk(s0[0], s0[1]), pk(s0[2], s0[3]), pk(s1[0], s1[1]), pk(s1[2], s1[3]), bar + B_SM + rd);
                sta32(ad + 512 + (l16 >> 2), pk(sm[0], sm[1]), bar + B_SM + rd);
            }
            TR(1);
            const uint32_t wof = sb + O_WOF + w * 24 * 512 + l16;
            uint4 bw[8];
#pragma unroll
            for (int kk = 0; kk < 8; kk++) bw[kk] = lds128(wof + kk * 512);
            mbar_wait(bar + B_SM, t & 1);
            TR(2);
            {
                const uint32_t ad = sb + O_SM + L * 640;
                const uint4 u = lds128(ad + l16), v = lds128(ad + 1280 + l16);
                const uint32_t x = lds32(ad + 512 + (l16 >> 2)), y = lds32(ad + 1280 + 512 + (l16 >> 2));
                s0[0] += bf_lo(u.x) + bf_lo(v.x); s0[1] += bf_hi(u.x) + bf_hi(v.x); s0[2] += bf_lo(u.y) + bf_lo(v.y); s0[3] += bf_hi(u.y) + bf_hi(v.y);
                s1[0] += bf_lo(u.z) + bf_lo(v.z); s1[1] += bf_hi(u.z) + bf_hi(v.z); s1[2] += bf_lo(u.w) + bf_lo(v.w); s1[3] += bf_hi(u.w) + bf_hi(v.w);
                sm[0] += bf_lo(x) + bf_lo(y); sm[1] += bf_hi(x) + bf_hi(y);
            }
            uint2 vm[4];
#pragma unroll
            for (int m = 0; m < 4; m++) vm[m] = lds64(sb + O_VM + (hf * 4 + m) * 512 + l16 + L * 8);
            float mx0 = fmaxf(fmaxf(fmaxf(s0[0], s0[2]), fmaxf(s1[0], s1[2])), sm[0]);
            float mx1 = fmaxf(fmaxf(fmaxf(s0[1], s0[3]), fmaxf(s1[1], s1[3])), sm[1]);
#pragma unroll
            for (int o = 4; o < 32; o <<= 1) { mx0 = fmaxf(mx0, __shfl_xor_sync(~0u, mx0, o)); mx1 = fmaxf(mx1, __shfl_xor_sync(~0u, mx1, o)); }
            mx0 *= -SC; mx1 *= -SC;
            s0[0] = ex2(fmaf(s0[0], SC, mx0)); s0[1] = ex2(fmaf(s0[1], SC, mx1));
            s0[2] = ex2(fmaf(s0[2], SC, mx0)); s0[3] = ex2(fmaf(s0[3], SC, mx1));
            const uint32_t pb0 = movm(pk(s0[0], s0[1])), pb1 = movm(pk(s0[2], s0[3]));
            s1[0] = ex2(fmaf(s1[0], SC, mx0)); s1[1] = ex2(fmaf(s1[1], SC, mx1));
            s1[2] = ex2(fmaf(s1[2], SC, mx0)); s1[3] = ex2(fmaf(s1[3], SC, mx1));
            const uint32_t pb2 = movm(pk(s1[0], s1[1])), pb3 = movm(pk(s1[2], s1[3]));
            sm[0] = ex2(fmaf(sm[0], SC, mx0)); sm[1] = ex2(fmaf(sm[1], SC, mx1));
            const uint32_t pm = movm(pk(sm[0], sm[1]));
            float l0 = (s0[0] + s0[2]) + (s1[0] + s1[2]) + sm[0], l1 = (s0[1] + s0[3]) + (s1[1] + s1[3]) + sm[1];
            float o[4][4];
#pragma unroll
            for (int m = 0; m < 4; m++) { o[m][0] = o[m][1] = o[m][2] = o[m][3] = 0.f; mma16(o[m], vx[m][0].x, vx[m][0].y, vx[m][0].z, vx[m][0].w, pb0, pb1); }
            l0 += __shfl_xor_sync(~0u, l0, 4); l1 += __shfl_xor_sync(~0u, l1, 4);
#pragma unroll
            for (int m = 0; m < 4; m++) mma16(o[m], vx[m][1].x, vx[m][1].y, vx[m][1].z, vx[m][1].w, pb2, pb3);
            l0 += __shfl_xor_sync(~0u, l0, 8); l1 += __shfl_xor_sync(~0u, l1, 8);
#pragma unroll
            for (int m = 0; m < 4; m++) mma8(o[m], vm[m].x, vm[m].y, pm);
            l0 += __shfl_xor_sync(~0u, l0, 16); l1 += __shfl_xor_sync(~0u, l1, 16);
            l0 = rcp(l0); l1 = rcp(l1);
#pragma unroll
            for (int m = 0; m < 4; m += 2)
                stsm4t(sb + O_OX + (hf * 4 + m) * 512 + (L ^ ((h >> 2) & 1)) * 128   + ((l16 & 0x180) << 1) + (l16 & 0x70),
                       pk(o[m][0] * l0, o[m][1] * l1), pk(o[m][2] * l0, o[m][3] * l1), pk(o[m + 1][0] * l0, o[m + 1][1] * l1), pk(o[m + 1][2] * l0, o[m + 1][3] * l1));
            TR(3);
            char* const pdst = reinterpret_cast<char*>(g_mp + (r * 32 + w * 8) * 384 + h * 4) + ((l16 >> 6) * 6144 + (l16 & 48));
            bar_sync(6, 128);
            uint4 ao[8];
#pragma unroll
            for (int kk = 0; kk < 8; kk++) ao[kk] = ldsm4(sb + O_OX + kk * 512 + l16);
            uint4 b1[8];
            sched_fence(rzero, 1);
            const uint32_t tag = (t & 1) ^ 1;
#pragma unroll
            for (int G = 0; G < 3; G++) {
                float e[4][4];
#pragma unroll
                for (int q = 0; q < 4; q++) e[q][0] = e[q][1] = e[q][2] = e[q][3] = 0.f;
#pragma unroll
                for (int kk = 0; kk < 8; kk++) {
                    const uint4 bb = G == 1 ? b1[kk] : bw[kk];
                    mma16(e[(kk & 1) * 2], ao[kk].x, ao[kk].y, ao[kk].z, ao[kk].w, bb.x, bb.y);
                    mma16(e[(kk & 1) * 2 + 1], ao[kk].x, ao[kk].y, ao[kk].z, ao[kk].w, bb.z, bb.w);
                    if (G < 2 && kk == 1) {
#pragma unroll
                        for (int j = 0; j < 8; j++) (G == 0 ? b1[j] : bw[j]) = lds128v(wof + 4096 * (G + 1) + j * 512);
                        sched_fence(rzero, 2 + G);
                    }
                }
                stg_pkt(pdst + G * 2048, (pk(e[0][0] + e[2][0], e[0][1] + e[2][1]) & ~1u) | tag, pk(e[1][0] + e[3][0], e[1][1] + e[3][1]),
                        pk(e[0][2] + e[2][2], e[0][3] + e[2][3]), pk(e[1][2] + e[3][2], e[1][3] + e[3][3]));
                if (G == 0) sched_fence(rzero, 4);
            }
            TR(4);
            if (w < 3) {
                bar_arrive(7, 384);
                if (t + 1 < NT) {
                    OPQ();
                    const char* const rsrc = reinterpret_cast<const char*>(g_mp + b * 384 + w * 128) + l16;
                    const bool fresh = t + 1 <= LAG && l16 >= 256;
                    uint2 m0v = make_uint2(0, 0);
                    if (t + 1 <= LAG) m0v = *reinterpret_cast<const uint2*>(mem0 + (b & 7) * DM + 192 * w + 16 * (b >> 3) + ((l16 >> 2) & 12));
                    delay(DLY1);
                    uint4 v[4];
#pragma unroll
                    for (int i = 0; i < 4; i++) v[i] = ldg_pkt(rsrc + i * 512);
                    for (int n = 0; __any_sync(~0u, ((v[0].x ^ tag) | (v[1].x ^ tag) | (v[2].x ^ tag) | (v[3].x ^ tag)) & 1); n++) {
#pragma unroll
                        for (int i = 0; i < 4; i++) ldg_pkt_if(v[i], rsrc + i * 512, (v[i].x ^ tag) & 1);
                        if (n > POLL_LIMIT) asm volatile("trap;");
                    }
                    TR(5);
                    float s[8];
                    s[0] = (bf_lo(v[0].x) + bf_lo(v[1].x)) + (bf_lo(v[2].x) + bf_lo(v[3].x)); s[1] = (bf_hi(v[0].x) + bf_hi(v[1].x)) + (bf_hi(v[2].x) + bf_hi(v[3].x));
                    s[2] = (bf_lo(v[0].y) + bf_lo(v[1].y)) + (bf_lo(v[2].y) + bf_lo(v[3].y)); s[3] = (bf_hi(v[0].y) + bf_hi(v[1].y)) + (bf_hi(v[2].y) + bf_hi(v[3].y));
                    s[4] = (bf_lo(v[0].z) + bf_lo(v[1].z)) + (bf_lo(v[2].z) + bf_lo(v[3].z)); s[5] = (bf_hi(v[0].z) + bf_hi(v[1].z)) + (bf_hi(v[2].z) + bf_hi(v[3].z));
                    s[6] = (bf_lo(v[0].w) + bf_lo(v[1].w)) + (bf_lo(v[2].w) + bf_lo(v[3].w)); s[7] = (bf_hi(v[0].w) + bf_hi(v[1].w)) + (bf_hi(v[2].w) + bf_hi(v[3].w));
#pragma unroll
                    for (int j = 0; j < 4; j++) s[j] += __shfl_xor_sync(~0u, s[j + 4], 16);
#pragma unroll
                    for (int of = 4; of < 16; of <<= 1)
#pragma unroll
                        for (int j = 0; j < 4; j++) s[j] += __shfl_xor_sync(~0u, s[j], of);
                    char* const mem_t = reinterpret_cast<char*>(g_mem + t * 1152 + w * 384);
                    stg_pkt8(mem_t + (b >> 3) * 512 + (((b & 7) >> 1) | ((b & 1) << 2)) * 32 + ((l16 & 256) + ((l16 & 48) >> 1)),
                             fresh ? m0v.x : pk(s[0], s[1]), fresh ? m0v.y : pk(s[2], s[3]), (l16 & 0xc0) == 0);
                    TR(6);
                    delay(DLY2);
                    const char* src = mem_t + l16;
                    const uint32_t gr = ((l16 >> 4) & 6) | ((l16 >> 7) & 1);
                    const uint32_t gdst = sb + O_H + 3 * w * H_KB + ((l16 & 256) << 2) + gr * 128 + ((l16 & 16) ^ (gr << 4));
                    uint4 x[12];
#pragma unroll
                    for (int i = 0; i < 12; i++) x[i] = ldg_pkt(src + i * 512);
                    for (int n = 0;; n++) {
                        uint32_t mx = 0;
#pragma unroll
                        for (int i = 0; i < 12; i++) mx = max(mx, max(x[i].x, x[i].z));
                        if (!__any_sync(~0u, mx == 0xffffffffu)) break;
#pragma unroll
                        for (int i = 0; i < 12; i++) ldg_pkt_if(x[i], src + i * 512, max(x[i].x, x[i].z) == 0xffffffffu);
                        if (n > POLL_LIMIT) asm volatile("trap;");
                    }
                    TR(7);
#pragma unroll
                    for (int i = 0; i < 12; i++) sts128((gdst ^ ((i & 3) << 5)) + (i >> 2) * H_KB, x[i].x, x[i].y, x[i].z, x[i].w);
                    fence_async_smem();
                    bar_arrive(1 + w, 288);
                    TR(8);
                }
            } else {
                bar_sync(7, 384);
                if (t + 1 < NT) {
                    arm();
                    __syncwarp();
                    mbar_arrive_all3(bar + B_WIN, l16 >> 4);
                    if (t + 2 < NT) cnt_wait(g_cnt + (C_X + t + 2) * 8, 64);
                }
                TR(5);
            }
        }
        cluster_sync();
    }
    TR_DUMP(b);
}

__global__ void k_init() {
    const int i = blockIdx.x * blockDim.x + threadIdx.x;
    if (i < NT * 1152) g_mem[i] = make_uint4(~0u, ~0u, ~0u, ~0u);
    if (i < 96 * 3 * 128) g_mp[i] = make_uint4(0, 0, 0, 0);
    if (i < C_TOTAL * 8) g_cnt[i] = 0;
}

extern "C" void kernel_launch(void* const* d_in, const int* in_sizes, int n_in, void* d_out, int out_size) {
    const __nv_bfloat16* x = (const __nv_bfloat16*)d_in[0];
    const __nv_bfloat16* wqkv = (const __nv_bfloat16*)d_in[1];
    const __nv_bfloat16* wo = (const __nv_bfloat16*)d_in[2];
    const __nv_bfloat16* mem0 = (const __nv_bfloat16*)d_in[4];
    const __nv_bfloat16* Wq = (const __nv_bfloat16*)d_in[5];
    const __nv_bfloat16* Wk = (const __nv_bfloat16*)d_in[6];
    const __nv_bfloat16* Wv = (const __nv_bfloat16*)d_in[7];
    const __nv_bfloat16* Wo = (const __nv_bfloat16*)d_in[8];
    cudaFuncSetAttribute(k_main, cudaFuncAttributeMaxDynamicSharedMemorySize, km::SMEM);
    cudaStream_t s = cudaStreamPerThread;
    k_init<<<(NT * 1152 + 255) / 256, 256, 0, s>>>();
    k_main<<<96, 384, km::SMEM, s>>>(mem0, Wq, Wk, Wv, Wo);
    cudaLaunchConfig_t cfg = {};
    cudaLaunchAttribute at[1];
    at[0].id = cudaLaunchAttributeProgrammaticStreamSerialization;
    at[0].val.programmaticStreamSerializationAllowed = 1;
    cfg.stream = s; cfg.attrs = at; cfg.numAttrs = 1;
    cudaFuncSetAttribute(k_aux, cudaFuncAttributeMaxDynamicSharedMemorySize, ka::SMEM);
    cfg.gridDim = dim3(36); cfg.blockDim = dim3(384); cfg.dynamicSmemBytes = ka::SMEM;
    cudaLaunchKernelEx(&cfg, k_aux, x, wqkv, wo, Wo, (__nv_bfloat16*)d_out);
}
```

```cpp
#include <cuda_runtime.h>
#include <cuda_bf16.h>
#include <stdint.h>

#define LAG 6
constexpr int NSEG = 64;
constexpr int NT = NSEG + LAG;
#define RING_ 8
constexpr int RING = RING_;
constexpr int DM = 576;

__device__ __align__(1024) uint4 g_xt[NT * 2 * 9 * 256];
__device__ __align__(1024) uint4 g_o[RING * 4 * 256 * 32];
__device__ __align__(1024) uint4 g_mp[96 * 3 * 128];
__device__ __align__(1024) uint4 g_mem[NT * 1152];
__device__ __align__(1024) uint4 g_pb[RING * 64 * 8 * 72];
__device__ __align__(1024) uint4 g_pa[RING * 64 * 4 * 72];
__device__ __align__(1024) uint4 g_oa[RING * 4 * 44 * 32];
__device__ __align__(1024) uint4 g_xa[NT * 2 * 9 * 256];
__device__ __align__(1024) uint4 g_x[3 * 2048 * 72];

constexpr int C_X = 0;
constexpr int C_O = C_X + NT;
constexpr int C_WB = C_O + NT * 8;
constexpr int C_RB = C_WB + NT;
constexpr int C_A = C_RB + NT;
constexpr int C_WA = C_A + NT;
constexpr int C_N0 = C_WA + NT;
constexpr int C_DONE = C_N0 + NSEG;
constexpr int C_TOTAL = C_DONE + 1;
__device__ __align__(1024) unsigned g_cnt[C_TOTAL * 8];

#define TR(i)
#define TR1(i)
#define TR_ON(t)
#define TR_INIT(base)
#define TR_DUMP(slot)
#define TRG(t, i)
constexpr int TR_BYTES = 0;

#define DEVI __device__ __forceinline__
DEVI uint32_t smem_u32(const void* p) { return (uint32_t)__cvta_generic_to_shared(p); }
DEVI uint32_t pk(float lo, float hi) { uint32_t r; asm("cvt.rn.bf16x2.f32 %0, %1, %2;" : "=r"(r) : "f"(hi), "f"(lo)); return r; }
DEVI float bf_lo(uint32_t u) { return __uint_as_float(u << 16); }
DEVI float bf_hi(uint32_t u) { return __uint_as_float(u & 0xffff0000u); }
DEVI uint32_t movm(uint32_t a) { uint32_t d; asm volatile("movmatrix.sync.aligned.m8n8.trans.b16 %0, %1;" : "=r"(d) : "r"(a)); return d; }
DEVI float ex2(float x) { float y; asm("ex2.approx.ftz.f32 %0, %1;" : "=f"(y) : "f"(x)); return y; }
DEVI float rcp(float x) { float y; asm("rcp.approx.ftz.f32 %0, %1;" : "=f"(y) : "f"(x)); return y; }
DEVI void mma16(float (&d)[4], uint32_t a0, uint32_t a1, uint32_t a2, uint32_t a3, uint32_t b0, uint32_t b1) {
    asm volatile("mma.sync.aligned.m16n8k16.row.col.f32.bf16.bf16.f32 {%0,%1,%2,%3}, {%4,%5,%6,%7}, {%8,%9}, {%0,%1,%2,%3};"
        : "+f"(d[0]), "+f"(d[1]), "+f"(d[2]), "+f"(d[3]) : "r"(a0), "r"(a1), "r"(a2), "r"(a3), "r"(b0), "r"(b1));
}
DEVI void mma8(float (&d)[4], uint32_t a0, uint32_t a1, uint32_t b0) {
    asm volatile("mma.sync.aligned.m16n8k8.row.col.f32.bf16.bf16.f32 {%0,%1,%2,%3}, {%4,%5}, {%6}, {%0,%1,%2,%3};"
        : "+f"(d[0]), "+f"(d[1]), "+f"(d[2]), "+f"(d[3]) : "r"(a0), "r"(a1), "r"(b0));
}
DEVI uint4 lds128(uint32_t a) { uint4 v; asm volatile("ld.shared.v4.u32 {%0,%1,%2,%3}, [%4];" : "=r"(v.x), "=r"(v.y), "=r"(v.z), "=r"(v.w) : "r"(a) : "memory"); return v; }
DEVI uint2 lds64(uint32_t a) { uint2 v; asm volatile("ld.shared.v2.u32 {%0,%1}, [%2];" : "=r"(v.x), "=r"(v.y) : "r"(a) : "memory"); return v; }
DEVI uint32_t lds32(uint32_t a) { uint32_t v; asm volatile("ld.shared.u32 %0, [%1];" : "=r"(v) : "r"(a) : "memory"); return v; }
DEVI uint32_t lds32v(uint32_t a) { uint32_t v; asm volatile("ld.volatile.shared.u32 %0, [%1];" : "=r"(v) : "r"(a) : "memory"); return v; }
DEVI uint4 lds128v(uint32_t a) { uint4 v; asm volatile("ld.volatile.shared.v4.u32 {%0,%1,%2,%3}, [%4];" : "=r"(v.x), "=r"(v.y), "=r"(v.z), "=r"(v.w) : "r"(a) : "memory"); return v; }
DEVI uint32_t lds16(uint32_t a) { uint32_t v; asm volatile("ld.shared.u16 %0, [%1];" : "=r"(v) : "r"(a) : "memory"); return v; }
DEVI uint4 ldsm4(uint32_t a) { uint4 v; asm volatile("ldmatrix.sync.aligned.m8n8.x4.shared.b16 {%0,%1,%2,%3}, [%4];" : "=r"(v.x), "=r"(v.y), "=r"(v.z), "=r"(v.w) : "r"(a) : "memory"); return v; }
DEVI uint2 ldsm2(uint32_t a) { uint2 v; asm volatile("ldmatrix.sync.aligned.m8n8.x2.shared.b16 {%0,%1}, [%2];" : "=r"(v.x), "=r"(v.y) : "r"(a) : "memory"); return v; }
DEVI void stsm4t(uint32_t a, uint32_t x, uint32_t y, uint32_t z, uint32_t w) { asm volatile("stmatrix.sync.aligned.m8n8.x4.trans.shared.b16 [%0], {%1,%2,%3,%4};" :: "r"(a), "r"(x), "r"(y), "r"(z), "r"(w) : "memory"); }
DEVI void sts128(uint32_t a, uint32_t x, uint32_t y, uint32_t z, uint32_t w) { asm volatile("st.shared.v4.u32 [%0], {%1,%2,%3,%4};" :: "r"(a), "r"(x), "r"(y), "r"(z), "r"(w) : "memory"); }
DEVI void sts64(uint32_t a, uint32_t x, uint32_t y) { asm volatile("st.shared.v2.u32 [%0], {%1,%2};" :: "r"(a), "r"(x), "r"(y) : "memory"); }
DEVI void sts32(uint32_t a, uint32_t x) { asm volatile("st.shared.u32 [%0], %1;" :: "r"(a), "r"(x) : "memory"); }
DEVI void sta128(uint32_t a, uint32_t x, uint32_t y, uint32_t z, uint32_t w, uint32_t bar) {
    asm volatile("st.async.weak.shared::cluster.mbarrier::complete_tx::bytes.v4.b32 [%0], {%1,%2,%3,%4}, [%5];" :: "r"(a), "r"(x), "r"(y), "r"(z), "r"(w), "r"(bar) : "memory");
}
DEVI void sta128p(uint32_t a, uint32_t x, uint32_t y, uint32_t z, uint32_t w, uint32_t bar, bool pred) {
    asm volatile("{.reg .pred p; setp.ne.u32 p, %6, 0; @p st.async.weak.shared::cluster.mbarrier::complete_tx::bytes.v4.b32 [%0], {%1,%2,%3,%4}, [%5];}" :: "r"(a), "r"(x), "r"(y), "r"(z), "r"(w), "r"(bar), "r"((uint32_t)pred) : "memory");
}
DEVI void sta64(uint32_t a, uint32_t x, uint32_t y, uint32_t bar) {
    asm volatile("st.async.weak.shared::cluster.mbarrier::complete_tx::bytes.v2.b32 [%0], {%1,%2}, [%3];" :: "r"(a), "r"(x), "r"(y), "r"(bar) : "memory");
}
DEVI void sta32(uint32_t a, uint32_t x, uint32_t bar) {
    asm volatile("st.async.weak.shared::cluster.mbarrier::complete_tx::bytes.b32 [%0], %1, [%2];" :: "r"(a), "r"(x), "r"(bar) : "memory");
}
DEVI uint4 ldg_pkt(const void* p) {
    uint4 v;
    asm volatile("ld.relaxed.gpu.global.v4.u32 {%0,%1,%2,%3}, [%4];" : "=r"(v.x), "=r"(v.y), "=r"(v.z), "=r"(v.w) : "l"(p) : "memory");
    return v;
}
DEVI void ldg_pkt_if(uint4& v, const void* p, bool pred) {
    asm volatile("{.reg .pred p; setp.ne.u32 p, %5, 0; @p ld.relaxed.gpu.global.v4.u32 {%0,%1,%2,%3}, [%4];}"
        : "+r"(v.x), "+r"(v.y), "+r"(v.z), "+r"(v.w) : "l"(p), "r"((uint32_t)pred) : "memory");
}
DEVI void stg_pkt(void* p, uint32_t x, uint32_t y, uint32_t z, uint32_t w) {
    asm volatile("st.relaxed.gpu.global.v4.u32 [%0], {%1,%2,%3,%4};" :: "l"(p), "r"(x), "r"(y), "r"(z), "r"(w) : "memory");
}
DEVI void stg_pkt8(void* p, uint32_t x, uint32_t y, bool pred) {
    asm volatile("{.reg .b64 t; .reg .pred p; setp.ne.u32 p, %3, 0; mov.b64 t, {%1,%2}; @p st.relaxed.gpu.global.b64 [%0], t;}" :: "l"(p), "r"(x), "r"(y), "r"((uint32_t)pred) : "memory");
}
DEVI uint4 ldg128(const void* p) { uint4 v; asm volatile("ld.global.cg.v4.u32 {%0,%1,%2,%3}, [%4];" : "=r"(v.x), "=r"(v.y), "=r"(v.z), "=r"(v.w) : "l"(p) : "memory"); return v; }
DEVI uint2 ldg64(const void* p) { uint2 v; asm volatile("ld.global.cg.v2.u32 {%0,%1}, [%2];" : "=r"(v.x), "=r"(v.y) : "l"(p) : "memory"); return v; }
DEVI uint32_t ldg32(const void* p) { uint32_t v; asm volatile("ld.global.cg.u32 %0, [%1];" : "=r"(v) : "l"(p) : "memory"); return v; }
DEVI void stg128(void* p, uint32_t x, uint32_t y, uint32_t z, uint32_t w) { asm volatile("st.global.cg.v4.u32 [%0], {%1,%2,%3,%4};" :: "l"(p), "r"(x), "r"(y), "r"(z), "r"(w) : "memory"); }
DEVI void stg128p(void* p, uint32_t x, uint32_t y, uint32_t z, uint32_t w, bool pred) { asm volatile("{.reg .pred p; setp.ne.u32 p, %5, 0; @p st.global.cg.v4.u32 [%0], {%1,%2,%3,%4};}" :: "l"(p), "r"(x), "r"(y), "r"(z), "r"(w), "r"((uint32_t)pred) : "memory"); }
DEVI void stg64(void* p, uint32_t x, uint32_t y) { asm volatile("st.global.cg.v2.u32 [%0], {%1,%2};" :: "l"(p), "r"(x), "r"(y) : "memory"); }
DEVI void stg32(void* p, uint32_t x) { asm volatile("st.global.cg.u32 [%0], %1;" :: "l"(p), "r"(x) : "memory"); }
DEVI void cp16(uint32_t dst, const void* src) { asm volatile("cp.async.cg.shared.global [%0], [%1], 16;" :: "r"(dst), "l"(src) : "memory"); }
DEVI void cp4(uint32_t dst, const void* src) { asm volatile("cp.async.ca.shared.global [%0], [%1], 4;" :: "r"(dst), "l"(src) : "memory"); }
DEVI void cp_wait_all() { asm volatile("cp.async.wait_all;" ::: "memory"); }
DEVI void bar_sync(int id, int n) { asm volatile("bar.sync %0, %1;" :: "r"(id), "r"(n) : "memory"); }
DEVI void bar_arrive(int id, int n) { asm volatile("bar.arrive %0, %1;" :: "r"(id), "r"(n) : "memory"); }
DEVI void fence_async_smem() { asm volatile("fence.proxy.async.shared::cta;" ::: "memory"); }
DEVI void mbar_init(uint32_t b, int n) { asm volatile("mbarrier.init.shared.b64 [%0], %1;" :: "r"(b), "r"(n) : "memory"); }
DEVI void mbar_expect(uint32_t b, uint32_t bytes, bool pred) {
    asm volatile("{.reg .pred p; setp.ne.u32 p, %2, 0; @p mbarrier.arrive.expect_tx.shared.b64 _, [%0], %1;}" :: "r"(b), "r"(bytes), "r"((uint32_t)pred) : "memory");
}
DEVI void mbar_arrive(uint32_t b, bool pred) { asm volatile("{.reg .pred p; setp.ne.u32 p, %1, 0; @p mbarrier.arrive.shared.b64 _, [%0];}" :: "r"(b), "r"((uint32_t)pred) : "memory"); }
DEVI void mbar_arrive_all3(uint32_t b, uint32_t lane) {
    asm volatile("{.reg .pred p; .reg .u32 a; setp.lt.u32 p, %1, 3; @p mapa.shared::cluster.u32 a, %0, %1; @p mbarrier.arrive.relaxed.cluster.shared::cluster.b64 _, [a];}" :: "r"(b), "r"(lane) : "memory");
}
#define FAULT "or.b32 n, n, 1; st.volatile.shared.u32 [n], n;\n"
#define LIM1 "400000"
#define LIM2 "2000000"
DEVI void fault_if(bool p, uint32_t n) { asm volatile("{.reg .pred p; setp.ne.u32 p, %0, 0; @p st.volatile.shared.u32 [%1], %1;}" :: "r"((uint32_t)p), "r"(n | 1) : "memory"); }
DEVI void mbar_wait(uint32_t b, uint32_t parity) {
    asm volatile("{.reg .pred p; .reg .u32 n;\n"
        "mbarrier.try_wait.parity.shared::cta.b64 p, [%0], %1;\n"
        "@p bra.uni D%=;\n"
        "mov.u32 n, 0;\n"
        "W%=: mbarrier.try_wait.parity.shared::cta.b64 p, [%0], %1;\n"
        "@p bra.uni D%=;\n"
        "add.u32 n, n, 1; setp.lt.u32 p, n, " LIM1 "; @p bra.uni W%=;\n"
        FAULT
        "D%=:}" :: "r"(b), "r"(parity) : "memory");
}
constexpr int POLL_LIMIT = 2000000;
DEVI void cnt_wait(const unsigned* c, unsigned target) {
    asm volatile("{.reg .pred p; .reg .u32 n, v;\n"
        "ld.acquire.gpu.global.u32 v, [%0];\n"
        "setp.ge.u32 p, v, %1; vote.sync.all.pred p, p, 0xffffffff; @p bra.uni D%=;\n"
        "mov.u32 n, 0;\n"
        "W%=: ld.acquire.gpu.global.u32 v, [%0];\n"
        "setp.ge.u32 p, v, %1; vote.sync.all.pred p, p, 0xffffffff; @p bra.uni D%=;\n"
        "add.u32 n, n, 1; setp.lt.u32 p, n, " LIM2 "; @p bra.uni W%=;\n"
        FAULT
        "D%=:}" :: "l"(c), "r"(target) : "memory");
}
DEVI void cnt_add(unsigned* c, int lane) {
    asm volatile("{.reg .pred p; setp.eq.u32 p, %1, 0; fence.acq_rel.gpu; bar.warp.sync 0xffffffff; @p red.relaxed.gpu.global.add.u32 [%0], 1;}" :: "l"(c), "r"(lane) : "memory");
}
DEVI void sched_fence(uint32_t zero, uint32_t id) { asm volatile("{.reg .pred p; setp.ne.u32 p, %0, %1; @p bra.uni D%=; exit; D%=:}" :: "r"(zero), "r"(id) : "memory"); }
DEVI uint32_t clk() { uint32_t c; asm volatile("mov.u32 %0, %%clock;" : "=r"(c) :: "memory"); return c; }
DEVI void delay(uint32_t n) {
    if (n) asm volatile("{.reg .pred p; .reg .u32 c, e; mov.u32 e, %%clock;\n W%=: mov.u32 c, %%clock; sub.u32 c, c, e; setp.lt.u32 p, c, %0; @p bra.uni W%=;}" :: "r"(n) : "memory");
}
DEVI void wg_fence() { asm volatile("wgmma.fence.sync.aligned;" ::: "memory"); }
DEVI void wg_commit() { asm volatile("wgmma.commit_group.sync.aligned;" ::: "memory"); }
template <int N> DEVI void wg_wait() { asm volatile("wgmma.wait_group.sync.aligned %0;" :: "n"(N) : "memory"); }
DEVI uint64_t mkdesc(uint32_t lo, uint32_t hi) { uint64_t d; asm("mov.b64 %0, {%1,%2};" : "=l"(d) : "r"(lo), "r"(hi)); return d; }
DEVI void cluster_sync() { asm volatile("barrier.cluster.arrive.aligned;\n barrier.cluster.wait.aligned;" ::: "memory"); }
DEVI void wgmma_ss16(float (&d)[8], uint64_t da, uint64_t db, int acc) {
    asm volatile("{.reg .pred p; setp.ne.b32 p, %10, 0;\n"
        "wgmma.mma_async.sync.aligned.m64n16k16.f32.bf16.bf16 {%0,%1,%2,%3,%4,%5,%6,%7}, %8, %9, p, 1, 1, 0, 0;}"
        : "+f"(d[0]), "+f"(d[1]), "+f"(d[2]), "+f"(d[3]), "+f"(d[4]), "+f"(d[5]), "+f"(d[6]), "+f"(d[7])
        : "l"(da), "l"(db), "r"(acc));
}
DEVI void wgmma_ss64(float (&d)[32], uint64_t da, uint64_t db, int acc) {
    asm volatile("{.reg .pred p; setp.ne.b32 p, %34, 0;\n"
        "wgmma.mma_async.sync.aligned.m64n64k16.f32.bf16.bf16 {%0,%1,%2,%3,%4,%5,%6,%7,%8,%9,%10,%11,%12,%13,%14,%15,%16,%17,%18,%19,%20,%21,%22,%23,%24,%25,%26,%27,%28,%29,%30,%31}, %32, %33, p, 1, 1, 0, 0;}"
        : "+f"(d[0]), "+f"(d[1]), "+f"(d[2]), "+f"(d[3]), "+f"(d[4]), "+f"(d[5]), "+f"(d[6]), "+f"(d[7]), "+f"(d[8]), "+f"(d[9]), "+f"(d[10]), "+f"(d[11]), "+f"(d[12]), "+f"(d[13]), "+f"(d[14]), "+f"(d[15]), "+f"(d[16]), "+f"(d[17]), "+f"(d[18]), "+f"(d[19]), "+f"(d[20]), "+f"(d[21]), "+f"(d[22]), "+f"(d[23]), "+f"(d[24]), "+f"(d[25]), "+f"(d[26]), "+f"(d[27]), "+f"(d[28]), "+f"(d[29]), "+f"(d[30]), "+f"(d[31])
        : "l"(da), "l"(db), "r"(acc));
}
DEVI void wgmma_rs16(float (&d)[8], uint32_t a0, uint32_t a1, uint32_t a2, uint32_t a3, uint64_t db, int acc) {
    asm volatile("{.reg .pred p; setp.ne.b32 p, %13, 0;\n"
        "wgmma.mma_async.sync.aligned.m64n16k16.f32.bf16.bf16 {%0,%1,%2,%3,%4,%5,%6,%7}, {%8,%9,%10,%11}, %12, p, 1, 1, 0;}"
        : "+f"(d[0]), "+f"(d[1]), "+f"(d[2]), "+f"(d[3]), "+f"(d[4]), "+f"(d[5]), "+f"(d[6]), "+f"(d[7])
        : "r"(a0), "r"(a1), "r"(a2), "r"(a3), "l"(db), "r"(acc));
}
DEVI void wgmma_rs64(float (&d)[32], uint32_t a0, uint32_t a1, uint32_t a2, uint32_t a3, uint64_t db, int acc) {
    asm volatile("{.reg .pred p; setp.ne.b32 p, %37, 0;\n"
        "wgmma.mma_async.sync.aligned.m64n64k16.f32.bf16.bf16 {%0,%1,%2,%3,%4,%5,%6,%7,%8,%9,%10,%11,%12,%13,%14,%15,%16,%17,%18,%19,%20,%21,%22,%23,%24,%25,%26,%27,%28,%29,%30,%31}, {%32,%33,%34,%35}, %36, p, 1, 1, 0;}"
        : "+f"(d[0]), "+f"(d[1]), "+f"(d[2]), "+f"(d[3]), "+f"(d[4]), "+f"(d[5]), "+f"(d[6]), "+f"(d[7]), "+f"(d[8]), "+f"(d[9]), "+f"(d[10]), "+f"(d[11]), "+f"(d[12]), "+f"(d[13]), "+f"(d[14]), "+f"(d[15]), "+f"(d[16]), "+f"(d[17]), "+f"(d[18]), "+f"(d[19]), "+f"(d[20]), "+f"(d[21]), "+f"(d[22]), "+f"(d[23]), "+f"(d[24]), "+f"(d[25]), "+f"(d[26]), "+f"(d[27]), "+f"(d[28]), "+f"(d[29]), "+f"(d[30]), "+f"(d[31])
        : "r"(a0), "r"(a1), "r"(a2), "r"(a3), "l"(db), "r"(acc));
}
DEVI void wgmma_ss168t(float (&d)[84], uint64_t da, uint64_t db, int acc) {
    asm volatile("{.reg .pred p; setp.ne.b32 p, %86, 0;\n"
        "wgmma.mma_async.sync.aligned.m64n168k16.f32.bf16.bf16 {%0,%1,%2,%3,%4,%5,%6,%7,%8,%9,%10,%11,%12,%13,%14,%15,%16,%17,%18,%19,%20,%21,%22,%23,%24,%25,%26,%27,%28,%29,%30,%31,%32,%33,%34,%35,%36,%37,%38,%39,%40,%41,%42,%43,%44,%45,%46,%47,%48,%49,%50,%51,%52,%53,%54,%55,%56,%57,%58,%59,%60,%61,%62,%63,%64,%65,%66,%67,%68,%69,%70,%71,%72,%73,%74,%75,%76,%77,%78,%79,%80,%81,%82,%83}, %84, %85, p, 1, 1, 0, 1;}"
        : "+f"(d[0]), "+f"(d[1]), "+f"(d[2]), "+f"(d[3]), "+f"(d[4]), "+f"(d[5]), "+f"(d[6]), "+f"(d[7]), "+f"(d[8]), "+f"(d[9]), "+f"(d[10]), "+f"(d[11]), "+f"(d[12]), "+f"(d[13]), "+f"(d[14]), "+f"(d[15]), "+f"(d[16]), "+f"(d[17]), "+f"(d[18]), "+f"(d[19]), "+f"(d[20]), "+f"(d[21]), "+f"(d[22]), "+f"(d[23]), "+f"(d[24]), "+f"(d[25]), "+f"(d[26]), "+f"(d[27]), "+f"(d[28]), "+f"(d[29]), "+f"(d[30]), "+f"(d[31]), "+f"(d[32]), "+f"(d[33]), "+f"(d[34]), "+f"(d[35]), "+f"(d[36]), "+f"(d[37]), "+f"(d[38]), "+f"(d[39]), "+f"(d[40]), "+f"(d[41]), "+f"(d[42]), "+f"(d[43]), "+f"(d[44]), "+f"(d[45]), "+f"(d[46]), "+f"(d[47]), "+f"(d[48]), "+f"(d[49]), "+f"(d[50]), "+f"(d[51]), "+f"(d[52]), "+f"(d[53]), "+f"(d[54]), "+f"(d[55]), "+f"(d[56]), "+f"(d[57]), "+f"(d[58]), "+f"(d[59]), "+f"(d[60]), "+f"(d[61]), "+f"(d[62]), "+f"(d[63]), "+f"(d[64]), "+f"(d[65]), "+f"(d[66]), "+f"(d[67]), "+f"(d[68]), "+f"(d[69]), "+f"(d[70]), "+f"(d[71]), "+f"(d[72]), "+f"(d[73]), "+f"(d[74]), "+f"(d[75]), "+f"(d[76]), "+f"(d[77]), "+f"(d[78]), "+f"(d[79]), "+f"(d[80]), "+f"(d[81]), "+f"(d[82]), "+f"(d[83])
        : "l"(da), "l"(db), "r"(acc));
}
DEVI void wgmma_rs96t(float (&d)[48], uint32_t a0, uint32_t a1, uint32_t a2, uint32_t a3, uint64_t db, int acc) {
    asm volatile("{.reg .pred p; setp.ne.b32 p, %53, 0;\n"
        "wgmma.mma_async.sync.aligned.m64n96k16.f32.bf16.bf16 {%0,%1,%2,%3,%4,%5,%6,%7,%8,%9,%10,%11,%12,%13,%14,%15,%16,%17,%18,%19,%20,%21,%22,%23,%24,%25,%26,%27,%28,%29,%30,%31,%32,%33,%34,%35,%36,%37,%38,%39,%40,%41,%42,%43,%44,%45,%46,%47}, {%48,%49,%50,%51}, %52, p, 1, 1, 1;}"
        : "+f"(d[0]), "+f"(d[1]), "+f"(d[2]), "+f"(d[3]), "+f"(d[4]), "+f"(d[5]), "+f"(d[6]), "+f"(d[7]), "+f"(d[8]), "+f"(d[9]), "+f"(d[10]), "+f"(d[11]), "+f"(d[12]), "+f"(d[13]), "+f"(d[14]), "+f"(d[15]), "+f"(d[16]), "+f"(d[17]), "+f"(d[18]), "+f"(d[19]), "+f"(d[20]), "+f"(d[21]), "+f"(d[22]), "+f"(d[23]), "+f"(d[24]), "+f"(d[25]), "+f"(d[26]), "+f"(d[27]), "+f"(d[28]), "+f"(d[29]), "+f"(d[30]), "+f"(d[31]), "+f"(d[32]), "+f"(d[33]), "+f"(d[34]), "+f"(d[35]), "+f"(d[36]), "+f"(d[37]), "+f"(d[38]), "+f"(d[39]), "+f"(d[40]), "+f"(d[41]), "+f"(d[42]), "+f"(d[43]), "+f"(d[44]), "+f"(d[45]), "+f"(d[46]), "+f"(d[47])
        : "r"(a0), "r"(a1), "r"(a2), "r"(a3), "l"(db), "r"(acc));
}
DEVI void wgmma_rs192t(float (&d)[96], uint32_t a0, uint32_t a1, uint32_t a2, uint32_t a3, uint64_t db, int acc) {
    asm volatile("{.reg .pred p; setp.ne.b32 p, %101, 0;\n"
        "wgmma.mma_async.sync.aligned.m64n192k16.f32.bf16.bf16 {%0,%1,%2,%3,%4,%5,%6,%7,%8,%9,%10,%11,%12,%13,%14,%15,%16,%17,%18,%19,%20,%21,%22,%23,%24,%25,%26,%27,%28,%29,%30,%31,%32,%33,%34,%35,%36,%37,%38,%39,%40,%41,%42,%43,%44,%45,%46,%47,%48,%49,%50,%51,%52,%53,%54,%55,%56,%57,%58,%59,%60,%61,%62,%63,%64,%65,%66,%67,%68,%69,%70,%71,%72,%73,%74,%75,%76,%77,%78,%79,%80,%81,%82,%83,%84,%85,%86,%87,%88,%89,%90,%91,%92,%93,%94,%95}, {%96,%97,%98,%99}, %100, p, 1, 1, 1;}"
        : "+f"(d[0]), "+f"(d[1]), "+f"(d[2]), "+f"(d[3]), "+f"(d[4]), "+f"(d[5]), "+f"(d[6]), "+f"(d[7]), "+f"(d[8]), "+f"(d[9]), "+f"(d[10]), "+f"(d[11]), "+f"(d[12]), "+f"(d[13]), "+f"(d[14]), "+f"(d[15]), "+f"(d[16]), "+f"(d[17]), "+f"(d[18]), "+f"(d[19]), "+f"(d[20]), "+f"(d[21]), "+f"(d[22]), "+f"(d[23]), "+f"(d[24]), "+f"(d[25]), "+f"(d[26]), "+f"(d[27]), "+f"(d[28]), "+f"(d[29]), "+f"(d[30]), "+f"(d[31]), "+f"(d[32]), "+f"(d[33]), "+f"(d[34]), "+f"(d[35]), "+f"(d[36]), "+f"(d[37]), "+f"(d[38]), "+f"(d[39]), "+f"(d[40]), "+f"(d[41]), "+f"(d[42]), "+f"(d[43]), "+f"(d[44]), "+f"(d[45]), "+f"(d[46]), "+f"(d[47]), "+f"(d[48]), "+f"(d[49]), "+f"(d[50]), "+f"(d[51]), "+f"(d[52]), "+f"(d[53]), "+f"(d[54]), "+f"(d[55]), "+f"(d[56]), "+f"(d[57]), "+f"(d[58]), "+f"(d[59]), "+f"(d[60]), "+f"(d[61]), "+f"(d[62]), "+f"(d[63]), "+f"(d[64]), "+f"(d[65]), "+f"(d[66]), "+f"(d[67]), "+f"(d[68]), "+f"(d[69]), "+f"(d[70]), "+f"(d[71]), "+f"(d[72]), "+f"(d[73]), "+f"(d[74]), "+f"(d[75]), "+f"(d[76]), "+f"(d[77]), "+f"(d[78]), "+f"(d[79]), "+f"(d[80]), "+f"(d[81]), "+f"(d[82]), "+f"(d[83]), "+f"(d[84]), "+f"(d[85]), "+f"(d[86]), "+f"(d[87]), "+f"(d[88]), "+f"(d[89]), "+f"(d[90]), "+f"(d[91]), "+f"(d[92]), "+f"(d[93]), "+f"(d[94]), "+f"(d[95])
        : "r"(a0), "r"(a1), "r"(a2), "r"(a3), "l"(db), "r"(acc));
}

#define PT_STEPS 36
namespace km {
constexpr int H_KB = 10240;
constexpr int O_H = 0;
constexpr int O_WOF = 92160;
constexpr int O_VX = 141312;
constexpr int O_KX = 157696;
constexpr int O_QX = 163840;
constexpr int O_VM = 169984;
constexpr int O_KM = 174080;
constexpr int O_QM = 175616;
constexpr int O_SM = 177152;
constexpr int O_ST = 182272;
constexpr int O_OX = 192512;
constexpr int O_STG_WO = 147456;
constexpr int O_WS = 199680;
constexpr int O_BAR = O_WS + 6 * 4096;
constexpr int SMEM = O_BAR + 128 + 1024 + TR_BYTES;
enum { B_X = 0, B_XFREE = 8, B_WIN = 16, B_VX = 24, B_SM = 32, B_ST = 40, B_SU = 48, B_EP = 56 };
#define RG "184"
#define RW "136"
#define DLY1 (200 * w)
#define DLY2 600
#define XON 1
#define GON 1
constexpr uint32_t DESC_HI = (1024 >> 4) | (1u << 30);
constexpr float SC = 0.08838834764831845f * 1.4426950408889634f;
}

__global__ void __cluster_dims__(3, 1, 1) __launch_bounds__(384, 1)
k_main(const __nv_bfloat16* __restrict__ mem0, const __nv_bfloat16* __restrict__ Wq, const __nv_bfloat16* __restrict__ Wk,
       const __nv_bfloat16* __restrict__ Wv, const __nv_bfloat16* __restrict__ Wo) {
    using namespace km;
    extern __shared__ unsigned char smem_raw[];
    const uint32_t sb = (smem_u32(smem_raw) + 1023) & ~1023u;
    const int tid = threadIdx.x, lane = tid & 31, warp = __shfl_sync(~0u, tid >> 5, 0), g = lane >> 2, c = lane & 3;
    uint32_t l16 = __shfl_sync(~0u, lane * 16, lane);
#define OPQ() asm volatile("" : "+r"(l16))
    const int b = blockIdx.x, h = b / 3, r = b % 3;
    const int nq = r == 2 ? 2 : 3;
    const uint32_t bar = sb + O_BAR;
    asm volatile("griddepcontrol.launch_dependents;");
    TR_INIT(bar + 128);
    TRG(79, 0);

    {
        const int ci = tid & 15, slot = ci >> 1;
        const __nv_bfloat16* src = slot < nq ? Wq + (3 * r + slot) * 16 : slot < 2 * nq ? Wk + (3 * r + slot - nq) * 16 : Wv + (2 * r + slot - 2 * nq) * 16;
        src += h * 128 + (ci & 1) * 8;
#pragma unroll 4
        for (int d = tid >> 4; d < DM; d += 24) cp16(sb + d * 256 + ((ci ^ (d & 7)) << 4), src + (size_t)d * 4096);
        for (int i = tid; i < 128 * 24; i += 384) {
            const int e = i / 24, q = i % 24;
            cp16(sb + O_STG_WO + e * 400 + q * 16, Wo + (size_t)(h * 128 + e) * DM + (q >> 3) * 192 + r * 64 + (q & 7) * 8);
        }
        if (tid == 0) {
            mbar_init(bar + B_X, 1); mbar_init(bar + B_XFREE, 24); mbar_init(bar + B_WIN, 3);
            mbar_init(bar + B_VX, 1); mbar_init(bar + B_SM, 1); mbar_init(bar + B_ST, 1); mbar_init(bar + B_SU, 1); mbar_init(bar + B_EP, 8);
            asm volatile("fence.mbarrier_init.release.cluster;" ::: "memory");
        }
        TR1(1);
        cp_wait_all();
        __syncthreads();
        TR1(2);
    }
    uint32_t roff0, roff1;
    {
        uint32_t x0, x1;
        asm("mapa.shared::cluster.u32 %0, %1, %2;" : "=r"(x0) : "r"(sb), "r"((r + 1) % 3));
        asm("mapa.shared::cluster.u32 %0, %1, %2;" : "=r"(x1) : "r"(sb), "r"((r + 2) % 3));
        roff0 = x0 - sb; roff1 = x1 - sb;
    }
#define LSWAP ((l16 & 0x70) | ((l16 & 0x80) << 1) | ((l16 & 0x100) >> 1))
    const uint32_t nv_remote = 8 - (8 - 2 * nq);

    if (warp < 8) {
        asm volatile("setmaxnreg.inc.sync.aligned.u32 " RG ";");
        uint32_t a[120];
#define AI(kk) (4 * ((kk) - ((kk) + 2) / 6))
        {
            const int mi = lane >> 3;
#pragma unroll
            for (int kk = 0; kk < 36; kk++) {
                const int d = 16 * kk + (mi >> 1) * 8 + (lane & 7);
                const uint32_t ad = sb + d * 256 + (((warp * 2 + (mi & 1)) ^ (lane & 7)) << 4);
                uint32_t f0, f1, f2, f3;
                asm volatile("ldmatrix.sync.aligned.m8n8.x4.trans.shared.b16 {%0,%1,%2,%3}, [%4];" : "=r"(f0), "=r"(f1), "=r"(f2), "=r"(f3) : "r"(ad) : "memory");
                if (kk % 6 == 3) {
                    const uint32_t o0 = sb + O_WS + (kk / 6) * 4096 + warp * 512 + lane * 4;
                    sts32(o0, f0); sts32(o0 + 256, f1); sts32(o0 + 128, f2); sts32(o0 + 384, f3);
                } else { a[AI(kk)] = f0; a[AI(kk) + 1] = f1; a[AI(kk) + 2] = f2; a[AI(kk) + 3] = f3; }
            }
        }
        bar_sync(9, 384);
        for (int i = tid; i < 9 * 640; i += 256) {
            const int kb = i / 640, rem = i % 640, row = rem >> 3, ch = rem & 7;
            uint4 v = make_uint4(0, 0, 0, 0);
            if (row < 16) v = *reinterpret_cast<const uint4*>(mem0 + (row & 7) * DM + kb * 64 + ch * 8);
            sts128(sb + O_H + kb * H_KB + row * 128 + ((ch ^ (row & 7)) << 4), v.x, v.y, v.z, v.w);
        }
        fence_async_smem();
        cluster_sync();

        TR1(3);
        const int kind = warp < nq ? 0 : warp < 2 * nq ? 1 : 2;
        const int sl = kind == 0 ? warp : kind == 1 ? warp - nq : 2 * r + warp - 2 * nq;
        const uint32_t adX0 = sb + (kind == 0 ? O_QX : kind == 1 ? O_KX : O_VX) + sl * 2048;
        const uint32_t adM0 = sb + (kind == 0 ? O_QM : kind == 1 ? O_KM : O_VM) + sl * 512;
        const uint32_t hlo = (((sb + O_H) >> 4) & 0x3fff) | (1u << 16);
        const uint32_t wlo = (((sb + O_WS + (warp >> 2) * 2048) >> 4) & 0x3fff) | (8u << 16);
        const int L = (warp >> 1) & 1, qh = warp & 1;
        const uint32_t st = sb + O_ST + warp * 1280;
        float s[5][4];
        unsigned* const ocnt = g_cnt + (C_O + (h >> 2)) * 8;

#pragma unroll 1
        for (int t = -1;; t++) {
            TR_ON(t);
            OPQ();
            const uint32_t adX = adX0 + l16, adM = adM0 + l16, l8 = l16 >> 1;
            const uint32_t lq = LSWAP;
            if (t >= 0) {
                {
                    float d0[8], d1[8];
#pragma unroll
                    for (int G = 0; G < 3; G++) {
                        bar_sync(1 + G, 288);
                        if (G == 0) { wg_fence(); TR(0); }
#pragma unroll
                        for (int q = 0; q < 12; q++) {
                            const int kk = 12 * G + q;
                            const uint64_t db = mkdesc(hlo + ((kk >> 2) * H_KB + (kk & 3) * 32) / 16, DESC_HI);
                            if (kk % 6 == 3) wgmma_ss16((kk & 1) ? d1 : d0, mkdesc(wlo + (kk / 6) * 256, 16), db, 1);
                            else wgmma_rs16((kk & 1) ? d1 : d0, a[AI(kk)], a[AI(kk) + 1], a[AI(kk) + 2], a[AI(kk) + 3], db, kk >= 2);
                        }
                    }
                    wg_commit(); wg_wait<0>();
                    TR(1);
                    const uint32_t p0 = pk(d0[0] + d1[0], d0[1] + d1[1]), p1 = pk(d0[2] + d1[2], d0[3] + d1[3]);
                    const uint32_t p2 = pk(d0[4] + d1[4], d0[5] + d1[5]), p3 = pk(d0[6] + d1[6], d0[7] + d1[7]);
                    if (kind == 2) {
                        sts128(adM, p0, p1, p2, p3);
                        bar_arrive(4, 384);
                        sta128(adM + roff0, p0, p1, p2, p3, bar + B_SM + roff0);
                        sta128(adM + roff1, p0, p1, p2, p3, bar + B_SM + roff1);
                    } else {
                        stsm4t(adM, p0, p1, p2, p3);
                        bar_arrive(4, 384);
                    }
                }
                if (warp < 4) {
                    mbar_wait(bar + B_ST, t & 1);
#pragma unroll
                    for (int src = 0; src < 2; src++) {
                        const uint4 u = lds128(st + src * 5120 + l16), v = lds128(st + src * 5120 + 512 + l16);
                        s[0][0] += bf_lo(u.x); s[0][1] += bf_hi(u.x); s[0][2] += bf_lo(u.y); s[0][3] += bf_hi(u.y);
                        s[1][0] += bf_lo(u.z); s[1][1] += bf_hi(u.z); s[1][2] += bf_lo(u.w); s[1][3] += bf_hi(u.w);
                        s[2][0] += bf_lo(v.x); s[2][1] += bf_hi(v.x); s[2][2] += bf_lo(v.y); s[2][3] += bf_hi(v.y);
                        s[3][0] += bf_lo(v.z); s[3][1] += bf_hi(v.z); s[3][2] += bf_lo(v.w); s[3][3] += bf_hi(v.w);
                    }
                    {
                        uint4 q[3];
#pragma unroll
                        for (int m = 0; m < 3; m++) q[m] = ldsm4(sb + O_QX + m * 2048 + warp * 512 + lq);
                        s[4][0] = s[4][1] = s[4][2] = s[4][3] = 0.f;
                        bar_sync(5, 256);
#pragma unroll
                        for (int m = 0; m < 3; m++) {
                            const uint2 km_ = ldsm2(sb + O_KM + m * 512 + L * 256 + l16);
                            mma16(s[4], q[m].x, q[m].y, q[m].z, q[m].w, km_.x, km_.y);
                        }
                        const uint32_t w0 = pk(s[4][0], s[4][1]), w1 = pk(s[4][2], s[4][3]);
                        sta64(st + l8 + 5120 + 1024 + roff0, w0, w1, bar + B_SU + roff0);
                        sta64(st + l8 + 1024 + roff1, w0, w1, bar + B_SU + roff1);
                    }
                    TR(2);
                    uint4 v0[3], v1[3];
#pragma unroll
                    for (int m = 0; m < 3; m++) {
                        v0[m] = lds128(sb + O_VX + (3 * r + m) * 2048 + L * 1024 + l16);
                    }
                    mbar_wait(bar + B_SM, t & 1);
                    mbar_wait(bar + B_SU, t & 1);
                    TR(3);
                    {
                        const uint2 x = lds64(st + 1024 + l8), y = lds64(st + 5120 + 1024 + l8);
                        s[4][0] += bf_lo(x.x) + bf_lo(y.x); s[4][1] += bf_hi(x.x) + bf_hi(y.x); s[4][2] += bf_lo(x.y) + bf_lo(y.y); s[4][3] += bf_hi(x.y) + bf_hi(y.y);
                    }
                    float mx0 = fmaxf(s[4][0], s[4][1]), mx1 = fmaxf(s[4][2], s[4][3]);
#pragma unroll
                    for (int n = 0; n < 4; n++) { mx0 = fmaxf(mx0, fmaxf(s[n][0], s[n][1])); mx1 = fmaxf(mx1, fmaxf(s[n][2], s[n][3])); }
#pragma unroll
                    for (int o = 1; o < 4; o <<= 1) { mx0 = fmaxf(mx0, __shfl_xor_sync(~0u, mx0, o)); mx1 = fmaxf(mx1, __shfl_xor_sync(~0u, mx1, o)); }
                    mx0 *= -SC; mx1 *= -SC;
                    float l0 = 0.f, l1 = 0.f;
                    uint32_t p[10];
#pragma unroll
                    for (int n = 0; n < 5; n++) {
                        const float e0 = ex2(fmaf(s[n][0], SC, mx0)), e1 = ex2(fmaf(s[n][1], SC, mx0));
                        const float e2 = ex2(fmaf(s[n][2], SC, mx1)), e3 = ex2(fmaf(s[n][3], SC, mx1));
                        l0 += e0 + e1; l1 += e2 + e3;
                        p[2 * n] = pk(e0, e1); p[2 * n + 1] = pk(e2, e3);
                    }
#pragma unroll
                    for (int o = 1; o < 4; o <<= 1) { l0 += __shfl_xor_sync(~0u, l0, o); l1 += __shfl_xor_sync(~0u, l1, o); }
                    l0 = rcp(l0); l1 = rcp(l1);
                    char* dst = reinterpret_cast<char*>(g_o + (((t & (RING - 1)) * 4 + warp) * 256 + h * 8 + 3 * r) * 32) + l16;
#pragma unroll
                    for (int m = 0; m < 3; m++) {
                        float o0[4] = {0, 0, 0, 0}, o1[4] = {0, 0, 0, 0};
                        v1[m] = lds128(sb + O_VX + (3 * r + m) * 2048 + L * 1024 + 512 + l16);
                        const uint2 vm = lds64(sb + O_VM + (3 * r + m) * 512 + l16 + L * 8);
                        mma8(o0, p[0], p[1], v0[m].x); mma8(o1, p[0], p[1], v0[m].y); mma8(o0, p[2], p[3], v0[m].z); mma8(o1, p[2], p[3], v0[m].w);
                        mma8(o0, p[4], p[5], v1[m].x); mma8(o1, p[4], p[5], v1[m].y); mma8(o0, p[6], p[7], v1[m].z); mma8(o1, p[6], p[7], v1[m].w);
                        mma8(o0, p[8], p[9], vm.x); mma8(o1, p[8], p[9], vm.y);
                        stg128p(dst + m * 512, pk(o0[0] * l0, o0[1] * l0), pk(o0[2] * l1, o0[3] * l1), pk(o1[0] * l0, o1[1] * l0), pk(o1[2] * l1, o1[3] * l1), m < nq && GON);
                    }
                    TR(4);
                }
            }
            if (t + 1 >= NT) break;
            {
                float d[32];
                mbar_wait(bar + B_X, (t + 1) & 1);
                bar_sync(7, 384);
                wg_fence();
                TR(6);
#pragma unroll
                for (int kk = 0; kk < PT_STEPS; kk++) {
                    const uint64_t db = mkdesc(hlo + ((kk >> 2) * H_KB + 2048 + (kk & 3) * 32) / 16, DESC_HI);
                    if (kk % 6 == 3) wgmma_ss64(d, mkdesc(wlo + (kk / 6) * 256, 16), db, 1);
                    else wgmma_rs64(d, a[AI(kk)], a[AI(kk) + 1], a[AI(kk) + 2], a[AI(kk) + 3], db, kk > 0);
                }
                wg_commit();
                asm volatile("{.reg .pred p, q; setp.ne.u32 p, %2, 0; setp.eq.and.u32 q, %1, 0, p; @p fence.acq_rel.gpu; bar.warp.sync 0xffffffff; @q red.relaxed.gpu.global.add.u32 [%0], 1;}"
                    :: "l"(ocnt + t * 64), "r"(l16), "r"((uint32_t)(t >= 0 && warp == 7)) : "memory");
                TR(5);
                if (warp == 7 && t >= 0) TRG(t, 0);
                mbar_wait(bar + B_WIN, (t + 1) & 1);
                wg_wait<0>();
                TR(7);
                mbar_arrive_all3(bar + B_XFREE, l16 >> 4);
                uint32_t p[16];
#pragma unroll
                for (int u = 0; u < 16; u++) p[u] = pk(d[2 * u], d[2 * u + 1]);
                if (kind == 2) {
#pragma unroll
                    for (int u = 0; u < 4; u++) sts128(adX + u * 512, p[4 * u], p[4 * u + 1], p[4 * u + 2], p[4 * u + 3]);
                } else {
#pragma unroll
                    for (int u = 0; u < 4; u++) stsm4t(adX + u * 512, p[4 * u], p[4 * u + 1], p[4 * u + 2], p[4 * u + 3]);
                }
                __syncwarp();
                asm volatile("{.reg .pred p; setp.eq.u32 p, %1, 0; @p mbarrier.arrive.shared.b64 _, [%0];}" :: "r"(bar + B_EP), "r"(l16) : "memory");
                if (kind == 2) {
                    fence_async_smem();
                    __syncwarp();
                    asm volatile("{.reg .pred p; setp.eq.u32 p, %5, 0;\n"
                        "@p cp.async.bulk.shared::cluster.shared::cta.mbarrier::complete_tx::bytes [%0], [%2], 2048, [%3];\n"
                        "@p cp.async.bulk.shared::cluster.shared::cta.mbarrier::complete_tx::bytes [%1], [%2], 2048, [%4];}"
                        :: "r"(adX0 + roff0), "r"(adX0 + roff1), "r"(adX0), "r"(bar + B_VX + roff0), "r"(bar + B_VX + roff1), "r"(l16) : "memory");
                }
                TR(8);
                {
                    const int lim = 16 * qh + (int)(l16 >> 6) - (int)((l16 >> 3) & 6);
#pragma unroll
                    for (int n = 0; n < 4; n++)
#pragma unroll
                        for (int j = 0; j < 4; j++) s[n][j] = (n == 0 && j >= 2) || 8 * (n - (j >> 1)) + (j & 1) <= lim ? 0.f : -1e30f;
                }
                if (warp < 4) {
                    mbar_wait(bar + B_EP, (t + 1) & 1);
#pragma unroll
                    for (int m = 0; m < 3; m++) {
                        const uint4 q = ldsm4(sb + O_QX + m * 2048 + warp * 512 + lq);
                        const uint4 k0 = ldsm4(sb + O_KX + m * 2048 + L * 1024 + l16);
                        const uint4 k1 = ldsm4(sb + O_KX + m * 2048 + L * 1024 + 512 + l16);
                        mma16(s[0], q.x, q.y, q.z, q.w, k0.x, k0.y);
                        mma16(s[1], q.x, q.y, q.z, q.w, k0.z, k0.w);
                        mma16(s[2], q.x, q.y, q.z, q.w, k1.x, k1.y);
                        mma16(s[3], q.x, q.y, q.z, q.w, k1.z, k1.w);
                    }
                    uint32_t w0 = pk(s[0][0], s[0][1]), w1 = pk(s[0][2], s[0][3]), w2 = pk(s[1][0], s[1][1]), w3 = pk(s[1][2], s[1][3]);
                    sta128(st + l16 + 5120 + roff0, w0, w1, w2, w3, bar + B_ST + roff0);
                    sta128(st + l16 + roff1, w0, w1, w2, w3, bar + B_ST + roff1);
                    w0 = pk(s[2][0], s[2][1]); w1 = pk(s[2][2], s[2][3]); w2 = pk(s[3][0], s[3][1]); w3 = pk(s[3][2], s[3][3]);
                    sta128p(st + l16 + 5120 + 512 + roff0, w0, w1, w2, w3, bar + B_ST + roff0, qh);
                    sta128p(st + l16 + 512 + roff1, w0, w1, w2, w3, bar + B_ST + roff1, qh);
                    TR(9);
                }
            }
        }
        bar_sync(7, 384);
        if (warp == 7) cnt_add(ocnt + (NT - 1) * 64, lane);
        cluster_sync();
    } else {
        asm volatile("setmaxnreg.dec.sync.aligned.u32 " RW ";");
        const int w = warp - 8;
        bar_sync(9, 384);
#pragma unroll 1
        for (int i = 0; i < 24; i++) {
            const int G = i >> 3, kk = i & 7;
            const uint32_t s = sb + O_STG_WO + (16 * kk + 2 * c) * 400 + (G * 64 + 16 * w + 4 * (g >> 1) + (g & 1)) * 2;
            uint32_t v[4];
#pragma unroll
            for (int q = 0; q < 4; q++) {
                const uint32_t s2 = s + (q & 1) * 3200 + (q >> 1) * 4;
                v[q] = lds16(s2) | (lds16(s2 + 400) << 16);
            }
            sts128(sb + O_WOF + (w * 24 + i) * 512 + lane * 16, v[0], v[1], v[2], v[3]);
        }
        bar_sync(6, 128);
        for (int i = tid - 256; i < (O_OX - O_KX) / 16; i += 128) sts128(sb + O_KX + i * 16, 0, 0, 0, 0);
        auto arm = [&]() {
            const uint32_t ln = l16 >> 4;
            mbar_expect(bar + B_VX + (ln & 3) * 8, ln == 0 ? nv_remote * 2048 : ln == 1 ? nv_remote * 512 + 2560 : ln == 2 ? 6144 : 2048, ln < 4);
        };
        if (w == 3) arm();
        cluster_sync();
        TR1(3);
        const int L = w >> 1, hf = w & 1;
        const uint32_t rd = hf ? roff1 : roff0;
        const uint32_t rzero = __shfl_sync(~0u, lds32(sb + O_ST + 512), 0);

        auto fetch_tile = [&](int u) {
            const bool a0 = u < NSEG && (XON || u < 8), a1 = u >= LAG && (XON || u < 8);
            mbar_expect(bar + B_X, ((int)a0 + (int)a1) * 36864, l16 == 0);
            const int kb = (l16 >> 5) * 3 + r, hl = (l16 >> 4) & 1;
            asm volatile("{.reg .pred p; setp.ne.u32 p, %4, 0; fence.proxy.async.global;\n"
                "@p cp.async.bulk.shared::cluster.global.mbarrier::complete_tx::bytes.multicast::cluster [%0], [%1], 4096, [%2], %3;}"
                :: "r"(sb + O_H + kb * H_KB + 2048 + hl * 4096), "l"(g_xt + ((u * 2 + hl) * 9 + kb) * 256), "r"(bar + B_X), "h"((uint16_t)7),
                   "r"((uint32_t)(l16 < 96 && (hl ? a1 : a0))) : "memory");
        };
        bar_arrive(7, 384);
        if (w < 3) bar_arrive(1 + w, 288);
        else {
            mbar_arrive_all3(bar + B_WIN, l16 >> 4);
            cnt_wait(g_cnt + C_X * 8, 64);
            TRG(0, 0);
            fetch_tile(0);
            TRG(0, 1);
            cnt_wait(g_cnt + (C_X + 1) * 8, 64);
            TRG(1, 0);
        }
#pragma unroll 1
        for (int t = 0; t < NT; t++) {
            TR_ON(t);
            OPQ();
            if (w == 3 && t + 1 < NT) { mbar_wait(bar + B_XFREE, t & 1); TR(6); fetch_tile(t + 1); TR(7); TRG(t + 1, 1); }
            mbar_wait(bar + B_EP, t & 1);
            uint4 kx[3][2], vx[4][2];
            const uint32_t lp = LSWAP;
#pragma unroll
            for (int m = 0; m < 3; m++) {
                kx[m][0] = ldsm4(sb + O_KX + m * 2048 + L * 1024 + lp);
                kx[m][1] = ldsm4(sb + O_KX + m * 2048 + L * 1024 + 512 + lp);
            }
            mbar_wait(bar + B_VX, t & 1);
#pragma unroll
            for (int m = 0; m < 8; m++) vx[m >> 1][m & 1] = lds128(sb + O_VX + (hf * 4 + (m >> 1)) * 2048 + L * 1024 + (m & 1) * 512 + l16);
            TR(0);
            bar_sync(4, 384);
            float s0[4] = {0, 0, 0, 0}, s1[4] = {0, 0, 0, 0}, sm[4] = {0, 0, 0, 0};
            {
                uint2 q[3]; uint4 km_[3];
#pragma unroll
                for (int m = 0; m < 3; m++) q[m] = ldsm2(sb + O_QM + m * 512 + L * 256 + l16);
#pragma unroll
                for (int m = 0; m < 3; m++) km_[m] = ldsm4(sb + O_KM + m * 512 + (lp ^ (L << 8)));
                bar_arrive(5, 256);
#pragma unroll
                for (int m = 0; m < 3; m++) {
                    mma16(s0, kx[m][0].x, kx[m][0].y, kx[m][0].z, kx[m][0].w, q[m].x, q[m].y);
                    mma16(s1, kx[m][1].x, kx[m][1].y, kx[m][1].z, kx[m][1].w, q[m].x, q[m].y);
                    mma16(sm, km_[m].x, km_[m].y, km_[m].z, km_[m].w, q[m].x, q[m].y);
                }
                const uint32_t ad = sb + O_SM + (1 - hf) * 1280 + L * 640 + rd;
                sta128(ad + l16, pk(s0[0], s0[1]), pk(s0[2], s0[3]), pk(s1[0], s1[1]), pk(s1[2], s1[3]), bar + B_SM + rd);
                sta32(ad + 512 + (l16 >> 2), pk(sm[0], sm[1]), bar + B_SM + rd);
            }
            TR(1);
            const uint32_t wof = sb + O_WOF + w * 24 * 512 + l16;
            uint4 bw[8];
#pragma unroll
            for (int kk = 0; kk < 8; kk++) bw[kk] = lds128(wof + kk * 512);
            mbar_wait(bar + B_SM, t & 1);
            TR(2);
            {
                const uint32_t ad = sb + O_SM + L * 640;
                const uint4 u = lds128(ad + l16), v = lds128(ad + 1280 + l16);
                const uint32_t x = lds32(ad + 512 + (l16 >> 2)), y = lds32(ad + 1280 + 512 + (l16 >> 2));
                s0[0] += bf_lo(u.x) + bf_lo(v.x); s0[1] += bf_hi(u.x) + bf_hi(v.x); s0[2] += bf_lo(u.y) + bf_lo(v.y); s0[3] += bf_hi(u.y) + bf_hi(v.y);
                s1[0] += bf_lo(u.z) + bf_lo(v.z); s1[1] += bf_hi(u.z) + bf_hi(v.z); s1[2] += bf_lo(u.w) + bf_lo(v.w); s1[3] += bf_hi(u.w) + bf_hi(v.w);
                sm[0] += bf_lo(x) + bf_lo(y); sm[1] += bf_hi(x) + bf_hi(y);
            }
            uint2 vm[4];
#pragma unroll
            for (int m = 0; m < 4; m++) vm[m] = lds64(sb + O_VM + (hf * 4 + m) * 512 + l16 + L * 8);
            float mx0 = fmaxf(fmaxf(fmaxf(s0[0], s0[2]), fmaxf(s1[0], s1[2])), sm[0]);
            float mx1 = fmaxf(fmaxf(fmaxf(s0[1], s0[3]), fmaxf(s1[1], s1[3])), sm[1]);
#pragma unroll
            for (int o = 4; o < 32; o <<= 1) { mx0 = fmaxf(mx0, __shfl_xor_sync(~0u, mx0, o)); mx1 = fmaxf(mx1, __shfl_xor_sync(~0u, mx1, o)); }
            mx0 *= -SC; mx1 *= -SC;
            s0[0] = ex2(fmaf(s0[0], SC, mx0)); s0[1] = ex2(fmaf(s0[1], SC, mx1));
            s0[2] = ex2(fmaf(s0[2], SC, mx0)); s0[3] = ex2(fmaf(s0[3], SC, mx1));
            const uint32_t pb0 = movm(pk(s0[0], s0[1])), pb1 = movm(pk(s0[2], s0[3]));
            s1[0] = ex2(fmaf(s1[0], SC, mx0)); s1[1] = ex2(fmaf(s1[1], SC, mx1));
            s1[2] = ex2(fmaf(s1[2], SC, mx0)); s1[3] = ex2(fmaf(s1[3], SC, mx1));
            const uint32_t pb2 = movm(pk(s1[0], s1[1])), pb3 = movm(pk(s1[2], s1[3]));
            sm[0] = ex2(fmaf(sm[0], SC, mx0)); sm[1] = ex2(fmaf(sm[1], SC, mx1));
            const uint32_t pm = movm(pk(sm[0], sm[1]));
            float l0 = (s0[0] + s0[2]) + (s1[0] + s1[2]) + sm[0], l1 = (s0[1] + s0[3]) + (s1[1] + s1[3]) + sm[1];
            float o[4][4];
#pragma unroll
            for (int m = 0; m < 4; m++) { o[m][0] = o[m][1] = o[m][2] = o[m][3] = 0.f; mma16(o[m], vx[m][0].x, vx[m][0].y, vx[m][0].z, vx[m][0].w, pb0, pb1); }
            l0 += __shfl_xor_sync(~0u, l0, 4); l1 += __shfl_xor_sync(~0u, l1, 4);
#pragma unroll
            for (int m = 0; m < 4; m++) mma16(o[m], vx[m][1].x, vx[m][1].y, vx[m][1].z, vx[m][1].w, pb2, pb3);
            l0 += __shfl_xor_sync(~0u, l0, 8); l1 += __shfl_xor_sync(~0u, l1, 8);
#pragma unroll
            for (int m = 0; m < 4; m++) mma8(o[m], vm[m].x, vm[m].y, pm);
            l0 += __shfl_xor_sync(~0u, l0, 16); l1 += __shfl_xor_sync(~0u, l1, 16);
            l0 = rcp(l0); l1 = rcp(l1);
#pragma unroll
            for (int m = 0; m < 4; m += 2)
                stsm4t(sb + O_OX + (hf * 4 + m) * 512 + (L ^ ((h >> 2) & 1)) * 128   + ((l16 & 0x180) << 1) + (l16 & 0x70),
                       pk(o[m][0] * l0, o[m][1] * l1), pk(o[m][2] * l0, o[m][3] * l1), pk(o[m + 1][0] * l0, o[m + 1][1] * l1), pk(o[m + 1][2] * l0, o[m + 1][3] * l1));
            TR(3);
            char* const pdst = reinterpret_cast<char*>(g_mp + (r * 32 + w * 8) * 384 + h * 4) + ((l16 >> 6) * 6144 + (l16 & 48));
            bar_sync(6, 128);
            uint4 ao[8];
#pragma unroll
            for (int kk = 0; kk < 8; kk++) ao[kk] = ldsm4(sb + O_OX + kk * 512 + l16);
            uint4 b1[8];
            sched_fence(rzero, 1);
            const uint32_t tag = (t & 1) ^ 1;
#pragma unroll
            for (int G = 0; G < 3; G++) {
                float e[4][4];
#pragma unroll
                for (int q = 0; q < 4; q++) e[q][0] = e[q][1] = e[q][2] = e[q][3] = 0.f;
#pragma unroll
                for (int kk = 0; kk < 8; kk++) {
                    const uint4 bb = G == 1 ? b1[kk] : bw[kk];
                    mma16(e[(kk & 1) * 2], ao[kk].x, ao[kk].y, ao[kk].z, ao[kk].w, bb.x, bb.y);
                    mma16(e[(kk & 1) * 2 + 1], ao[kk].x, ao[kk].y, ao[kk].z, ao[kk].w, bb.z, bb.w);
                    if (G < 2 && kk == 1) {
#pragma unroll
                        for (int j = 0; j < 8; j++) (G == 0 ? b1[j] : bw[j]) = lds128v(wof + 4096 * (G + 1) + j * 512);
                        sched_fence(rzero, 2 + G);
                    }
                }
                stg_pkt(pdst + G * 2048, (pk(e[0][0] + e[2][0], e[0][1] + e[2][1]) & ~1u) | tag, pk(e[1][0] + e[3][0], e[1][1] + e[3][1]),
                        pk(e[0][2] + e[2][2], e[0][3] + e[2][3]), pk(e[1][2] + e[3][2], e[1][3] + e[3][3]));
                if (G == 0) sched_fence(rzero, 4);
            }
            TR(4);
            if (w < 3) {
                bar_arrive(7, 384);
                if (t + 1 < NT) {
                    OPQ();
                    const char* const rsrc = reinterpret_cast<const char*>(g_mp + b * 384 + w * 128) + l16;
                    const bool fresh = t + 1 <= LAG && l16 >= 256;
                    uint2 m0v = make_uint2(0, 0);
                    if (t + 1 <= LAG) m0v = *reinterpret_cast<const uint2*>(mem0 + (b & 7) * DM + 192 * w + 16 * (b >> 3) + ((l16 >> 2) & 12));
                    delay(DLY1);
                    uint4 v[4];
#pragma unroll
                    for (int i = 0; i < 4; i++) v[i] = ldg_pkt(rsrc + i * 512);
                    for (int n = 0; __any_sync(~0u, ((v[0].x ^ tag) | (v[1].x ^ tag) | (v[2].x ^ tag) | (v[3].x ^ tag)) & 1); n++) {
#pragma unroll
                        for (int i = 0; i < 4; i++) ldg_pkt_if(v[i], rsrc + i * 512, (v[i].x ^ tag) & 1);
                        fault_if(n > POLL_LIMIT, n);
                    }
                    TR(5);
                    float s[8];
                    s[0] = (bf_lo(v[0].x) + bf_lo(v[1].x)) + (bf_lo(v[2].x) + bf_lo(v[3].x)); s[1] = (bf_hi(v[0].x) + bf_hi(v[1].x)) + (bf_hi(v[2].x) + bf_hi(v[3].x));
                    s[2] = (bf_lo(v[0].y) + bf_lo(v[1].y)) + (bf_lo(v[2].y) + bf_lo(v[3].y)); s[3] = (bf_hi(v[0].y) + bf_hi(v[1].y)) + (bf_hi(v[2].y) + bf_hi(v[3].y));
                    s[4] = (bf_lo(v[0].z) + bf_lo(v[1].z)) + (bf_lo(v[2].z) + bf_lo(v[3].z)); s[5] = (bf_hi(v[0].z) + bf_hi(v[1].z)) + (bf_hi(v[2].z) + bf_hi(v[3].z));
                    s[6] = (bf_lo(v[0].w) + bf_lo(v[1].w)) + (bf_lo(v[2].w) + bf_lo(v[3].w)); s[7] = (bf_hi(v[0].w) + bf_hi(v[1].w)) + (bf_hi(v[2].w) + bf_hi(v[3].w));
#pragma unroll
                    for (int j = 0; j < 4; j++) s[j] += __shfl_xor_sync(~0u, s[j + 4], 16);
#pragma unroll
                    for (int of = 4; of < 16; of <<= 1)
#pragma unroll
                        for (int j = 0; j < 4; j++) s[j] += __shfl_xor_sync(~0u, s[j], of);
                    char* const mem_t = reinterpret_cast<char*>(g_mem + t * 1152 + w * 384);
                    stg_pkt8(mem_t + (b >> 3) * 512 + (((b & 7) >> 1) | ((b & 1) << 2)) * 32 + ((l16 & 256) + ((l16 & 48) >> 1)),
                             fresh ? m0v.x : pk(s[0], s[1]), fresh ? m0v.y : pk(s[2], s[3]), (l16 & 0xc0) == 0);
                    TR(6);
                    delay(DLY2);
                    const char* src = mem_t + l16;
                    const uint32_t gr = ((l16 >> 4) & 6) | ((l16 >> 7) & 1);
                    const uint32_t gdst = sb + O_H + 3 * w * H_KB + ((l16 & 256) << 2) + gr * 128 + ((l16 & 16) ^ (gr << 4));
                    uint4 x[12];
#pragma unroll
                    for (int i = 0; i < 12; i++) x[i] = ldg_pkt(src + i * 512);
                    for (int n = 0;; n++) {
                        uint32_t mx = 0;
#pragma unroll
                        for (int i = 0; i < 12; i++) mx = max(mx, max(x[i].x, x[i].z));
                        if (!__any_sync(~0u, mx == 0xffffffffu)) break;
#pragma unroll
                        for (int i = 0; i < 12; i++) ldg_pkt_if(x[i], src + i * 512, max(x[i].x, x[i].z) == 0xffffffffu);
                        fault_if(n > POLL_LIMIT, n);
                    }
                    TR(7);
#pragma unroll
                    for (int i = 0; i < 12; i++) sts128((gdst ^ ((i & 3) << 5)) + (i >> 2) * H_KB, x[i].x, x[i].y, x[i].z, x[i].w);
                    fence_async_smem();
                    bar_arrive(1 + w, 288);
                    TR(8);
                }
            } else {
                bar_sync(7, 384);
                if (t + 1 < NT) {
                    arm();
                    __syncwarp();
                    mbar_arrive_all3(bar + B_WIN, l16 >> 4);
                    if (t + 2 < NT) { cnt_wait(g_cnt + (C_X + t + 2) * 8, 64); TRG(t + 2, 0); }
                }
                TR(5);
            }
        }
        cluster_sync();
    }
    TR_DUMP(b);
}

namespace ka {
constexpr int O_WA = 196608;
constexpr int A_SBO = 9232;
constexpr int O_RING = 194560;
constexpr int O_BAR = 230400;
constexpr int SMEM = O_BAR + 128 + 1024;
constexpr float SC = 0.23570226039551584f * 1.4426950408889634f;
}

template <int NP>
DEVI void row_task(const uint4* res, const uint4* part, uint4* xout, char* img, int pos, int lane) {
    const bool on = lane < 24;
    const int ln = on ? lane : 0;
    uint4 rv[3], pv[NP > 0 ? NP * 3 : 1];
#pragma unroll
    for (int i = 0; i < 3; i++) rv[i] = ldg128(res + i * 24 + ln);
#pragma unroll
    for (int i = 0; i < NP * 3; i++) pv[i] = ldg128(part + i * 24 + ln);
    float x[24];
#pragma unroll
    for (int i = 0; i < 3; i++) {
        x[8 * i] = bf_lo(rv[i].x); x[8 * i + 1] = bf_hi(rv[i].x); x[8 * i + 2] = bf_lo(rv[i].y); x[8 * i + 3] = bf_hi(rv[i].y);
        x[8 * i + 4] = bf_lo(rv[i].z); x[8 * i + 5] = bf_hi(rv[i].z); x[8 * i + 6] = bf_lo(rv[i].w); x[8 * i + 7] = bf_hi(rv[i].w);
    }
    if (NP > 0) {
#pragma unroll
        for (int q = 0; q < NP * 3; q++) {
            const int i = q % 3;
            x[8 * i] += bf_lo(pv[q].x); x[8 * i + 1] += bf_hi(pv[q].x); x[8 * i + 2] += bf_lo(pv[q].y); x[8 * i + 3] += bf_hi(pv[q].y);
            x[8 * i + 4] += bf_lo(pv[q].z); x[8 * i + 5] += bf_hi(pv[q].z); x[8 * i + 6] += bf_lo(pv[q].w); x[8 * i + 7] += bf_hi(pv[q].w);
        }
#pragma unroll
        for (int i = 0; i < 3; i++) {
            uint32_t w[4];
#pragma unroll
            for (int j = 0; j < 4; j++) { w[j] = pk(x[8 * i + 2 * j], x[8 * i + 2 * j + 1]); x[8 * i + 2 * j] = bf_lo(w[j]); x[8 * i + 2 * j + 1] = bf_hi(w[j]); }
            stg128p(xout + i * 24 + ln, w[0], w[1], w[2], w[3], on);
        }
    }
    if (img) {
        float s = 0.f;
#pragma unroll
        for (int j = 0; j < 24; j++) s += x[j];
        if (!on) s = 0.f;
#pragma unroll
        for (int o = 1; o < 32; o <<= 1) s += __shfl_xor_sync(~0u, s, o);
        const float mean = s * (1.f / DM);
        float v = 0.f;
#pragma unroll
        for (int j = 0; j < 24; j++) { x[j] -= mean; v = fmaf(x[j], x[j], v); }
        if (!on) v = 0.f;
#pragma unroll
        for (int o = 1; o < 32; o <<= 1) v += __shfl_xor_sync(~0u, v, o);
        const float rs = rsqrtf(v * (1.f / DM) + 1e-5f);
        char* dst = img + (ln >> 3) * 4096 + pos * 128 + (((ln ^ pos) & 7) << 4);
#pragma unroll
        for (int i = 0; i < 3; i++)
            stg128p(dst + i * 12288, pk(x[8 * i] * rs, x[8 * i + 1] * rs), pk(x[8 * i + 2] * rs, x[8 * i + 3] * rs),
                    pk(x[8 * i + 4] * rs, x[8 * i + 5] * rs), pk(x[8 * i + 6] * rs, x[8 * i + 7] * rs), on);
    }
}

__global__ void __launch_bounds__(384, 1)
k_aux(const __nv_bfloat16* __restrict__ x0, const __nv_bfloat16* __restrict__ wqkv, const __nv_bfloat16* __restrict__ wo,
      const __nv_bfloat16* __restrict__ Wo, __nv_bfloat16* __restrict__ out) {
    using namespace ka;
    extern __shared__ unsigned char smem_raw[];
    const uint32_t sb = (smem_u32(smem_raw) + 1023) & ~1023u;
    const int tid = threadIdx.x, lane = tid & 31, warp = __shfl_sync(~0u, tid >> 5, 0), g = lane >> 2, c = lane & 3;
    const int b = blockIdx.x;
    const uint32_t bar = sb + O_BAR;

    if (warp >= 8) {
        asm volatile("setmaxnreg.dec.sync.aligned.u32 128;");
        const int rw = b * 4 + warp - 8;
        const uint4* xin = reinterpret_cast<const uint4*>(x0);
#pragma unroll 1
        for (int row = rw; row < 2048; row += 16) {
            row_task<0>(xin + row * 72, nullptr, nullptr, reinterpret_cast<char*>(g_xa + (row >> 5) * 4608), (row & 1) * 16 + ((row & 31) >> 1), lane);
            cnt_add(g_cnt + (C_N0 + (row >> 5)) * 8, lane);
            if (rw < 128) break;
        }
        const int R = rw & 63, f = R >> 5, i = R & 31;
        if (rw < 64) {
#pragma unroll 1
            for (int u = 0; u < NT; u++) {
                const int seg = u - f * LAG, row = seg * 32 + i;
                if (seg >= 0 && seg < NSEG) {
                    cnt_wait(g_cnt + (C_WB + u) * 8, 24);
                    TRG(u, 0);
                    row_task<8>(g_x + (f * 4096 + row) * 72, g_pb + ((u & (RING - 1)) * 64 + R) * 576,
                                f ? reinterpret_cast<uint4*>(out) + row * 72 : g_x + (2048 + row) * 72,
                                f ? nullptr : reinterpret_cast<char*>(g_xa + (u + LAG) * 4608 + 2304), (i & 1) * 16 + (i >> 1), lane);
                    TRG(u, 1);
                }
                cnt_add(g_cnt + (C_RB + u) * 8, lane);
                TRG(u, 2);
            }
        } else if (rw < 128) {
#pragma unroll 1
            for (int u = 0; u < NT; u++) {
                const int seg = u - f * LAG, row = seg * 32 + i;
                if (seg >= 0 && seg < NSEG) {
                    cnt_wait(g_cnt + (C_WA + u) * 8, 24);
                    TRG(u, 0);
                    row_task<4>((f ? g_x + 2048 * 72 : xin) + row * 72, g_pa + ((u & (RING - 1)) * 64 + R) * 288,
                                g_x + (f * 4096 + row) * 72, reinterpret_cast<char*>(g_xt + u * 4608 + f * 2304), i, lane);
                    TRG(u, 1);
                }
                cnt_add(g_cnt + (C_X + u) * 8, lane);
                TRG(u, 2);
            }
        }
        return;
    }
    if (b == 35) return;

    if (b < 24) {
        {
            const int kq = b / 6, nq = b % 6;
            uint4 v[9];
#pragma unroll
            for (int q = 0; q < 9; q++) {
                const int it = q * 8 + warp, kr = (it / 3) * 8 + g, s = kq * 11 + (kr >> 4), a = s >> 2, j = s & 3, e = kr & 15;
                const int head = 3 * a + (j < 3 ? j : e >> 1), row = head * 18 + (j < 3 ? e : 16 + (e & 1));
                v[q] = make_uint4(0, 0, 0, 0);
                if (it < 66 && head < 32 && (j < 3 || e < 6)) v[q] = *reinterpret_cast<const uint4*>(wo + row * DM + nq * 96 + (it % 3) * 32 + c * 8);
            }
#pragma unroll
            for (int q = 0; q < 9; q++) {
                const int it = q * 8 + warp;
                const uint32_t ad = sb + O_WA + (it % 3) * 4 * 2816 + (it / 3) * 128 + lane * 4;
                if (it < 66) { sts32(ad, v[q].x); sts32(ad + 2816, v[q].y); sts32(ad + 2 * 2816, v[q].z); sts32(ad + 3 * 2816, v[q].w); }
            }
        }
        const int kg = b / 3, ng = b % 3;
#pragma unroll 1
        for (int bt = 0; bt < 2; bt++) {
            uint4 v[24];
#pragma unroll
            for (int q = 0; q < 24; q++)
                v[q] = *reinterpret_cast<const uint4*>(Wo + (size_t)(kg * 512 + ((bt * 4 + q / 6) * 8 + warp) * 8 + g) * DM + ng * 192 + (q % 6) * 32 + c * 8);
#pragma unroll
            for (int q = 0; q < 24; q++) {
                const uint32_t ad = sb + (q % 6) * 4 * 8192 + ((bt * 4 + q / 6) * 8 + warp) * 128 + lane * 4;
                sts32(ad, v[q].x); sts32(ad + 8192, v[q].y); sts32(ad + 2 * 8192, v[q].z); sts32(ad + 3 * 8192, v[q].w);
            }
        }
    } else {
        const int a = b - 24, nw = a == 10 ? 18 : 27, ch = lane & 7, off = (a * 108) & 15;
        int d0[4], dw[4];
#pragma unroll
        for (int j = 0; j < 4; j++) {
            const int w = ch * 4 + j - (off >> 2), hh = w / 9, jj = w % 9;
            d0[j] = w < 0 || w >= nw ? -1 : jj < 8 ? (hh * 2 + (jj >> 2)) * A_SBO + (jj & 3) * 4 : 18 * A_SBO + hh * 4;
            dw[j] = jj < 8 ? 6 * A_SBO : A_SBO;
        }
        const bool any = ch * 4 - (off >> 2) < nw;
        const char* src = reinterpret_cast<const char*>(wqkv) + (warp * 4 + (lane >> 3)) * 3456 + a * 108 - off + ch * 16;
#pragma unroll 1
        for (int wh = 0; wh < 3; wh++) {
            uint4 v[18];
#pragma unroll
            for (int q = 0; q < 18; q++) { v[q] = make_uint4(0, 0, 0, 0); if (any) v[q] = *reinterpret_cast<const uint4*>(src + q * 32 * 3456 + wh * 1152); }
            if (wh == 0) {
                for (int i = tid; i < 3 * A_SBO / 16; i += 256) {
                    sts128(sb + 18 * A_SBO + i * 16, 0, 0, 0, 0);
                    if (a == 10 && i < 2 * A_SBO / 16) { sts128(sb + 4 * A_SBO + i * 16, 0, 0, 0, 0); sts128(sb + 10 * A_SBO + i * 16, 0, 0, 0, 0); sts128(sb + 16 * A_SBO + i * 16, 0, 0, 0, 0); }
                }
                for (int i = tid; i < 2048; i += 256) sts128(sb + O_RING + i * 16, 0, 0, 0, 0);
                if (tid == 0) for (int i = 0; i < 4; i++) { mbar_init(bar + i * 8, 1); mbar_init(bar + 32 + i * 8, 4); }
                bar_sync(1, 256);
            }
            const uint32_t ad = sb + (warp * 4 + (lane >> 3)) * 16;
#pragma unroll
            for (int q = 0; q < 18; q++) {
                if (d0[0] >= 0) sts32(ad + d0[0] + wh * dw[0] + q * 512, v[q].x);
                if (d0[1] >= 0) sts32(ad + d0[1] + wh * dw[1] + q * 512, v[q].y);
                if (d0[2] >= 0) sts32(ad + d0[2] + wh * dw[2] + q * 512, v[q].z);
                if (d0[3] >= 0) sts32(ad + d0[3] + wh * dw[3] + q * 512, v[q].w);
            }
        }
    }
    fence_async_smem();
    bar_sync(1, 256);
    const int wq = warp & 3;

    if (warp < 4) {
        asm volatile("setmaxnreg.inc.sync.aligned.u32 256;");
        if (b < 24) {
            const int kg = b / 3, ng = b % 3;
            const uint32_t blo = ((sb >> 4) & 0x3fff) | (8u << 16);
#pragma unroll 1
            for (int u = 0; u < NT; u++) {
                cnt_wait(g_cnt + (C_O + u * 8 + kg) * 8, 12);
                TRG(u, 0);
                const uint4* src = g_o + (((u & (RING - 1)) * 4 + wq) * 256 + kg * 32) * 32 + lane;
                uint4 a[32];
                float d[96];
#pragma unroll
                for (int i = 0; i < 32; i++) a[i] = ldg128(src + i * 32);
#pragma unroll
                for (int i = 0; i < 32; i++) {
                    if (i % 8 == 0) wg_fence();
                    wgmma_rs192t(d, a[i].x, a[i].y, a[i].z, a[i].w, mkdesc(blo + i * 16, 512), i > 0);
                    if (i == 31) wg_commit();
                }
                wg_wait<0>();
                TRG(u, 1);
                uint4* dst = g_pb + (((u & (RING - 1)) * 64 + wq * 16 + g) * 8 + kg) * 72 + ng * 24 + c;
#pragma unroll
                for (int m = 0; m < 6; m++) {
                    stg128(dst + 4 * m, pk(d[16 * m], d[16 * m + 1]), pk(d[16 * m + 4], d[16 * m + 5]), pk(d[16 * m + 8], d[16 * m + 9]), pk(d[16 * m + 12], d[16 * m + 13]));
                    stg128(dst + 4 * m + 8 * 576, pk(d[16 * m + 2], d[16 * m + 3]), pk(d[16 * m + 6], d[16 * m + 7]), pk(d[16 * m + 10], d[16 * m + 11]), pk(d[16 * m + 14], d[16 * m + 15]));
                }
                bar_sync(2, 128);
                TRG(u, 2);
                if (wq == (u & 3)) cnt_add(g_cnt + (C_WB + u) * 8, lane);
                TRG(u, 3);
            }
        } else {
            const int a = b - 24, f = wq >> 1;
            const uint32_t blo = ((sb >> 4) & 0x3fff) | (8u << 16), alo = (((sb + O_RING) >> 4) & 0x3fff) | (1u << 16);
            const bool m0 = 2 * c <= g, m1 = 2 * c + 1 <= g;
            const uint32_t M = (m0 ? 0xffffu : 0u) | (m1 ? 0xffff0000u : 0u);
            uint32_t kh[7], vh[7];
#pragma unroll
            for (int i = 0; i < 7; i++) kh[i] = vh[i] = 0;
            int it = 0;
#pragma unroll 1
            for (int u = 0; u < NT; u++) {
                float d[84];
#pragma unroll 1
                for (int kb = 0; kb < 9; kb++, it++) {
                    mbar_wait(bar + (it & 3) * 8, (it >> 2) & 1);
                    if (kb == 0) TRG(u, 0);
                    wg_fence();
#pragma unroll
                    for (int q = 0; q < 4; q++)
                        wgmma_ss168t(d, mkdesc(alo + (it & 3) * 512 + q * 2, km::DESC_HI), mkdesc(blo + (kb * 4 + q) * 16, A_SBO >> 4), kb + q > 0);
                    wg_commit();
                    wg_wait<1>();
                    mbar_arrive(bar + 32 + ((it - 1) & 3) * 8, lane == 0 && kb > 0);
                }
                wg_wait<0>();
                mbar_arrive(bar + 32 + ((it - 1) & 3) * 8, lane == 0);
                TRG(u, 1);
                const bool first = u == f * LAG;
                const uint32_t qt0 = pk(d[72], d[73]), qt1 = pk(d[74], d[75]), kt0 = pk(d[76], d[77]), kt1 = pk(d[78], d[79]);
                const uint32_t vt0 = movm(pk(d[80], d[81])), vt1 = movm(pk(d[82], d[83]));
                float ot[4] = {0, 0, 0, 0};
                uint4* dst = g_oa + (((u & (RING - 1)) * 4 + wq) * 44 + a * 4) * 32 + lane;
#pragma unroll
                for (int h = 0; h < 3; h++) {
                    const float* q = d + 8 * h; const float* k = d + 24 + 8 * h; const float* v = d + 48 + 8 * h;
                    const uint32_t q0 = pk(q[0], q[1]), q1 = pk(q[2], q[3]), q2 = pk(q[4], q[5]), q3 = pk(q[6], q[7]);
                    const uint32_t k0 = pk(k[0], k[1]), k1 = pk(k[4], k[5]), k2 = pk(k[2], k[3]), k3 = pk(k[6], k[7]);
                    const uint32_t v0 = movm(pk(v[0], v[1])), v1 = movm(pk(v[2], v[3])), v2 = movm(pk(v[4], v[5])), v3 = movm(pk(v[6], v[7]));
                    const uint32_t t0 = c == h ? qt0 : 0, t1 = c == h ? qt1 : 0;
                    float sp[4] = {0, 0, 0, 0}, sl[4] = {0, 0, 0, 0}, sh[4] = {0, 0, 0, 0};
                    mma16(sp, q0, q1, q2, q3, kh[2 * h], kh[2 * h + 1]); mma16(sl, q0, q1, q2, q3, k0, k1); mma16(sh, q0, q1, q2, q3, k2, k3);
                    mma8(sp, t0, t1, kh[6]); mma8(sl, t0, t1, kt0); mma8(sh, t0, t1, kt1);
                    float x0_ = m0 ? sl[0] : first ? -INFINITY : sp[0], x1_ = m1 ? sl[1] : first ? -INFINITY : sp[1];
                    float y0_ = m0 ? sh[2] : sl[2], y1_ = m1 ? sh[3] : sl[3];
                    float mx = fmaxf(x0_, x1_), my = fmaxf(y0_, y1_);
#pragma unroll
                    for (int o = 1; o < 4; o <<= 1) { mx = fmaxf(mx, __shfl_xor_sync(~0u, mx, o)); my = fmaxf(my, __shfl_xor_sync(~0u, my, o)); }
                    mx *= -SC; my *= -SC;
                    x0_ = ex2(fmaf(x0_, SC, mx)); x1_ = ex2(fmaf(x1_, SC, mx)); y0_ = ex2(fmaf(y0_, SC, my)); y1_ = ex2(fmaf(y1_, SC, my));
                    float lx = x0_ + x1_, ly = y0_ + y1_;
#pragma unroll
                    for (int o = 1; o < 4; o <<= 1) { lx += __shfl_xor_sync(~0u, lx, o); ly += __shfl_xor_sync(~0u, ly, o); }
                    lx = rcp(lx); ly = rcp(ly);
                    const uint32_t px = pk(x0_ * lx, x1_ * lx), py = pk(y0_ * ly, y1_ * ly);
                    const uint32_t hm = (g >> 1) == h ? ~0u : 0u;
                    float o0[4] = {0, 0, 0, 0}, o1[4] = {0, 0, 0, 0};
                    mma16(o0, px & M, py & ~M, 0, py & M, v0, v1); mma16(o1, px & M, py & ~M, 0, py & M, v2, v3);
                    mma16(ot, px & M, py & ~M, 0, py & M, vt0 & hm, vt1 & hm);
                    mma8(o0, px & ~M, 0, vh[2 * h]); mma8(o1, px & ~M, 0, vh[2 * h + 1]); mma8(ot, px & ~M, 0, vh[6] & hm);
                    stg128(dst + h * 32, pk(o0[0], o0[1]), pk(o0[2], o0[3]), pk(o1[0], o1[1]), pk(o1[2], o1[3]));
                    kh[2 * h] = k2; kh[2 * h + 1] = k3; vh[2 * h] = v1; vh[2 * h + 1] = v3;
                }
                kh[6] = kt1; vh[6] = vt1;
                stg128(dst + 96, pk(ot[0], ot[1]), pk(ot[2], ot[3]), 0, 0);
                TRG(u, 2);
                bar_arrive(2 + (u & 1), 160);
            }
        }
    } else {
        asm volatile("setmaxnreg.dec.sync.aligned.u32 120;");
        if (b < 24) {
            const int kq = b / 6, nq = b % 6;
            const uint32_t blo = (((sb + O_WA) >> 4) & 0x3fff) | (8u << 16);
#pragma unroll 1
            for (int u = 0; u < NT; u++) {
                cnt_wait(g_cnt + (C_A + u) * 8, 11);
                TRG(u, 0);
                const uint4* src = g_oa + (((u & (RING - 1)) * 4 + wq) * 44 + kq * 11) * 32 + lane;
                uint4 a[11];
                float d[48];
#pragma unroll
                for (int i = 0; i < 11; i++) a[i] = ldg128(src + i * 32);
                wg_fence();
#pragma unroll
                for (int i = 0; i < 11; i++) wgmma_rs96t(d, a[i].x, a[i].y, a[i].z, a[i].w, mkdesc(blo + i * 16, 176), i > 0);
                wg_commit();
                wg_wait<0>();
                TRG(u, 1);
                uint4* dst = g_pa + (((u & (RING - 1)) * 64 + (wq >> 1) * 32 + 2 * g + (wq & 1)) * 4 + kq) * 72 + nq * 12 + c;
#pragma unroll
                for (int m = 0; m < 3; m++) {
                    stg128(dst + 4 * m, pk(d[16 * m], d[16 * m + 1]), pk(d[16 * m + 4], d[16 * m + 5]), pk(d[16 * m + 8], d[16 * m + 9]), pk(d[16 * m + 12], d[16 * m + 13]));
                    stg128(dst + 4 * m + 16 * 288, pk(d[16 * m + 2], d[16 * m + 3]), pk(d[16 * m + 6], d[16 * m + 7]), pk(d[16 * m + 10], d[16 * m + 11]), pk(d[16 * m + 14], d[16 * m + 15]));
                }
                bar_sync(3, 128);
                TRG(u, 2);
                if (wq == 0) cnt_add(g_cnt + (C_WA + u) * 8, lane);
                TRG(u, 3);
            }
        } else if (warp == 4) {
            int it = 0;
#pragma unroll 1
            for (int u = 0; u < NT; u++) {
                if (u < NSEG) cnt_wait(g_cnt + (C_N0 + u) * 8, 32);
                if (u >= LAG) cnt_wait(g_cnt + (C_RB + u - LAG) * 8, 64);
                TRG(u, 0);
                asm volatile("fence.proxy.async.global;" ::: "memory");
                const bool on = lane == 0 ? u < NSEG : lane == 1 && u >= LAG;
#pragma unroll 1
                for (int kb = 0; kb < 9; kb++, it++) {
                    if (it >= 4) mbar_wait(bar + 32 + (it & 3) * 8, ((it >> 2) - 1) & 1);
                    mbar_expect(bar + (it & 3) * 8, u < NSEG && u >= LAG ? 8192 : 4096, lane == 0);
                    asm volatile("{.reg .pred p; setp.ne.u32 p, %3, 0; @p cp.async.bulk.shared::cluster.global.mbarrier::complete_tx::bytes [%0], [%1], 4096, [%2];}"
                        :: "r"(sb + O_RING + (it & 3) * 8192 + (lane & 1) * 4096), "l"(g_xa + u * 4608 + (lane & 1) * 2304 + kb * 256), "r"(bar + (it & 3) * 8), "r"((uint32_t)on) : "memory");
                }
            }
        } else if (warp == 5) {
#pragma unroll 1
            for (int u = 0; u < NT; u++) {
                bar_sync(2 + (u & 1), 160);
                cnt_add(g_cnt + (C_A + u) * 8, lane);
                TRG(u, 0);
            }
        }
    }
}

__global__ void k_init() {
    const int i = blockIdx.x * blockDim.x + threadIdx.x;
    if (i < NT * 1152) g_mem[i] = make_uint4(~0u, ~0u, ~0u, ~0u);
    if (i < 96 * 3 * 128) g_mp[i] = make_uint4(0, 0, 0, 0);
    if (i < C_TOTAL * 8) g_cnt[i] = 0;
}

extern "C" void kernel_launch(void* const* d_in, const int* in_sizes, int n_in, void* d_out, int out_size) {
    const __nv_bfloat16* x = (const __nv_bfloat16*)d_in[0];
    const __nv_bfloat16* wqkv = (const __nv_bfloat16*)d_in[1];
    const __nv_bfloat16* wo = (const __nv_bfloat16*)d_in[2];
    const __nv_bfloat16* mem0 = (const __nv_bfloat16*)d_in[4];
    const __nv_bfloat16* Wq = (const __nv_bfloat16*)d_in[5];
    const __nv_bfloat16* Wk = (const __nv_bfloat16*)d_in[6];
    const __nv_bfloat16* Wv = (const __nv_bfloat16*)d_in[7];
    const __nv_bfloat16* Wo = (const __nv_bfloat16*)d_in[8];
    cudaFuncSetAttribute(k_main, cudaFuncAttributeMaxDynamicSharedMemorySize, km::SMEM);
    cudaFuncSetAttribute(k_aux, cudaFuncAttributeMaxDynamicSharedMemorySize, ka::SMEM);
    cudaStream_t s = cudaStreamPerThread;
    k_init<<<(NT * 1152 + 255) / 256, 256, 0, s>>>();
    k_main<<<96, 384, km::SMEM, s>>>(mem0, Wq, Wk, Wv, Wo);
    cudaLaunchConfig_t cfg = {};
    cudaLaunchAttribute at[1];
    at[0].id = cudaLaunchAttributeProgrammaticStreamSerialization;
    at[0].val.programmaticStreamSerializationAllowed = 1;
    cfg.stream = s; cfg.attrs = at; cfg.numAttrs = 1;
    cfg.gridDim = dim3(36); cfg.blockDim = dim3(384); cfg.dynamicSmemBytes = ka::SMEM;
    cudaLaunchKernelEx(&cfg, k_aux, x, wqkv, wo, Wo, (__nv_bfloat16*)d_out);
}
```

```cpp
#include <cuda_runtime.h>
#include <cuda_bf16.h>
#include <stdint.h>

#define LAG 6
constexpr int NSEG = 64;
constexpr int NT = NSEG + LAG;
#define RING_ 8
constexpr int RING = RING_;
constexpr int DM = 576;

__device__ __align__(1024) uint4 g_xt[NT * 2 * 9 * 256];
__device__ __align__(1024) uint4 g_o[RING * 4 * 256 * 32];
__device__ __align__(1024) uint4 g_ex[2 * 131072];
__device__ unsigned g_side[96];
__device__ __align__(1024) uint4 g_pb[RING * 64 * 8 * 72];
__device__ __align__(1024) uint4 g_pa[RING * 64 * 4 * 72];
__device__ __align__(1024) uint4 g_oa[RING * 4 * 44 * 32];
__device__ __align__(1024) uint4 g_xa[NT * 2 * 9 * 256];
__device__ __align__(1024) uint4 g_x[3 * 2048 * 72];

constexpr int C_X = 0;
constexpr int C_O = C_X + NT;
constexpr int C_WB = C_O + NT * 8;
constexpr int C_RB = C_WB + NT * 4;
constexpr int C_A = C_RB + NT;
constexpr int C_WA = C_A + NT * 4;
constexpr int C_N0 = C_WA + NT * 4;
constexpr int C_DONE = C_N0 + NSEG;
constexpr int C_TOTAL = C_DONE + 1;
__device__ __align__(1024) unsigned g_cnt[C_TOTAL * 8];
__device__ unsigned g_epoch;

#define TR(i)
#define TR1(i)
#define TR_ON(t)
#define TR_INIT(base)
#define TR_DUMP(slot)
#define TRG(t, i)
constexpr int TR_BYTES = 0;

#define DEVI __device__ __forceinline__
DEVI uint32_t smem_u32(const void* p) { return (uint32_t)__cvta_generic_to_shared(p); }
DEVI uint32_t pk(float lo, float hi) { uint32_t r; asm("cvt.rn.bf16x2.f32 %0, %1, %2;" : "=r"(r) : "f"(hi), "f"(lo)); return r; }
DEVI float bf_lo(uint32_t u) { return __uint_as_float(u << 16); }
DEVI float bf_hi(uint32_t u) { return __uint_as_float(u & 0xffff0000u); }
DEVI uint32_t add2(uint32_t a, uint32_t b) { uint32_t d; asm("add.rn.bf16x2 %0, %1, %2;" : "=r"(d) : "r"(a), "r"(b)); return d; }
DEVI uint32_t movm(uint32_t a) { uint32_t d; asm volatile("movmatrix.sync.aligned.m8n8.trans.b16 %0, %1;" : "=r"(d) : "r"(a)); return d; }
DEVI float ex2(float x) { float y; asm("ex2.approx.ftz.f32 %0, %1;" : "=f"(y) : "f"(x)); return y; }
DEVI float rcp(float x) { float y; asm("rcp.approx.ftz.f32 %0, %1;" : "=f"(y) : "f"(x)); return y; }
DEVI void mma16(float (&d)[4], uint32_t a0, uint32_t a1, uint32_t a2, uint32_t a3, uint32_t b0, uint32_t b1) {
    asm volatile("mma.sync.aligned.m16n8k16.row.col.f32.bf16.bf16.f32 {%0,%1,%2,%3}, {%4,%5,%6,%7}, {%8,%9}, {%0,%1,%2,%3};"
        : "+f"(d[0]), "+f"(d[1]), "+f"(d[2]), "+f"(d[3]) : "r"(a0), "r"(a1), "r"(a2), "r"(a3), "r"(b0), "r"(b1));
}
DEVI void mma8(float (&d)[4], uint32_t a0, uint32_t a1, uint32_t b0) {
    asm volatile("mma.sync.aligned.m16n8k8.row.col.f32.bf16.bf16.f32 {%0,%1,%2,%3}, {%4,%5}, {%6}, {%0,%1,%2,%3};"
        : "+f"(d[0]), "+f"(d[1]), "+f"(d[2]), "+f"(d[3]) : "r"(a0), "r"(a1), "r"(b0));
}
DEVI uint4 lds128(uint32_t a) { uint4 v; asm volatile("ld.shared.v4.u32 {%0,%1,%2,%3}, [%4];" : "=r"(v.x), "=r"(v.y), "=r"(v.z), "=r"(v.w) : "r"(a) : "memory"); return v; }
DEVI uint2 lds64(uint32_t a) { uint2 v; asm volatile("ld.shared.v2.u32 {%0,%1}, [%2];" : "=r"(v.x), "=r"(v.y) : "r"(a) : "memory"); return v; }
DEVI uint32_t lds32(uint32_t a) { uint32_t v; asm volatile("ld.shared.u32 %0, [%1];" : "=r"(v) : "r"(a) : "memory"); return v; }
DEVI uint32_t lds32v(uint32_t a) { uint32_t v; asm volatile("ld.volatile.shared.u32 %0, [%1];" : "=r"(v) : "r"(a) : "memory"); return v; }
DEVI uint4 lds128v(uint32_t a) { uint4 v; asm volatile("ld.volatile.shared.v4.u32 {%0,%1,%2,%3}, [%4];" : "=r"(v.x), "=r"(v.y), "=r"(v.z), "=r"(v.w) : "r"(a) : "memory"); return v; }
DEVI uint32_t lds16(uint32_t a) { uint32_t v; asm volatile("ld.shared.u16 %0, [%1];" : "=r"(v) : "r"(a) : "memory"); return v; }
DEVI uint4 ldsm4(uint32_t a) { uint4 v; asm volatile("ldmatrix.sync.aligned.m8n8.x4.shared.b16 {%0,%1,%2,%3}, [%4];" : "=r"(v.x), "=r"(v.y), "=r"(v.z), "=r"(v.w) : "r"(a) : "memory"); return v; }
DEVI uint4 ldsm4t(uint32_t a) { uint4 v; asm volatile("ldmatrix.sync.aligned.m8n8.x4.trans.shared.b16 {%0,%1,%2,%3}, [%4];" : "=r"(v.x), "=r"(v.y), "=r"(v.z), "=r"(v.w) : "r"(a) : "memory"); return v; }
DEVI uint2 ldsm2(uint32_t a) { uint2 v; asm volatile("ldmatrix.sync.aligned.m8n8.x2.shared.b16 {%0,%1}, [%2];" : "=r"(v.x), "=r"(v.y) : "r"(a) : "memory"); return v; }
DEVI void stsm4t(uint32_t a, uint32_t x, uint32_t y, uint32_t z, uint32_t w) { asm volatile("stmatrix.sync.aligned.m8n8.x4.trans.shared.b16 [%0], {%1,%2,%3,%4};" :: "r"(a), "r"(x), "r"(y), "r"(z), "r"(w) : "memory"); }
DEVI void sts128(uint32_t a, uint32_t x, uint32_t y, uint32_t z, uint32_t w) { asm volatile("st.shared.v4.u32 [%0], {%1,%2,%3,%4};" :: "r"(a), "r"(x), "r"(y), "r"(z), "r"(w) : "memory"); }
DEVI void sts64(uint32_t a, uint32_t x, uint32_t y) { asm volatile("st.shared.v2.u32 [%0], {%1,%2};" :: "r"(a), "r"(x), "r"(y) : "memory"); }
DEVI void sts32(uint32_t a, uint32_t x) { asm volatile("st.shared.u32 [%0], %1;" :: "r"(a), "r"(x) : "memory"); }
DEVI void sts32p(uint32_t a, uint32_t x, bool pred) { asm volatile("{.reg .pred p; setp.ne.u32 p, %2, 0; @p st.shared.u32 [%0], %1;}" :: "r"(a), "r"(x), "r"((uint32_t)pred) : "memory"); }
DEVI void sta128(uint32_t a, uint32_t x, uint32_t y, uint32_t z, uint32_t w, uint32_t bar) {
    asm volatile("st.async.weak.shared::cluster.mbarrier::complete_tx::bytes.v4.b32 [%0], {%1,%2,%3,%4}, [%5];" :: "r"(a), "r"(x), "r"(y), "r"(z), "r"(w), "r"(bar) : "memory");
}
DEVI void sta128p(uint32_t a, uint32_t x, uint32_t y, uint32_t z, uint32_t w, uint32_t bar, bool pred) {
    asm volatile("{.reg .pred p; setp.ne.u32 p, %6, 0; @p st.async.weak.shared::cluster.mbarrier::complete_tx::bytes.v4.b32 [%0], {%1,%2,%3,%4}, [%5];}" :: "r"(a), "r"(x), "r"(y), "r"(z), "r"(w), "r"(bar), "r"((uint32_t)pred) : "memory");
}
DEVI void sta64(uint32_t a, uint32_t x, uint32_t y, uint32_t bar) {
    asm volatile("st.async.weak.shared::cluster.mbarrier::complete_tx::bytes.v2.b32 [%0], {%1,%2}, [%3];" :: "r"(a), "r"(x), "r"(y), "r"(bar) : "memory");
}
DEVI void sta32(uint32_t a, uint32_t x, uint32_t bar) {
    asm volatile("st.async.weak.shared::cluster.mbarrier::complete_tx::bytes.b32 [%0], %1, [%2];" :: "r"(a), "r"(x), "r"(bar) : "memory");
}
DEVI uint4 ldg_pkt(const void* p) {
    uint4 v;
    asm volatile("ld.relaxed.gpu.global.v4.u32 {%0,%1,%2,%3}, [%4];" : "=r"(v.x), "=r"(v.y), "=r"(v.z), "=r"(v.w) : "l"(p) : "memory");
    return v;
}
DEVI void ldg_pkt_if(uint4& v, const void* p, bool pred) {
    asm volatile("{.reg .pred p; setp.ne.u32 p, %5, 0; @p ld.relaxed.gpu.global.v4.u32 {%0,%1,%2,%3}, [%4];}"
        : "+r"(v.x), "+r"(v.y), "+r"(v.z), "+r"(v.w) : "l"(p), "r"((uint32_t)pred) : "memory");
}
DEVI void ldg_pkt_retry(uint4& v, const void* p, uint32_t tag) {
    asm volatile("{.reg .pred p; .reg .b32 t; lop3.b32 t, %0, %5, 1, 0x28; setp.ne.u32 p, t, 0; @p ld.relaxed.gpu.global.v4.u32 {%0,%1,%2,%3}, [%4];}"
        : "+r"(v.x), "+r"(v.y), "+r"(v.z), "+r"(v.w) : "l"(p), "r"(tag) : "memory");
}
DEVI void stg_pkt(void* p, uint32_t x, uint32_t y, uint32_t z, uint32_t w) {
    asm volatile("st.relaxed.gpu.global.v4.u32 [%0], {%1,%2,%3,%4};" :: "l"(p), "r"(x), "r"(y), "r"(z), "r"(w) : "memory");
}
DEVI uint32_t ldg_word(const void* p) { uint32_t v; asm volatile("ld.relaxed.gpu.global.u32 %0, [%1];" : "=r"(v) : "l"(p) : "memory"); return v; }
DEVI void stg_word(void* p, uint32_t x, bool pred) {
    asm volatile("{.reg .pred p; setp.ne.u32 p, %2, 0; @p st.relaxed.gpu.global.u32 [%0], %1;}" :: "l"(p), "r"(x), "r"((uint32_t)pred) : "memory");
}
DEVI uint2 ldg64nc(const void* p) { uint2 v; asm volatile("ld.global.nc.L1::no_allocate.v2.u32 {%0,%1}, [%2];" : "=r"(v.x), "=r"(v.y) : "l"(p)); return v; }
DEVI void prefetch_l2(const void* p, uint32_t bytes) { asm volatile("cp.async.bulk.prefetch.L2.global [%0], %1;" :: "l"(p), "r"(bytes) : "memory"); }
DEVI uint4 ldg128(const void* p) { uint4 v; asm volatile("ld.global.cg.v4.u32 {%0,%1,%2,%3}, [%4];" : "=r"(v.x), "=r"(v.y), "=r"(v.z), "=r"(v.w) : "l"(p) : "memory"); return v; }
DEVI uint2 ldg64(const void* p) { uint2 v; asm volatile("ld.global.cg.v2.u32 {%0,%1}, [%2];" : "=r"(v.x), "=r"(v.y) : "l"(p) : "memory"); return v; }
DEVI uint32_t ldg32(const void* p) { uint32_t v; asm volatile("ld.global.cg.u32 %0, [%1];" : "=r"(v) : "l"(p) : "memory"); return v; }
DEVI void stg128(void* p, uint32_t x, uint32_t y, uint32_t z, uint32_t w) { asm volatile("st.global.cg.v4.u32 [%0], {%1,%2,%3,%4};" :: "l"(p), "r"(x), "r"(y), "r"(z), "r"(w) : "memory"); }
DEVI void stg128p(void* p, uint32_t x, uint32_t y, uint32_t z, uint32_t w, bool pred) { asm volatile("{.reg .pred p; setp.ne.u32 p, %5, 0; @p st.global.cg.v4.u32 [%0], {%1,%2,%3,%4};}" :: "l"(p), "r"(x), "r"(y), "r"(z), "r"(w), "r"((uint32_t)pred) : "memory"); }
DEVI void stg64(void* p, uint32_t x, uint32_t y) { asm volatile("st.global.cg.v2.u32 [%0], {%1,%2};" :: "l"(p), "r"(x), "r"(y) : "memory"); }
DEVI void stg32(void* p, uint32_t x) { asm volatile("st.global.cg.u32 [%0], %1;" :: "l"(p), "r"(x) : "memory"); }
DEVI void cp16(uint32_t dst, const void* src) { asm volatile("cp.async.cg.shared.global [%0], [%1], 16;" :: "r"(dst), "l"(src) : "memory"); }
DEVI void cp16_if(uint32_t dst, const void* src, bool pred) { asm volatile("{.reg .pred p; setp.ne.u32 p, %2, 0; @p cp.async.cg.shared.global [%0], [%1], 16;}" :: "r"(dst), "l"(src), "r"((uint32_t)pred) : "memory"); }
DEVI void cp_commit() { asm volatile("cp.async.commit_group;" ::: "memory"); }
DEVI void cp4(uint32_t dst, const void* src) { asm volatile("cp.async.ca.shared.global [%0], [%1], 4;" :: "r"(dst), "l"(src) : "memory"); }
template <int N> DEVI void cp_wait() { asm volatile("cp.async.wait_group %0;" :: "n"(N) : "memory"); }
DEVI void cp_wait_all() { asm volatile("cp.async.wait_all;" ::: "memory"); }
DEVI void bar_sync(int id, int n) { asm volatile("bar.sync %0, %1;" :: "r"(id), "r"(n) : "memory"); }
DEVI void bar_arrive(int id, int n) { asm volatile("bar.arrive %0, %1;" :: "r"(id), "r"(n) : "memory"); }
DEVI void fence_async_smem() { asm volatile("fence.proxy.async.shared::cta;" ::: "memory"); }
DEVI void fence_async_global() { asm volatile("fence.proxy.async.global;" ::: "memory"); }
DEVI void mbar_init(uint32_t b, int n) { asm volatile("mbarrier.init.shared.b64 [%0], %1;" :: "r"(b), "r"(n) : "memory"); }
DEVI void mbar_expect(uint32_t b, uint32_t bytes, bool pred) {
    asm volatile("{.reg .pred p; setp.ne.u32 p, %2, 0; @p mbarrier.arrive.expect_tx.shared.b64 _, [%0], %1;}" :: "r"(b), "r"(bytes), "r"((uint32_t)pred) : "memory");
}
DEVI void mbar_arrive(uint32_t b, bool pred) { asm volatile("{.reg .pred p; setp.ne.u32 p, %1, 0; @p mbarrier.arrive.shared.b64 _, [%0];}" :: "r"(b), "r"((uint32_t)pred) : "memory"); }
DEVI void mbar_arrive_all3(uint32_t b, uint32_t lane) {
    asm volatile("{.reg .pred p; .reg .u32 a; setp.lt.u32 p, %1, 3; @p mapa.shared::cluster.u32 a, %0, %1; @p mbarrier.arrive.relaxed.cluster.shared::cluster.b64 _, [a];}" :: "r"(b), "r"(lane) : "memory");
}
#define FAULT "or.b32 n, n, 1; st.volatile.shared.u32 [n], n;\n"
#define LIM1 "400000"
#define LIM2 "2000000"
DEVI void fault_if(bool p, uint32_t n) { asm volatile("{.reg .pred p; setp.ne.u32 p, %0, 0; @p st.volatile.shared.u32 [%1], %1;}" :: "r"((uint32_t)p), "r"(n | 1) : "memory"); }
DEVI void mbar_wait(uint32_t b, uint32_t parity) {
    asm volatile("{.reg .pred p; .reg .u32 n;\n"
        "mbarrier.try_wait.parity.shared::cta.b64 p, [%0], %1;\n"
        "@p bra.uni D%=;\n"
        "mov.u32 n, 0;\n"
        "W%=: mbarrier.try_wait.parity.shared::cta.b64 p, [%0], %1;\n"
        "@p bra.uni D%=;\n"
        "add.u32 n, n, 1; setp.lt.u32 p, n, " LIM1 "; @p bra.uni W%=;\n"
        FAULT
        "D%=:}" :: "r"(b), "r"(parity) : "memory");
}
constexpr int POLL_LIMIT = 2000000;
DEVI void cnt_wait(const unsigned* c, unsigned target) {
    asm volatile("{.reg .pred p; .reg .u32 n, v;\n"
        "ld.acquire.gpu.global.u32 v, [%0];\n"
        "setp.ge.u32 p, v, %1; vote.sync.all.pred p, p, 0xffffffff; @p bra.uni D%=;\n"
        "mov.u32 n, 0;\n"
        "W%=: ld.acquire.gpu.global.u32 v, [%0];\n"
        "setp.ge.u32 p, v, %1; vote.sync.all.pred p, p, 0xffffffff; @p bra.uni D%=;\n"
        "add.u32 n, n, 1; setp.lt.u32 p, n, " LIM2 "; @p bra.uni W%=;\n"
        FAULT
        "D%=:}" :: "l"(c), "r"(target) : "memory");
}
DEVI void cnt_add(unsigned* c, int lane) {
    asm volatile("{.reg .pred p; setp.eq.u32 p, %1, 0; fence.acq_rel.gpu; bar.warp.sync 0xffffffff; @p red.relaxed.gpu.global.add.u32 [%0], 1;}" :: "l"(c + lane), "r"(lane) : "memory");
}
DEVI void cnt_hint(unsigned* c, int lane) {
    asm volatile("{.reg .pred p; setp.eq.u32 p, %1, 0; @p red.relaxed.gpu.global.add.u32 [%0], 1;}" :: "l"(c + lane), "r"(lane) : "memory");
}
DEVI uint32_t ring_tag(int u, uint32_t ep) { return (u / RING + ep * ((NT - 1 - u % RING) / RING + 1) + 1) & 1; }
DEVI uint32_t lop_bad(uint32_t acc, uint32_t x, uint32_t y, uint32_t tag) {
    uint32_t d; asm("{.reg .b32 t; lop3.b32 t, %2, %3, %4, 0x7e; or.b32 %0, t, %1;}" : "=r"(d) : "r"(acc), "r"(x), "r"(y), "r"(tag)); return d;
}
template <int N> DEVI void validate(uint4* v, const void* p, int step, uint32_t tag) {
    for (int n = 0;; n++) {
        uint32_t bad = 0;
#pragma unroll
        for (int i = 0; i < N; i += 2) bad = lop_bad(bad, v[i].x, v[i + 1 < N ? i + 1 : i].x, tag);
        if (!__any_sync(~0u, bad & 1)) break;
#pragma unroll
        for (int i = 0; i < N; i++) v[i] = ldg_pkt(static_cast<const char*>(p) + i * step);
        fault_if(n > POLL_LIMIT, n);
    }
}
DEVI uint32_t page_par(uint32_t off) { return __popc((off >> 12) & 0xb2) & 1; }
DEVI uint32_t inbox_off(int b) { return (b >> 1) * 32768 + (b & 1) * 8192; }
DEVI uint32_t mem_off(int w, int i) { return 0x180000 + w * 1024 + (i & 1) * 512 + (i & 3) * 16384 + (i < 4 ? 0 : i < 8 ? 0x30000 : 0x40000); }
DEVI void sched_fence(uint32_t zero, uint32_t id) { asm volatile("{.reg .pred p; setp.ne.u32 p, %0, %1; @p bra.uni D%=; exit; D%=:}" :: "r"(zero), "r"(id) : "memory"); }
DEVI uint32_t clk() { uint32_t c; asm volatile("mov.u32 %0, %%clock;" : "=r"(c) :: "memory"); return c; }
DEVI void delay(uint32_t n) {
    if (n) asm volatile("{.reg .pred p; .reg .u32 c, e; mov.u32 e, %%clock;\n W%=: mov.u32 c, %%clock; sub.u32 c, c, e; setp.lt.u32 p, c, %0; @p bra.uni W%=;}" :: "r"(n) : "memory");
}
DEVI void wg_fence() { asm volatile("wgmma.fence.sync.aligned;" ::: "memory"); }
DEVI void wg_commit() { asm volatile("wgmma.commit_group.sync.aligned;" ::: "memory"); }
template <int N> DEVI void wg_wait() { asm volatile("wgmma.wait_group.sync.aligned %0;" :: "n"(N) : "memory"); }
DEVI uint64_t mkdesc(uint32_t lo, uint32_t hi) { uint64_t d; asm("mov.b64 %0, {%1,%2};" : "=l"(d) : "r"(lo), "r"(hi)); return d; }
DEVI void cluster_arrive() { asm volatile("barrier.cluster.arrive.relaxed.aligned;" ::: "memory"); }
DEVI void cluster_wait() { asm volatile("barrier.cluster.wait.aligned;" ::: "memory"); }
DEVI void cluster_sync() { asm volatile("barrier.cluster.arrive.aligned;\n barrier.cluster.wait.aligned;" ::: "memory"); }
DEVI void wgmma_ss16t(float (&d)[8], uint64_t da, uint64_t db, int acc) {
    asm volatile("{.reg .pred p; setp.ne.b32 p, %10, 0;\n"
        "wgmma.mma_async.sync.aligned.m64n16k16.f32.bf16.bf16 {%0,%1,%2,%3,%4,%5,%6,%7}, %8, %9, p, 1, 1, 0, 1;}"
        : "+f"(d[0]), "+f"(d[1]), "+f"(d[2]), "+f"(d[3]), "+f"(d[4]), "+f"(d[5]), "+f"(d[6]), "+f"(d[7])
        : "l"(da), "l"(db), "r"(acc));
}
DEVI void wgmma_ss16a(float (&d)[8], uint64_t da, uint64_t db, int acc) {
    asm volatile("{.reg .pred p; setp.ne.b32 p, %10, 0;\n"
        "wgmma.mma_async.sync.aligned.m64n16k16.f32.bf16.bf16 {%0,%1,%2,%3,%4,%5,%6,%7}, %8, %9, p, 1, 1, 1, 0;}"
        : "+f"(d[0]), "+f"(d[1]), "+f"(d[2]), "+f"(d[3]), "+f"(d[4]), "+f"(d[5]), "+f"(d[6]), "+f"(d[7])
        : "l"(da), "l"(db), "r"(acc));
}
DEVI void wgmma_ss64(float (&d)[32], uint64_t da, uint64_t db, int acc) {
    asm volatile("{.reg .pred p; setp.ne.b32 p, %34, 0;\n"
        "wgmma.mma_async.sync.aligned.m64n64k16.f32.bf16.bf16 {%0,%1,%2,%3,%4,%5,%6,%7,%8,%9,%10,%11,%12,%13,%14,%15,%16,%17,%18,%19,%20,%21,%22,%23,%24,%25,%26,%27,%28,%29,%30,%31}, %32, %33, p, 1, 1, 0, 0;}"
        : "+f"(d[0]), "+f"(d[1]), "+f"(d[2]), "+f"(d[3]), "+f"(d[4]), "+f"(d[5]), "+f"(d[6]), "+f"(d[7]), "+f"(d[8]), "+f"(d[9]), "+f"(d[10]), "+f"(d[11]), "+f"(d[12]), "+f"(d[13]), "+f"(d[14]), "+f"(d[15]), "+f"(d[16]), "+f"(d[17]), "+f"(d[18]), "+f"(d[19]), "+f"(d[20]), "+f"(d[21]), "+f"(d[22]), "+f"(d[23]), "+f"(d[24]), "+f"(d[25]), "+f"(d[26]), "+f"(d[27]), "+f"(d[28]), "+f"(d[29]), "+f"(d[30]), "+f"(d[31])
        : "l"(da), "l"(db), "r"(acc));
}
DEVI void wgmma_rs16t(float (&d)[8], uint32_t a0, uint32_t a1, uint32_t a2, uint32_t a3, uint64_t db, int acc) {
    asm volatile("{.reg .pred p; setp.ne.b32 p, %13, 0;\n"
        "wgmma.mma_async.sync.aligned.m64n16k16.f32.bf16.bf16 {%0,%1,%2,%3,%4,%5,%6,%7}, {%8,%9,%10,%11}, %12, p, 1, 1, 1;}"
        : "+f"(d[0]), "+f"(d[1]), "+f"(d[2]), "+f"(d[3]), "+f"(d[4]), "+f"(d[5]), "+f"(d[6]), "+f"(d[7])
        : "r"(a0), "r"(a1), "r"(a2), "r"(a3), "l"(db), "r"(acc));
}
DEVI void wgmma_rs64(float (&d)[32], uint32_t a0, uint32_t a1, uint32_t a2, uint32_t a3, uint64_t db, int acc) {
    asm volatile("{.reg .pred p; setp.ne.b32 p, %37, 0;\n"
        "wgmma.mma_async.sync.aligned.m64n64k16.f32.bf16.bf16 {%0,%1,%2,%3,%4,%5,%6,%7,%8,%9,%10,%11,%12,%13,%14,%15,%16,%17,%18,%19,%20,%21,%22,%23,%24,%25,%26,%27,%28,%29,%30,%31}, {%32,%33,%34,%35}, %36, p, 1, 1, 0;}"
        : "+f"(d[0]), "+f"(d[1]), "+f"(d[2]), "+f"(d[3]), "+f"(d[4]), "+f"(d[5]), "+f"(d[6]), "+f"(d[7]), "+f"(d[8]), "+f"(d[9]), "+f"(d[10]), "+f"(d[11]), "+f"(d[12]), "+f"(d[13]), "+f"(d[14]), "+f"(d[15]), "+f"(d[16]), "+f"(d[17]), "+f"(d[18]), "+f"(d[19]), "+f"(d[20]), "+f"(d[21]), "+f"(d[22]), "+f"(d[23]), "+f"(d[24]), "+f"(d[25]), "+f"(d[26]), "+f"(d[27]), "+f"(d[28]), "+f"(d[29]), "+f"(d[30]), "+f"(d[31])
        : "r"(a0), "r"(a1), "r"(a2), "r"(a3), "l"(db), "r"(acc));
}
DEVI void wgmma_ss168t(float (&d)[84], uint64_t da, uint64_t db, int acc) {
    asm volatile("{.reg .pred p; setp.ne.b32 p, %86, 0;\n"
        "wgmma.mma_async.sync.aligned.m64n168k16.f32.bf16.bf16 {%0,%1,%2,%3,%4,%5,%6,%7,%8,%9,%10,%11,%12,%13,%14,%15,%16,%17,%18,%19,%20,%21,%22,%23,%24,%25,%26,%27,%28,%29,%30,%31,%32,%33,%34,%35,%36,%37,%38,%39,%40,%41,%42,%43,%44,%45,%46,%47,%48,%49,%50,%51,%52,%53,%54,%55,%56,%57,%58,%59,%60,%61,%62,%63,%64,%65,%66,%67,%68,%69,%70,%71,%72,%73,%74,%75,%76,%77,%78,%79,%80,%81,%82,%83}, %84, %85, p, 1, 1, 0, 1;}"
        : "+f"(d[0]), "+f"(d[1]), "+f"(d[2]), "+f"(d[3]), "+f"(d[4]), "+f"(d[5]), "+f"(d[6]), "+f"(d[7]), "+f"(d[8]), "+f"(d[9]), "+f"(d[10]), "+f"(d[11]), "+f"(d[12]), "+f"(d[13]), "+f"(d[14]), "+f"(d[15]), "+f"(d[16]), "+f"(d[17]), "+f"(d[18]), "+f"(d[19]), "+f"(d[20]), "+f"(d[21]), "+f"(d[22]), "+f"(d[23]), "+f"(d[24]), "+f"(d[25]), "+f"(d[26]), "+f"(d[27]), "+f"(d[28]), "+f"(d[29]), "+f"(d[30]), "+f"(d[31]), "+f"(d[32]), "+f"(d[33]), "+f"(d[34]), "+f"(d[35]), "+f"(d[36]), "+f"(d[37]), "+f"(d[38]), "+f"(d[39]), "+f"(d[40]), "+f"(d[41]), "+f"(d[42]), "+f"(d[43]), "+f"(d[44]), "+f"(d[45]), "+f"(d[46]), "+f"(d[47]), "+f"(d[48]), "+f"(d[49]), "+f"(d[50]), "+f"(d[51]), "+f"(d[52]), "+f"(d[53]), "+f"(d[54]), "+f"(d[55]), "+f"(d[56]), "+f"(d[57]), "+f"(d[58]), "+f"(d[59]), "+f"(d[60]), "+f"(d[61]), "+f"(d[62]), "+f"(d[63]), "+f"(d[64]), "+f"(d[65]), "+f"(d[66]), "+f"(d[67]), "+f"(d[68]), "+f"(d[69]), "+f"(d[70]), "+f"(d[71]), "+f"(d[72]), "+f"(d[73]), "+f"(d[74]), "+f"(d[75]), "+f"(d[76]), "+f"(d[77]), "+f"(d[78]), "+f"(d[79]), "+f"(d[80]), "+f"(d[81]), "+f"(d[82]), "+f"(d[83])
        : "l"(da), "l"(db), "r"(acc));
}
DEVI void wgmma_rs96t(float (&d)[48], uint32_t a0, uint32_t a1, uint32_t a2, uint32_t a3, uint64_t db, int acc) {
    asm volatile("{.reg .pred p; setp.ne.b32 p, %53, 0;\n"
        "wgmma.mma_async.sync.aligned.m64n96k16.f32.bf16.bf16 {%0,%1,%2,%3,%4,%5,%6,%7,%8,%9,%10,%11,%12,%13,%14,%15,%16,%17,%18,%19,%20,%21,%22,%23,%24,%25,%26,%27,%28,%29,%30,%31,%32,%33,%34,%35,%36,%37,%38,%39,%40,%41,%42,%43,%44,%45,%46,%47}, {%48,%49,%50,%51}, %52, p, 1, 1, 1;}"
        : "+f"(d[0]), "+f"(d[1]), "+f"(d[2]), "+f"(d[3]), "+f"(d[4]), "+f"(d[5]), "+f"(d[6]), "+f"(d[7]), "+f"(d[8]), "+f"(d[9]), "+f"(d[10]), "+f"(d[11]), "+f"(d[12]), "+f"(d[13]), "+f"(d[14]), "+f"(d[15]), "+f"(d[16]), "+f"(d[17]), "+f"(d[18]), "+f"(d[19]), "+f"(d[20]), "+f"(d[21]), "+f"(d[22]), "+f"(d[23]), "+f"(d[24]), "+f"(d[25]), "+f"(d[26]), "+f"(d[27]), "+f"(d[28]), "+f"(d[29]), "+f"(d[30]), "+f"(d[31]), "+f"(d[32]), "+f"(d[33]), "+f"(d[34]), "+f"(d[35]), "+f"(d[36]), "+f"(d[37]), "+f"(d[38]), "+f"(d[39]), "+f"(d[40]), "+f"(d[41]), "+f"(d[42]), "+f"(d[43]), "+f"(d[44]), "+f"(d[45]), "+f"(d[46]), "+f"(d[47])
        : "r"(a0), "r"(a1), "r"(a2), "r"(a3), "l"(db), "r"(acc));
}
DEVI void wgmma_rs192t(float (&d)[96], uint32_t a0, uint32_t a1, uint32_t a2, uint32_t a3, uint64_t db, int acc) {
    asm volatile("{.reg .pred p; setp.ne.b32 p, %101, 0;\n"
        "wgmma.mma_async.sync.aligned.m64n192k16.f32.bf16.bf16 {%0,%1,%2,%3,%4,%5,%6,%7,%8,%9,%10,%11,%12,%13,%14,%15,%16,%17,%18,%19,%20,%21,%22,%23,%24,%25,%26,%27,%28,%29,%30,%31,%32,%33,%34,%35,%36,%37,%38,%39,%40,%41,%42,%43,%44,%45,%46,%47,%48,%49,%50,%51,%52,%53,%54,%55,%56,%57,%58,%59,%60,%61,%62,%63,%64,%65,%66,%67,%68,%69,%70,%71,%72,%73,%74,%75,%76,%77,%78,%79,%80,%81,%82,%83,%84,%85,%86,%87,%88,%89,%90,%91,%92,%93,%94,%95}, {%96,%97,%98,%99}, %100, p, 1, 1, 1;}"
        : "+f"(d[0]), "+f"(d[1]), "+f"(d[2]), "+f"(d[3]), "+f"(d[4]), "+f"(d[5]), "+f"(d[6]), "+f"(d[7]), "+f"(d[8]), "+f"(d[9]), "+f"(d[10]), "+f"(d[11]), "+f"(d[12]), "+f"(d[13]), "+f"(d[14]), "+f"(d[15]), "+f"(d[16]), "+f"(d[17]), "+f"(d[18]), "+f"(d[19]), "+f"(d[20]), "+f"(d[21]), "+f"(d[22]), "+f"(d[23]), "+f"(d[24]), "+f"(d[25]), "+f"(d[26]), "+f"(d[27]), "+f"(d[28]), "+f"(d[29]), "+f"(d[30]), "+f"(d[31]), "+f"(d[32]), "+f"(d[33]), "+f"(d[34]), "+f"(d[35]), "+f"(d[36]), "+f"(d[37]), "+f"(d[38]), "+f"(d[39]), "+f"(d[40]), "+f"(d[41]), "+f"(d[42]), "+f"(d[43]), "+f"(d[44]), "+f"(d[45]), "+f"(d[46]), "+f"(d[47]), "+f"(d[48]), "+f"(d[49]), "+f"(d[50]), "+f"(d[51]), "+f"(d[52]), "+f"(d[53]), "+f"(d[54]), "+f"(d[55]), "+f"(d[56]), "+f"(d[57]), "+f"(d[58]), "+f"(d[59]), "+f"(d[60]), "+f"(d[61]), "+f"(d[62]), "+f"(d[63]), "+f"(d[64]), "+f"(d[65]), "+f"(d[66]), "+f"(d[67]), "+f"(d[68]), "+f"(d[69]), "+f"(d[70]), "+f"(d[71]), "+f"(d[72]), "+f"(d[73]), "+f"(d[74]), "+f"(d[75]), "+f"(d[76]), "+f"(d[77]), "+f"(d[78]), "+f"(d[79]), "+f"(d[80]), "+f"(d[81]), "+f"(d[82]), "+f"(d[83]), "+f"(d[84]), "+f"(d[85]), "+f"(d[86]), "+f"(d[87]), "+f"(d[88]), "+f"(d[89]), "+f"(d[90]), "+f"(d[91]), "+f"(d[92]), "+f"(d[93]), "+f"(d[94]), "+f"(d[95])
        : "r"(a0), "r"(a1), "r"(a2), "r"(a3), "l"(db), "r"(acc));
}

#define TRD(t, i)
namespace km {
#define NSS 6
#define RG "184"
#define RW "136"
#define NFL 3
#define NR1 3
#define NR2 3
#define FK 5
#define NGAP 12
constexpr int O_H = 0;
constexpr int O_MB = 73728;
constexpr int O_VX = 96768;
constexpr int O_KX = 113152;
constexpr int O_QX = 119296;
constexpr int O_VM = 125440;
constexpr int O_KM = 129536;
constexpr int O_QM = 131072;
constexpr int O_SM = 132608;
constexpr int O_ST = 135168;
constexpr int O_OX = 145408;
constexpr int O_WO = 149504;
constexpr int O_OS = O_WO;
constexpr int O_WS = O_WO + 49152;
constexpr int O_BAR = O_WS + NSS * 4096;
constexpr int SMEM = O_BAR + 128 + 1024 + TR_BYTES;
enum { B_X = 0, B_XFREE = 8, B_WIN = 16, B_VX = 24, B_SM = 32, B_ST = 40, B_SU = 48, B_EP = 56 };
#define DLY1 (200 * w)
#define DLY2 600
#define XON 1
#define GON 1
#define DLY0 1000
#define PFON 0
#define PLACE 1
#define XST 1
#define IV1 200
#define IV2 200
constexpr uint32_t DESC_HI = (1024 >> 4) | (1u << 30);
constexpr float SC = 0.08838834764831845f * 1.4426950408889634f;
}

__global__ void __cluster_dims__(3, 1, 1) __launch_bounds__(384, 1)
k_main(const __nv_bfloat16* __restrict__ x0, const __nv_bfloat16* __restrict__ wqkv, const __nv_bfloat16* __restrict__ wo,
       const __nv_bfloat16* __restrict__ mem0, const __nv_bfloat16* __restrict__ Wq, const __nv_bfloat16* __restrict__ Wk,
       const __nv_bfloat16* __restrict__ Wv, const __nv_bfloat16* __restrict__ Wo) {
    using namespace km;
    extern __shared__ unsigned char smem_raw[];
    const uint32_t sb = (smem_u32(smem_raw) + 1023) & ~1023u;
    const int tid = threadIdx.x, lane = tid & 31, warp = __shfl_sync(~0u, tid >> 5, 0);
    uint32_t l16 = __shfl_sync(~0u, lane * 16, lane);
#define OPQ() asm volatile("" : "+r"(l16))
    const int b = blockIdx.x, h = b / 3, r = b % 3;
    const int nq = r == 2 ? 2 : 3;
    const uint32_t bar = sb + O_BAR;
    asm volatile("griddepcontrol.launch_dependents;");
    if (tid == 352) {
        prefetch_l2(wqkv + b * (6 * 1728), 6 * 3456); prefetch_l2(x0 + b * (2 * DM), 2 * 1152); prefetch_l2(wo + b * (6 * DM), 6 * 1152);
    }
    if (tid == 320) sts32(bar + 64, ldg32(&g_epoch));
#define EP lds32(bar + 64)
    TR_INIT(bar + 128);
    TRG(79, 0);
    uint32_t roff0, roff1;
    {
        uint32_t y0, y1;
        asm("mapa.shared::cluster.u32 %0, %1, %2;" : "=r"(y0) : "r"(sb), "r"((r + 1) % 3));
        asm("mapa.shared::cluster.u32 %0, %1, %2;" : "=r"(y1) : "r"(sb), "r"((r + 2) % 3));
        roff0 = y0 - sb; roff1 = y1 - sb;
    }
#define LSWAP ((l16 & 0x70) | ((l16 & 0x80) << 1) | ((l16 & 0x100) >> 1))
    const uint32_t nv_remote = 8 - (8 - 2 * nq);

    if (warp < 8) {
        asm volatile("setmaxnreg.inc.sync.aligned.u32 " RG ";");
        constexpr int SSP = 36 / NSS;
#define IS_SS(kk) ((kk) % SSP == 3)
#define AI(kk) (4 * ((kk) - ((kk) + SSP - 4) / SSP))
        uint32_t a[144 - 4 * NSS];
        {
            const int ci = tid & 15, slot = ci >> 1, d0 = tid >> 4;
            const __nv_bfloat16* src = slot < nq ? Wq + (3 * r + slot) * 16 : slot < 2 * nq ? Wk + (3 * r + slot - nq) * 16 : Wv + (2 * r + slot - 2 * nq) * 16;
            src += h * 128 + (ci & 1) * 8 + d0 * 4096;
            delay(DLY0);
            auto issue = [&](int q) {
#pragma unroll
                for (int i = 0; i < 3; i++) if (q < 12) cp16(sb + (q * 3 + i) * 4096 + d0 * 256 + ((ci ^ (d0 & 7)) << 4), src + (size_t)(q * 3 + i) * 65536);
                asm volatile("cp.async.commit_group;" ::: "memory");
            };
#pragma unroll
            for (int q = 0; q < NFL; q++) issue(q);
            TR1(1);
            const int mi = lane >> 3;
            const uint32_t ad = sb + ((mi >> 1) * 8 + (lane & 7)) * 256 + (((warp * 2 + (mi & 1)) ^ (lane & 7)) << 4);
#pragma unroll
            for (int kk = 0; kk < 36; kk++) {
                if (kk % 3 == 0) { cp_wait<NFL - 1>(); issue(kk / 3 + NFL); bar_sync(10, 256); }
                const uint4 f = ldsm4t(ad + kk * 4096);
                if (IS_SS(kk)) {
                    const uint32_t o0 = sb + O_WS + (kk / SSP) * 4096 + warp * 512 + lane * 4;
                    sts32(o0, f.x); sts32(o0 + 256, f.y); sts32(o0 + 128, f.z); sts32(o0 + 384, f.w);
                } else { a[AI(kk)] = f.x; a[AI(kk) + 1] = f.y; a[AI(kk) + 2] = f.z; a[AI(kk) + 3] = f.w; }
            }
            TR1(2);
            bar_sync(9, 384);
#pragma unroll
            for (int i = 0; i < 9; i++) sts128(sb + O_H + i * 8192 + 4096 + tid * 16, 0, 0, 0, 0);
#pragma unroll
            for (int i = 0; i < 8; i++) if (i * 256 + tid < (O_OX - O_KX) / 16) sts128(sb + O_KX + i * 4096 + tid * 16, 0, 0, 0, 0);
            fence_async_smem();
            cluster_sync();
        }
        TR1(3);
        const int kind = warp < nq ? 0 : warp < 2 * nq ? 1 : 2;
        const int sl = kind == 0 ? warp : kind == 1 ? warp - nq : 2 * r + warp - 2 * nq;
        const uint32_t adX0 = sb + (kind == 0 ? O_QX : kind == 1 ? O_KX : O_VX) + sl * 2048;
        const uint32_t adM0 = sb + (kind == 0 ? O_QM : kind == 1 ? O_KM : O_VM) + sl * 512;
        const uint32_t hlo = (((sb + O_H) >> 4) & 0x3fff) | (1u << 16);
        const uint32_t mlo = (((sb + O_MB) >> 4) & 0x3fff) | (16u << 16);
        const uint32_t wlo = (((sb + O_WS + (warp >> 2) * 2048) >> 4) & 0x3fff) | (8u << 16);
        const int L = (warp >> 1) & 1, qh = warp & 1;
        const uint32_t st = sb + O_ST + warp * 1280;
        float s[5][4];

#pragma unroll 1
        for (int t = -1;; t++) {
            TR_ON(t);
            OPQ();
            const uint32_t adX = adX0 + l16, adM = adM0 + l16, l8 = l16 >> 1;
            const uint32_t lq = LSWAP;
            if (t >= 0) {
                {
                    float d0[8], d1[8];
#pragma unroll
                    for (int G = 0; G < 3; G++) {
                        if (warp < 4) bar_sync(1 + G, 160); else bar_sync(12 + G, 160);
                        if (G == 0) wg_fence();
#pragma unroll
                        for (int q = 0; q < 12; q++) {
                            const int kk = 12 * G + q;
                            const uint64_t db = mkdesc(mlo + kk * 32, 8);
                            if (IS_SS(kk)) wgmma_ss16t((kk & 1) ? d1 : d0, mkdesc(wlo + (kk / SSP) * 256, 16), db, 1);
                            else wgmma_rs16t((kk & 1) ? d1 : d0, a[AI(kk)], a[AI(kk) + 1], a[AI(kk) + 2], a[AI(kk) + 3], db, kk >= 2);
                            if (kk == 0) TR(0);
                        }
                    }
                    wg_commit(); wg_wait<0>();
                    TR(1);
                    const uint32_t p0 = pk(d0[0] + d1[0], d0[1] + d1[1]), p1 = pk(d0[2] + d1[2], d0[3] + d1[3]);
                    const uint32_t p2 = pk(d0[4] + d1[4], d0[5] + d1[5]), p3 = pk(d0[6] + d1[6], d0[7] + d1[7]);
                    if (kind == 2) {
                        sts128(adM, p0, p1, p2, p3);
                        bar_arrive(4, 384);
                        sta128(adM + roff0, p0, p1, p2, p3, bar + B_SM + roff0);
                        sta128(adM + roff1, p0, p1, p2, p3, bar + B_SM + roff1);
                    } else {
                        stsm4t(adM, p0, p1, p2, p3);
                        bar_arrive(4, 384);
                    }
                }
                if (warp < 4) {
                    {
                        uint4 q[3];
                        s[4][0] = s[4][1] = s[4][2] = s[4][3] = 0.f;
                        mbar_wait(bar + B_ST, t & 1);
                        bar_sync(5, 256);
                        const uint4 k01 = ldsm4(sb + O_KM + L * 256 + l16 + (l16 & 256));
                        const uint2 k2 = ldsm2(sb + O_KM + 1024 + L * 256 + l16);
#pragma unroll
                        for (int m = 0; m < 3; m++) q[m] = ldsm4(sb + O_QX + m * 2048 + warp * 512 + lq);
                        mma16(s[4], q[0].x, q[0].y, q[0].z, q[0].w, k01.x, k01.y);
                        mma16(s[4], q[1].x, q[1].y, q[1].z, q[1].w, k01.z, k01.w);
                        mma16(s[4], q[2].x, q[2].y, q[2].z, q[2].w, k2.x, k2.y);
                        const uint32_t w0 = pk(s[4][0], s[4][1]), w1 = pk(s[4][2], s[4][3]);
                        bar_arrive(11, 256);
                        sta64(st + l8 + 5120 + 1024 + roff0, w0, w1, bar + B_SU + roff0);
                        sta64(st + l8 + 1024 + roff1, w0, w1, bar + B_SU + roff1);
                    }
                    TR(2);
#pragma unroll
                    for (int src = 0; src < 2; src++) {
                        const uint4 u = lds128(st + src * 5120 + l16), v = lds128(st + src * 5120 + 512 + l16);
                        s[0][0] += bf_lo(u.x); s[0][1] += bf_hi(u.x); s[0][2] += bf_lo(u.y); s[0][3] += bf_hi(u.y);
                        s[1][0] += bf_lo(u.z); s[1][1] += bf_hi(u.z); s[1][2] += bf_lo(u.w); s[1][3] += bf_hi(u.w);
                        s[2][0] += bf_lo(v.x); s[2][1] += bf_hi(v.x); s[2][2] += bf_lo(v.y); s[2][3] += bf_hi(v.y);
                        s[3][0] += bf_lo(v.z); s[3][1] += bf_hi(v.z); s[3][2] += bf_lo(v.w); s[3][3] += bf_hi(v.w);
                    }
                    uint4 v0[3], v1[3];
#pragma unroll
                    for (int m = 0; m < 3; m++) {
                        v0[m] = lds128(sb + O_VX + (3 * r + m) * 2048 + L * 1024 + l16);
                    }
                    mbar_wait(bar + B_SM, t & 1);
                    mbar_wait(bar + B_SU, t & 1);
                    TR(3);
                    {
                        const uint2 x = lds64(st + 1024 + l8), y = lds64(st + 5120 + 1024 + l8);
                        s[4][0] += bf_lo(x.x) + bf_lo(y.x); s[4][1] += bf_hi(x.x) + bf_hi(y.x); s[4][2] += bf_lo(x.y) + bf_lo(y.y); s[4][3] += bf_hi(x.y) + bf_hi(y.y);
                    }
                    float mx0 = fmaxf(s[4][0], s[4][1]), mx1 = fmaxf(s[4][2], s[4][3]);
#pragma unroll
                    for (int n = 0; n < 4; n++) { mx0 = fmaxf(mx0, fmaxf(s[n][0], s[n][1])); mx1 = fmaxf(mx1, fmaxf(s[n][2], s[n][3])); }
#pragma unroll
                    for (int o = 1; o < 4; o <<= 1) { mx0 = fmaxf(mx0, __shfl_xor_sync(~0u, mx0, o)); mx1 = fmaxf(mx1, __shfl_xor_sync(~0u, mx1, o)); }
                    mx0 *= -SC; mx1 *= -SC;
                    float l0 = 0.f, l1 = 0.f;
                    uint32_t p[10];
#pragma unroll
                    for (int n = 0; n < 5; n++) {
                        const float e0 = ex2(fmaf(s[n][0], SC, mx0)), e1 = ex2(fmaf(s[n][1], SC, mx0));
                        const float e2 = ex2(fmaf(s[n][2], SC, mx1)), e3 = ex2(fmaf(s[n][3], SC, mx1));
                        l0 += e0 + e1; l1 += e2 + e3;
                        p[2 * n] = pk(e0, e1); p[2 * n + 1] = pk(e2, e3);
                    }
#pragma unroll
                    for (int o = 1; o < 4; o <<= 1) { l0 += __shfl_xor_sync(~0u, l0, o); l1 += __shfl_xor_sync(~0u, l1, o); }
                    l0 = rcp(l0); l1 = rcp(l1);
                    const uint32_t otag = ring_tag(t, EP);
#pragma unroll
                    for (int m = 0; m < 3; m++) {
                        float o0[4] = {0, 0, 0, 0}, o1[4] = {0, 0, 0, 0};
                        v1[m] = lds128(sb + O_VX + (3 * r + m) * 2048 + L * 1024 + 512 + l16);
                        const uint2 vm = lds64(sb + O_VM + (3 * r + m) * 512 + l16 + L * 8);
                        mma8(o0, p[0], p[1], v0[m].x); mma8(o1, p[0], p[1], v0[m].y); mma8(o0, p[2], p[3], v0[m].z); mma8(o1, p[2], p[3], v0[m].w);
                        mma8(o0, p[4], p[5], v1[m].x); mma8(o1, p[4], p[5], v1[m].y); mma8(o0, p[6], p[7], v1[m].z); mma8(o1, p[6], p[7], v1[m].w);
                        mma8(o0, p[8], p[9], vm.x); mma8(o1, p[8], p[9], vm.y);
                        sts128(sb + O_OS + warp * 1536 + m * 512 + l16, (pk(o0[0] * l0, o0[1] * l0) & ~1u) | otag, pk(o0[2] * l1, o0[3] * l1), pk(o1[0] * l0, o1[1] * l0), pk(o1[2] * l1, o1[3] * l1));
                    }
                    TR(4);
                }
            }
            if (t + 1 >= NT) break;
            {
                float d[32];
                mbar_wait(bar + B_X, (t + 1) & 1);
                if (warp < 4) bar_sync(7, 384); else if (t >= 0) bar_sync(11, 256);
                wg_fence();
                TR(6);
#pragma unroll
                for (int kk = 0; kk < 36; kk++) {
                    if (kk == NGAP) asm volatile("{.reg .pred p; setp.ge.u32 p, %0, 4; @p bar.sync 7, 384;}" :: "r"(warp) : "memory");
                    const uint64_t db = mkdesc(hlo + ((kk >> 2) * 8192 + (kk & 3) * 32) / 16, DESC_HI);
                    if (IS_SS(kk)) wgmma_ss64(d, mkdesc(wlo + (kk / SSP) * 256, 16), db, 1);
                    else wgmma_rs64(d, a[AI(kk)], a[AI(kk) + 1], a[AI(kk) + 2], a[AI(kk) + 3], db, kk > 0);
                }
                wg_commit();
                TR(5);
                mbar_wait(bar + B_WIN, (t + 1) & 1);
                wg_wait<0>();
                TR(7);
                mbar_arrive_all3(bar + B_XFREE, l16 >> 4);
                uint32_t p[16];
#pragma unroll
                for (int u = 0; u < 16; u++) p[u] = pk(d[2 * u], d[2 * u + 1]);
                if (kind == 2) {
#pragma unroll
                    for (int u = 0; u < 4; u++) sts128(adX + u * 512, p[4 * u], p[4 * u + 1], p[4 * u + 2], p[4 * u + 3]);
                } else {
#pragma unroll
                    for (int u = 0; u < 4; u++) stsm4t(adX + u * 512, p[4 * u], p[4 * u + 1], p[4 * u + 2], p[4 * u + 3]);
                }
                __syncwarp();
                asm volatile("{.reg .pred p; setp.eq.u32 p, %1, 0; @p mbarrier.arrive.shared.b64 _, [%0];}" :: "r"(bar + B_EP), "r"(l16) : "memory");
                if (kind == 2) {
                    fence_async_smem();
                    __syncwarp();
                    asm volatile("{.reg .pred p; setp.eq.u32 p, %5, 0;\n"
                        "@p cp.async.bulk.shared::cluster.shared::cta.mbarrier::complete_tx::bytes [%0], [%2], 2048, [%3];\n"
                        "@p cp.async.bulk.shared::cluster.shared::cta.mbarrier::complete_tx::bytes [%1], [%2], 2048, [%4];}"
                        :: "r"(adX0 + roff0), "r"(adX0 + roff1), "r"(adX0), "r"(bar + B_VX + roff0), "r"(bar + B_VX + roff1), "r"(l16) : "memory");
                }
                TR(8);
                {
                    const int lim = 16 * qh + (int)(l16 >> 6) - (int)((l16 >> 3) & 6);
#pragma unroll
                    for (int n = 0; n < 4; n++)
#pragma unroll
                        for (int j = 0; j < 4; j++) s[n][j] = (n == 0 && j >= 2) || 8 * (n - (j >> 1)) + (j & 1) <= lim ? 0.f : -1e30f;
                }
                if (warp < 4) {
                    mbar_wait(bar + B_EP, (t + 1) & 1);
#pragma unroll
                    for (int m = 0; m < 3; m++) {
                        const uint4 q = ldsm4(sb + O_QX + m * 2048 + warp * 512 + lq);
                        const uint4 k0 = ldsm4(sb + O_KX + m * 2048 + L * 1024 + l16);
                        const uint4 k1 = ldsm4(sb + O_KX + m * 2048 + L * 1024 + 512 + l16);
                        mma16(s[0], q.x, q.y, q.z, q.w, k0.x, k0.y);
                        mma16(s[1], q.x, q.y, q.z, q.w, k0.z, k0.w);
                        mma16(s[2], q.x, q.y, q.z, q.w, k1.x, k1.y);
                        mma16(s[3], q.x, q.y, q.z, q.w, k1.z, k1.w);
                    }
                    uint32_t w0 = pk(s[0][0], s[0][1]), w1 = pk(s[0][2], s[0][3]), w2 = pk(s[1][0], s[1][1]), w3 = pk(s[1][2], s[1][3]);
                    sta128(st + l16 + 5120 + roff0, w0, w1, w2, w3, bar + B_ST + roff0);
                    sta128(st + l16 + roff1, w0, w1, w2, w3, bar + B_ST + roff1);
                    w0 = pk(s[2][0], s[2][1]); w1 = pk(s[2][2], s[2][3]); w2 = pk(s[3][0], s[3][1]); w3 = pk(s[3][2], s[3][3]);
                    sta128p(st + l16 + 5120 + 512 + roff0, w0, w1, w2, w3, bar + B_ST + roff0, qh);
                    sta128p(st + l16 + 512 + roff1, w0, w1, w2, w3, bar + B_ST + roff1, qh);
                    TR(9);
                }
            }
        }
        if (warp >= 4) bar_sync(11, 256); else bar_arrive(7, 160);
        cluster_sync();
    } else {
        asm volatile("setmaxnreg.dec.sync.aligned.u32 " RW ";");
        const int w = warp - 8, t2 = tid - 256;
        if (t2 == 0) {
            mbar_init(bar + B_X, 1); mbar_init(bar + B_XFREE, 24); mbar_init(bar + B_WIN, 3);
            mbar_init(bar + B_VX, 1); mbar_init(bar + B_SM, 1); mbar_init(bar + B_ST, 1); mbar_init(bar + B_SU, 1); mbar_init(bar + B_EP, 8);
            asm volatile("fence.mbarrier_init.release.cluster;" ::: "memory");
        }
        char* const ex = reinterpret_cast<char*>((reinterpret_cast<uintptr_t>(g_ex) + 0x1fffff) & ~(uintptr_t)0x1fffff);
        char* rbase; uint32_t side;
        {
            uint32_t m0[5][4];
#pragma unroll
            for (int i = 0; i < 5; i++) {
                const unsigned short* m = reinterpret_cast<const unsigned short*>(mem0) + min(i * 128 + t2, DM - 1);
#pragma unroll
                for (int j = 0; j < 4; j++) m0[i][j] = m[2 * j * DM] | (m[(2 * j + 1) * DM] << 16);
            }
            if (w < 2) {
                unsigned* pp = reinterpret_cast<unsigned*>(ex + inbox_off(b) + 16384 + w * 4096 + 2048);
                uint32_t best = ~0u, v = 0;
                if (lane == 0) {
#pragma unroll 1
                    for (int i = 0; i < 6; i++) {
                        const uint32_t c0 = clk();
                        v = atomicAdd(pp + (v >> 31), 0);
                        asm volatile("" :: "r"(v) : "memory");
                        sts32(bar + 80, v);
                        best = min(best, clk() - c0);
                    }
                    sts32(bar + 72 + w * 4, best);
                }
            }
            bar_sync(6, 128);
            const uint32_t xs = PLACE ? lds32(bar + 76) < lds32(bar + 72) : 0, ep = EP;
            side = PLACE ? xs ^ page_par(inbox_off(b)) : 0;
            rbase = ex + inbox_off(b) + xs * 4096;
            const uint32_t inv = (ep * (NT - 1)) & 1;
#pragma unroll
            for (int G = 0; G < 3; G++) stg128(rbase + (G == 2 ? 16384 : G * 2048) + t2 * 16, inv, 0, 0, 0);
            __threadfence();
            bar_sync(6, 128);
            if (t2 == 0) stg_word(g_side + b, (ep + 1) * 2 + xs, true);
            if (t2 >= 96 && t2 < 99 && PFON) prefetch_l2((t2 == 96 ? Wq : t2 == 97 ? Wk : Wv) + b * (6 * 4096), 6 * 8192);
            delay(DLY0 * 6);
#pragma unroll 4
            for (int i = t2; i < 128 * 24; i += 128) {
                const int e = (i >> 3) & 127, G = i >> 10, q = i & 7;
                cp16(sb + O_WO + G * 16384 + e * 128 + ((q ^ (e & 7) ^ ((h >> 1) & 1)) << 4), Wo + (size_t)(h * 128 + e) * DM + G * 192 + r * 64 + q * 8);
            }
            bar_sync(9, 384);
#pragma unroll
            for (int i = 0; i < 5; i++) {
                const int k = min(i * 128 + t2, DM - 1);
                const uint32_t ad = sb + O_MB + (k >> 3) * 256 + (k & 7) * 16;
                sts128(ad, m0[i][0], m0[i][1], m0[i][2], m0[i][3]); sts128(ad + 128, m0[i][0], m0[i][1], m0[i][2], m0[i][3]);
            }
            fence_async_smem();
        }
        auto arm = [&]() {
            const uint32_t ln = l16 >> 4;
            mbar_expect(bar + B_VX + (ln & 3) * 8, ln == 0 ? nv_remote * 2048 : ln == 1 ? nv_remote * 512 + 2560 : ln == 2 ? 6144 : 2048, ln < 4);
        };
        if (w == 3) arm();
        cluster_sync();
        TR1(3);
        const int L = w >> 1, hf = w & 1;
        const uint32_t rd = hf ? roff1 : roff0;
        const uint32_t rzero = gridDim.y + 100;
#define WOAD (sb + O_WO + ((l16 & 0x100) << 2) + ((l16 & 0x70) << 3) + (((w * 32) | ((l16 >> 3) & 16)) ^ (l16 & 0x70)))

        auto fetch_tile = [&](int u) {
            const bool a0 = u < NSEG && (XON || u < 8), a1 = u >= LAG && (XON || u < 8);
            mbar_expect(bar + B_X, ((int)a0 + (int)a1) * 36864, l16 == 0);
            const int kb = (l16 >> 5) * 3 + r, hl = (l16 >> 4) & 1;
            asm volatile("{.reg .pred p; setp.ne.u32 p, %4, 0;\n"
                "@p cp.async.bulk.shared::cluster.global.mbarrier::complete_tx::bytes.multicast::cluster [%0], [%1], 4096, [%2], %3;}"
                :: "r"(sb + O_H + kb * 8192 + hl * 4096), "l"(g_xt + ((u * 2 + hl) * 9 + kb) * 256), "r"(bar + B_X), "h"((uint16_t)7),
                   "r"((uint32_t)(l16 < 96 && (hl ? a1 : a0))) : "memory");
        };
        auto store_o = [&](int u) {
            asm volatile("{.reg .pred p; setp.lt.u32 p, %3, 64;\n"
                "@p cp.async.bulk.global.shared::cta.bulk_group [%0], [%1], %2;\n cp.async.bulk.commit_group;}"
                :: "l"(g_o + (((u & (RING - 1)) * 4 + ((l16 >> 4) & 3)) * 256 + h * 8 + 3 * r) * 32), "r"(sb + O_OS + (l16 & 48) * 96), "r"(nq * 512), "r"(l16) : "memory");
        };
        auto hint_o = [&](int u) {
            asm volatile("cp.async.bulk.wait_group 0;" ::: "memory");
            __syncwarp();
            cnt_hint(g_cnt + (C_O + u * 8 + (h >> 2)) * 8, l16);
            TRG(u, 2);
        };
        bar_arrive(7, 384);
        if (w < 3) { bar_arrive(1 + w, 160); bar_arrive(12 + w, 160); if (w == 0) bar_arrive(8, 64); }
        else {
            mbar_arrive_all3(bar + B_WIN, l16 >> 4);
            cnt_wait(g_cnt + C_X * 8, 64 * (EP + 1)); fence_async_global();
            TRG(0, 0);
            fetch_tile(0);
            TRG(0, 1);
            cnt_wait(g_cnt + (C_X + 1) * 8, 64 * (EP + 1)); fence_async_global();
            TRG(1, 0);
        }
        cp_wait_all();
        bar_sync(6, 128);
        uint32_t poff;
        {
            const int rb = r * 32 + w * 8 + (lane >> 2);
            const uint32_t want = EP + 1;
            uint32_t v;
            for (int n = 0; __any_sync(~0u, ((v = ldg_word(g_side + rb)) >> 1) != want); n++) fault_if(n > POLL_LIMIT, n);
            __threadfence();
            poff = inbox_off(rb) + (v & 1) * 4096 + h * 64 + (lane & 3) * 16;
        }
        side = __shfl_sync(~0u, side, 0);
        const uint32_t roff = __shfl_sync(~0u, (uint32_t)(rbase - ex), 0) + (w == 2 ? 16384 : (w & 1) * 2048);
        uint4 a0[8];
#pragma unroll
        for (int kk = 0; kk < 8; kk++) a0[kk] = ldsm4t(WOAD + kk * 2048);
#pragma unroll 1
        for (int t = 0;; t++) {
            TR_ON(t);
            OPQ();
            mbar_wait(bar + B_EP, t & 1);
            uint4 kx[3][2], vx[4][2];
            const uint32_t lp = LSWAP;
#pragma unroll
            for (int m = 0; m < 3; m++) {
                kx[m][0] = ldsm4(sb + O_KX + m * 2048 + L * 1024 + lp);
                kx[m][1] = ldsm4(sb + O_KX + m * 2048 + L * 1024 + 512 + lp);
            }
            mbar_wait(bar + B_VX, t & 1);
            if (w == 3) {
                mbar_wait(bar + B_XFREE, t & 1);
                bar_sync(8, 64);
                TR(6);
                if (t + 1 < NT) { fetch_tile(t + 1); TRG(t + 1, 1); }
                if (t > 0) store_o(t - 1);
                TR(7);
            }
            TR(0);
            bar_sync(4, 384);
            float s0[4] = {0, 0, 0, 0}, s1[4] = {0, 0, 0, 0}, sm[4] = {0, 0, 0, 0};
            {
                const uint4 q01 = ldsm4(sb + O_QM + L * 256 + l16 + (l16 & 256));
                const uint2 q2 = ldsm2(sb + O_QM + 1024 + L * 256 + l16);
                uint4 km_[3];
#pragma unroll
                for (int m = 0; m < 3; m++) km_[m] = ldsm4(sb + O_KM + m * 512 + (lp ^ (L << 8)));
                bar_arrive(5, 256);
                mma16(s0, kx[0][0].x, kx[0][0].y, kx[0][0].z, kx[0][0].w, q01.x, q01.y);
                mma16(s1, kx[0][1].x, kx[0][1].y, kx[0][1].z, kx[0][1].w, q01.x, q01.y);
                mma16(sm, km_[0].x, km_[0].y, km_[0].z, km_[0].w, q01.x, q01.y);
                mma16(s0, kx[1][0].x, kx[1][0].y, kx[1][0].z, kx[1][0].w, q01.z, q01.w);
                mma16(s1, kx[1][1].x, kx[1][1].y, kx[1][1].z, kx[1][1].w, q01.z, q01.w);
                mma16(sm, km_[1].x, km_[1].y, km_[1].z, km_[1].w, q01.z, q01.w);
                mma16(s0, kx[2][0].x, kx[2][0].y, kx[2][0].z, kx[2][0].w, q2.x, q2.y);
                mma16(s1, kx[2][1].x, kx[2][1].y, kx[2][1].z, kx[2][1].w, q2.x, q2.y);
                mma16(sm, km_[2].x, km_[2].y, km_[2].z, km_[2].w, q2.x, q2.y);
                const uint32_t ad = sb + O_SM + (1 - hf) * 1280 + L * 640 + rd;
                sta128(ad + l16, pk(s0[0], s0[1]), pk(s0[2], s0[3]), pk(s1[0], s1[1]), pk(s1[2], s1[3]), bar + B_SM + rd);
                sta32(ad + 512 + (l16 >> 2), pk(sm[0], sm[1]), bar + B_SM + rd);
            }
            TR(1);
            if (w == 3 && t > 0) hint_o(t - 1);
            if (t + 1 == NT) break;
#pragma unroll
            for (int m = 0; m < 8; m++) vx[m >> 1][m & 1] = lds128(sb + O_VX + (hf * 4 + (m >> 1)) * 2048 + L * 1024 + (m & 1) * 512 + l16);
            const uint32_t tag = (t + EP * (NT - 1) + 1) & 1;
            mbar_wait(bar + B_SM, t & 1);
            TR(2);
            {
                const uint32_t ad = sb + O_SM + L * 640;
                const uint4 u = lds128(ad + l16), v = lds128(ad + 1280 + l16);
                const uint32_t x = lds32(ad + 512 + (l16 >> 2)), y = lds32(ad + 1280 + 512 + (l16 >> 2));
                s0[0] += bf_lo(u.x) + bf_lo(v.x); s0[1] += bf_hi(u.x) + bf_hi(v.x); s0[2] += bf_lo(u.y) + bf_lo(v.y); s0[3] += bf_hi(u.y) + bf_hi(v.y);
                s1[0] += bf_lo(u.z) + bf_lo(v.z); s1[1] += bf_hi(u.z) + bf_hi(v.z); s1[2] += bf_lo(u.w) + bf_lo(v.w); s1[3] += bf_hi(u.w) + bf_hi(v.w);
                sm[0] += bf_lo(x) + bf_lo(y); sm[1] += bf_hi(x) + bf_hi(y);
            }
            uint2 vm[4];
#pragma unroll
            for (int m = 0; m < 4; m++) vm[m] = lds64(sb + O_VM + (hf * 4 + m) * 512 + l16 + L * 8);
            float mx0 = fmaxf(fmaxf(fmaxf(s0[0], s0[2]), fmaxf(s1[0], s1[2])), sm[0]);
            float mx1 = fmaxf(fmaxf(fmaxf(s0[1], s0[3]), fmaxf(s1[1], s1[3])), sm[1]);
#pragma unroll
            for (int o = 4; o < 32; o <<= 1) { mx0 = fmaxf(mx0, __shfl_xor_sync(~0u, mx0, o)); mx1 = fmaxf(mx1, __shfl_xor_sync(~0u, mx1, o)); }
            mx0 *= -SC; mx1 *= -SC;
            s0[0] = ex2(fmaf(s0[0], SC, mx0)); s0[1] = ex2(fmaf(s0[1], SC, mx1));
            s0[2] = ex2(fmaf(s0[2], SC, mx0)); s0[3] = ex2(fmaf(s0[3], SC, mx1));
            const uint32_t pb0 = movm(pk(s0[0], s0[1])), pb1 = movm(pk(s0[2], s0[3]));
            s1[0] = ex2(fmaf(s1[0], SC, mx0)); s1[1] = ex2(fmaf(s1[1], SC, mx1));
            s1[2] = ex2(fmaf(s1[2], SC, mx0)); s1[3] = ex2(fmaf(s1[3], SC, mx1));
            const uint32_t pb2 = movm(pk(s1[0], s1[1])), pb3 = movm(pk(s1[2], s1[3]));
            sm[0] = ex2(fmaf(sm[0], SC, mx0)); sm[1] = ex2(fmaf(sm[1], SC, mx1));
            const uint32_t pm = movm(pk(sm[0], sm[1]));
            float l0 = (s0[0] + s0[2]) + (s1[0] + s1[2]) + sm[0], l1 = (s0[1] + s0[3]) + (s1[1] + s1[3]) + sm[1];
            float o[4][4];
#pragma unroll
            for (int m = 0; m < 4; m++) { o[m][0] = o[m][1] = o[m][2] = o[m][3] = 0.f; mma16(o[m], vx[m][0].x, vx[m][0].y, vx[m][0].z, vx[m][0].w, pb0, pb1); }
            l0 += __shfl_xor_sync(~0u, l0, 4); l1 += __shfl_xor_sync(~0u, l1, 4);
#pragma unroll
            for (int m = 0; m < 4; m++) mma16(o[m], vx[m][1].x, vx[m][1].y, vx[m][1].z, vx[m][1].w, pb2, pb3);
            l0 += __shfl_xor_sync(~0u, l0, 8); l1 += __shfl_xor_sync(~0u, l1, 8);
#pragma unroll
            for (int m = 0; m < 4; m++) mma8(o[m], vm[m].x, vm[m].y, pm);
            l0 += __shfl_xor_sync(~0u, l0, 16); l1 += __shfl_xor_sync(~0u, l1, 16);
            l0 = rcp(l0); l1 = rcp(l1);
#pragma unroll
            for (int m = 0; m < 4; m += 2)
                stsm4t(sb + O_OX + (hf * 4 + m) * 512 + (L ^ ((h >> 2) & 1)) * 256   + ((l16 & 0x100) << 1) + (l16 & 0xf0),
                       pk(o[m][0] * l0, o[m][1] * l1), pk(o[m][2] * l0, o[m][3] * l1), pk(o[m + 1][0] * l0, o[m + 1][1] * l1), pk(o[m + 1][2] * l0, o[m + 1][3] * l1));
            TR(3);
            char* const pdst = ex + poff;
            bar_sync(6, 128);
            {
                uint4 bo[8], a1[8];
                const uint32_t wad = WOAD;
#pragma unroll
                for (int kk = 0; kk < 8; kk++) bo[kk] = ldsm4(sb + O_OX + kk * 512 + l16);
#pragma unroll
                for (int G = 0; G < 3; G++) {
                    float e[4][4];
#pragma unroll
                    for (int q = 0; q < 4; q++) e[q][0] = e[q][1] = e[q][2] = e[q][3] = 0.f;
#pragma unroll
                    for (int kk = 0; kk < 8; kk++) {
                        const uint4 f = G == 0 ? a0[kk] : a1[kk];
                        mma16(e[(kk & 1) * 2], f.x, f.y, f.z, f.w, bo[kk].x, bo[kk].y);
                        mma16(e[(kk & 1) * 2 + 1], f.x, f.y, f.z, f.w, bo[kk].z, bo[kk].w);
                        if (G == 1) a1[kk] = ldsm4t(wad + 32768 + kk * 2048);
                        if (G == 0 && kk == FK) {
                            sched_fence(rzero, 2);
#pragma unroll
                            for (int j = 0; j < 8; j++) a1[j] = ldsm4t(wad + 16384 + j * 2048);
                        }
                    }
                    stg_pkt(pdst + (G == 2 ? 16384 : G * 2048), (pk(e[0][0] + e[2][0], e[0][1] + e[2][1]) & ~1u) | tag, pk(e[0][2] + e[2][2], e[0][3] + e[2][3]),
                            pk(e[1][0] + e[3][0], e[1][1] + e[3][1]), pk(e[1][2] + e[3][2], e[1][3] + e[3][3]));
                    if (G == 0) { TR(9); TRD(t, 0); }
                    if (G < 2) sched_fence(rzero, 3 + G);
                }
            }
            TR(4);
            if (w < 3) {
                bar_arrive(7, 384);
                OPQ();
                const uint32_t tagm = tag;
                uint32_t m0v = 0;
                if (t + 1 <= LAG) {
                    const unsigned short* m = reinterpret_cast<const unsigned short*>(mem0) + ((l16 >> 3) & 6) * DM + 192 * w + 16 * (b >> 3) + (b & 7) + ((l16 >> 4) & 8);
                    m0v = m[0] | (m[DM] << 16);
                }
                const char* const rsrc = ex + roff + l16;
                uint4 v[4];
                delay(DLY1);
#pragma unroll
                for (int i = 0; i < 4; i++) v[i] = ldg_pkt(rsrc + i * 512);
                for (int n = 0; __any_sync(~0u, lop_bad(lop_bad(0, v[0].x, v[1].x, tagm), v[2].x, v[3].x, tagm) & 1); n++) {
#pragma unroll
                    for (int i = 0; i < 4; i++) v[i] = ldg_pkt(rsrc + i * 512);
                    fault_if(n > POLL_LIMIT, n);
                }
                TR(5); TRD(t, 1);
                float s[8];
                s[4] = (bf_lo(v[0].z) + bf_lo(v[1].z)) + (bf_lo(v[2].z) + bf_lo(v[3].z)); s[5] = (bf_hi(v[0].z) + bf_hi(v[1].z)) + (bf_hi(v[2].z) + bf_hi(v[3].z));
                s[6] = (bf_lo(v[0].w) + bf_lo(v[1].w)) + (bf_lo(v[2].w) + bf_lo(v[3].w)); s[7] = (bf_hi(v[0].w) + bf_hi(v[1].w)) + (bf_hi(v[2].w) + bf_hi(v[3].w));
                s[2] = (bf_lo(v[0].y) + bf_lo(v[1].y)) + (bf_lo(v[2].y) + bf_lo(v[3].y)); s[3] = (bf_hi(v[0].y) + bf_hi(v[1].y)) + (bf_hi(v[2].y) + bf_hi(v[3].y));
                s[0] = (bf_lo(v[0].x) + bf_lo(v[1].x)) + (bf_lo(v[2].x) + bf_lo(v[3].x)); s[1] = (bf_hi(v[0].x) + bf_hi(v[1].x)) + (bf_hi(v[2].x) + bf_hi(v[3].x));
#pragma unroll
                for (int j = 0; j < 4; j++) s[j] += __shfl_xor_sync(~0u, s[j + 4], 16);
#pragma unroll
                for (int j = 0; j < 2; j++) s[j] += __shfl_xor_sync(~0u, s[j + 2], 8);
#pragma unroll
                for (int j = 0; j < 2; j++) s[j] += __shfl_xor_sync(~0u, s[j], 4);
                char* const mem_w = ex + mem_off(w, 0);
                uint32_t res = t + 1 <= LAG && l16 >= 256 ? m0v : pk(s[0], s[1]);
                if ((l16 & 48) == 0) res = (res & ~1u) | tag;
                stg_word(mem_w + (mem_off(0, b >> 3) - mem_off(0, 0)) + (b & 7) * 16 + (((l16 & 64) << 6) + ((l16 & 128) << 1) + ((l16 & 256) >> 1) + ((l16 >> 2) & 12)), res, true);
                TR(6); TRD(t, 2);
                delay(DLY2);
                const char* src = mem_w + (side ^ page_par(0x180000)) * 4096 + l16;
                const uint32_t gdst = sb + O_MB + w * 6144 + l16;
                uint4 x[12];
#pragma unroll
                for (int i = 0; i < 12; i++) x[i] = ldg_pkt(src + (mem_off(0, i) - mem_off(0, 0)));
                for (int n = 0;; n++) {
                    uint32_t bad = 0;
#pragma unroll
                    for (int i = 0; i < 12; i += 2) bad = lop_bad(bad, x[i].x, x[i + 1].x, tagm);
                    if (!__any_sync(~0u, bad & 1)) break;
#pragma unroll
                    for (int i = 0; i < 12; i++) ldg_pkt_retry(x[i], src + (mem_off(0, i) - mem_off(0, 0)), tagm);
                    fault_if(n > POLL_LIMIT, n);
                }
#pragma unroll
                for (int i = 0; i < 12; i++) sts128(gdst + i * 512, x[i].x, x[i].y, x[i].z, x[i].w);
                TR(7); TRD(t, 3);
                fence_async_smem();
                bar_arrive(12 + w, 160);
                bar_arrive(1 + w, 160);
                if (w == XST) bar_arrive(8, 64);
                TR(8);
            } else {
                bar_sync(7, 384);
                fence_async_smem();
                arm();
                __syncwarp();
                mbar_arrive_all3(bar + B_WIN, l16 >> 4);
                if (t + 2 < NT) { cnt_wait(g_cnt + (C_X + t + 2) * 8, 64 * (EP + 1)); fence_async_global(); TRG(t + 2, 0); }
                TR(5);
            }
        }
        if (w == 3) { bar_sync(7, 160); fence_async_smem(); store_o(NT - 1); hint_o(NT - 1); }
        cluster_sync();
    }
    TR_DUMP(b);
}

#define VG 12
namespace ka {
constexpr int O_WA = 196608;
constexpr int A_SBO = 9232;
constexpr int O_RING = 194560;
constexpr int O_BAR = 230400;
constexpr int SMEM = O_BAR + 128 + 1024;
constexpr float SC = 0.23570226039551584f * 1.4426950408889634f;
}

template <int NP>
DEVI void row_task(const uint4* res, const uint4* part, uint4* xout, char* img, int pos, int lane, uint32_t tag) {
    const bool on = lane < 24;
    const int ln = on ? lane : 0;
    uint4 rv[3], pv[NP > 0 ? NP * 3 : 1];
#pragma unroll
    for (int i = 0; i < 3; i++) rv[i] = ldg128(res + i * 24 + ln);
#pragma unroll
    for (int i = 0; i < NP * 3; i++) pv[i] = ldg_pkt(part + i * 24 + ln);
    if (NP > 0) validate<NP * 3>(pv, part + ln, 384, tag);
#pragma unroll
    for (int q = 0; q < NP * 3 / 2; q++) {
        const uint4 y = pv[q + NP * 3 / 2];
        pv[q] = make_uint4(add2(pv[q].x, y.x), add2(pv[q].y, y.y), add2(pv[q].z, y.z), add2(pv[q].w, y.w));
    }
    float x[24];
#pragma unroll
    for (int i = 0; i < 3; i++) {
        x[8 * i] = bf_lo(rv[i].x); x[8 * i + 1] = bf_hi(rv[i].x); x[8 * i + 2] = bf_lo(rv[i].y); x[8 * i + 3] = bf_hi(rv[i].y);
        x[8 * i + 4] = bf_lo(rv[i].z); x[8 * i + 5] = bf_hi(rv[i].z); x[8 * i + 6] = bf_lo(rv[i].w); x[8 * i + 7] = bf_hi(rv[i].w);
    }
    if (NP > 0) {
#pragma unroll
        for (int q = 0; q < NP * 3 / 2; q++) {
            const int i = q % 3;
            x[8 * i] += bf_lo(pv[q].x); x[8 * i + 1] += bf_hi(pv[q].x); x[8 * i + 2] += bf_lo(pv[q].y); x[8 * i + 3] += bf_hi(pv[q].y);
            x[8 * i + 4] += bf_lo(pv[q].z); x[8 * i + 5] += bf_hi(pv[q].z); x[8 * i + 6] += bf_lo(pv[q].w); x[8 * i + 7] += bf_hi(pv[q].w);
        }
#pragma unroll
        for (int i = 0; i < 3; i++) {
            uint32_t w[4];
#pragma unroll
            for (int j = 0; j < 4; j++) { w[j] = pk(x[8 * i + 2 * j], x[8 * i + 2 * j + 1]); x[8 * i + 2 * j] = bf_lo(w[j]); x[8 * i + 2 * j + 1] = bf_hi(w[j]); }
            stg128p(xout + i * 24 + ln, w[0], w[1], w[2], w[3], on);
        }
    }
    if (img) {
        float s = 0.f;
#pragma unroll
        for (int j = 0; j < 24; j++) s += x[j];
        if (!on) s = 0.f;
#pragma unroll
        for (int o = 1; o < 32; o <<= 1) s += __shfl_xor_sync(~0u, s, o);
        const float mean = s * (1.f / DM);
        float v = 0.f;
#pragma unroll
        for (int j = 0; j < 24; j++) { x[j] -= mean; v = fmaf(x[j], x[j], v); }
        if (!on) v = 0.f;
#pragma unroll
        for (int o = 1; o < 32; o <<= 1) v += __shfl_xor_sync(~0u, v, o);
        const float rs = rsqrtf(v * (1.f / DM) + 1e-5f);
        char* dst = img + (ln >> 3) * 4096 + pos * 128 + (((ln ^ pos) & 7) << 4);
#pragma unroll
        for (int i = 0; i < 3; i++)
            stg128p(dst + i * 12288, pk(x[8 * i] * rs, x[8 * i + 1] * rs), pk(x[8 * i + 2] * rs, x[8 * i + 3] * rs),
                    pk(x[8 * i + 4] * rs, x[8 * i + 5] * rs), pk(x[8 * i + 6] * rs, x[8 * i + 7] * rs), on);
    }
}

__global__ void __launch_bounds__(384, 1)
k_aux(const __nv_bfloat16* __restrict__ x0, const __nv_bfloat16* __restrict__ wqkv, const __nv_bfloat16* __restrict__ wo,
      const __nv_bfloat16* __restrict__ Wo, __nv_bfloat16* __restrict__ out) {
    using namespace ka;
    extern __shared__ unsigned char smem_raw[];
    const uint32_t sb = (smem_u32(smem_raw) + 1023) & ~1023u;
    const int tid = threadIdx.x, lane = tid & 31, warp = __shfl_sync(~0u, tid >> 5, 0), g = lane >> 2, c = lane & 3;
    const int b = blockIdx.x;
    const uint32_t bar = sb + O_BAR;
    const uint32_t ep = __shfl_sync(~0u, ldg32(&g_epoch), 0);

    TRG(79, 0);
    if (warp >= 8) {
        asm volatile("setmaxnreg.dec.sync.aligned.u32 128;");
        const int rw = b * 4 + warp - 8;
        const uint4* xin = reinterpret_cast<const uint4*>(x0);
#pragma unroll 1
        for (int row = rw; row < 2048; row += 16) {
            row_task<0>(xin + row * 72, nullptr, nullptr, reinterpret_cast<char*>(g_xa + (row >> 5) * 4608), (row & 1) * 16 + ((row & 31) >> 1), lane, 0);
            cnt_add(g_cnt + (C_N0 + (row >> 5)) * 8, lane);
            if (rw < 128) break;
        }
        const int R = rw & 63, f = R >> 5, i = R & 31;
        if (rw < 64) {
#pragma unroll 1
            for (int u = 0; u < NT; u++) {
                const int seg = u - f * LAG, row = seg * 32 + i;
                if (seg >= 0 && seg < NSEG) {
                    cnt_wait(g_cnt + (C_WB + u * 4 + (R >> 4)) * 8, 24 * (ep + 1));
                    TRG(u, 0);
                    row_task<8>(g_x + (f * 4096 + row) * 72, g_pb + ((u & (RING - 1)) * 64 + R) * 576,
                                f ? reinterpret_cast<uint4*>(out) + row * 72 : g_x + (2048 + row) * 72,
                                f ? nullptr : reinterpret_cast<char*>(g_xa + (u + LAG) * 4608 + 2304), (i & 1) * 16 + (i >> 1), lane, ring_tag(u, ep));
                    TRG(u, 1);
                }
                cnt_add(g_cnt + (C_RB + u) * 8, lane);
                TRG(u, 2);
            }
            if (rw == 63) {
                asm volatile("griddepcontrol.wait;" ::: "memory");
                if (lane == 0) g_epoch = ep + 1;
            }
        } else if (rw < 128) {
#pragma unroll 1
            for (int u = 0; u < NT; u++) {
                const int seg = u - f * LAG, row = seg * 32 + i;
                if (seg >= 0 && seg < NSEG) {
                    cnt_wait(g_cnt + (C_WA + u * 4 + f * 2 + (i & 1)) * 8, 24 * (ep + 1));
                    TRG(u, 0);
                    row_task<4>((f ? g_x + 2048 * 72 : xin) + row * 72, g_pa + ((u & (RING - 1)) * 64 + R) * 288,
                                g_x + (f * 4096 + row) * 72, reinterpret_cast<char*>(g_xt + u * 4608 + f * 2304), i, lane, ring_tag(u, ep));
                    TRG(u, 1);
                }
                cnt_add(g_cnt + (C_X + u) * 8, lane);
                TRG(u, 2);
            }
        }
        return;
    }
    if (b == 35) return;

    if (b < 24) {
        if (warp >= 4) {
            const int kq = b / 6, nq = b % 6;
            uint4 v[17];
#pragma unroll
            for (int q = 0; q < 17; q++) {
                const int it = q * 4 + warp - 4, kr = (it / 3) * 8 + g, s = kq * 11 + (kr >> 4), a = s >> 2, j = s & 3, e = kr & 15;
                const int head = 3 * a + (j < 3 ? j : e >> 1), row = head * 18 + (j < 3 ? e : 16 + (e & 1));
                v[q] = make_uint4(0, 0, 0, 0);
                if (it < 66 && head < 32 && (j < 3 || e < 6)) v[q] = *reinterpret_cast<const uint4*>(wo + row * DM + nq * 96 + (it % 3) * 32 + c * 8);
            }
#pragma unroll
            for (int q = 0; q < 17; q++) {
                const int it = q * 4 + warp - 4;
                const uint32_t ad = sb + O_WA + (it % 3) * 4 * 2816 + (it / 3) * 128 + lane * 4;
                if (it < 66) { sts32(ad, v[q].x); sts32(ad + 2816, v[q].y); sts32(ad + 2 * 2816, v[q].z); sts32(ad + 3 * 2816, v[q].w); }
            }
        } else {
            const int kg = b / 3, ng = b % 3;
            delay(DLY0 * 7);
#pragma unroll 1
            for (int bt = 0; bt < 4; bt++) {
                uint4 v[24];
#pragma unroll
                for (int q = 0; q < 24; q++)
                    v[q] = *reinterpret_cast<const uint4*>(Wo + (size_t)(kg * 512 + (bt * 4 + q / 6) * 32 + warp * 8 + g) * DM + ng * 192 + (q % 6) * 32 + c * 8);
#pragma unroll
                for (int q = 0; q < 24; q++) {
                    const uint32_t ad = sb + (q % 6) * 4 * 8192 + ((bt * 4 + q / 6) * 4 + warp) * 128 + lane * 4;
                    sts32(ad, v[q].x); sts32(ad + 8192, v[q].y); sts32(ad + 2 * 8192, v[q].z); sts32(ad + 3 * 8192, v[q].w);
                }
            }
        }
        fence_async_smem();
        bar_sync(2 + (warp >> 2), 128);
    } else {
        const int a = b - 24, nw = a == 10 ? 18 : 27, ch = lane & 7, off = (a * 108) & 15;
        int d0[4], dw[4];
#pragma unroll
        for (int j = 0; j < 4; j++) {
            const int w = ch * 4 + j - (off >> 2), hh = w / 9, jj = w % 9;
            d0[j] = w < 0 || w >= nw ? -1 : jj < 8 ? (hh * 2 + (jj >> 2)) * A_SBO + (jj & 3) * 4 : 18 * A_SBO + hh * 4;
            dw[j] = jj < 8 ? 6 * A_SBO : A_SBO;
        }
        const bool any = ch * 4 - (off >> 2) < nw;
        const char* src = reinterpret_cast<const char*>(wqkv) + (warp * 4 + (lane >> 3)) * 3456 + a * 108 - off + (any ? ch * 16 : 0);
#pragma unroll 1
        for (int wh = 0; wh < 3; wh++) {
            uint4 v[18];
#pragma unroll
            for (int q = 0; q < 18; q++) v[q] = ldg128(src + q * 32 * 3456 + wh * 1152);
            sched_fence(gridDim.y, 2);
            TRG(78, wh);
            if (wh == 0) {
                for (int i = tid; i < 3 * A_SBO / 16; i += 256) {
                    sts128(sb + 18 * A_SBO + i * 16, 0, 0, 0, 0);
                    if (a == 10 && i < 2 * A_SBO / 16) { sts128(sb + 4 * A_SBO + i * 16, 0, 0, 0, 0); sts128(sb + 10 * A_SBO + i * 16, 0, 0, 0, 0); sts128(sb + 16 * A_SBO + i * 16, 0, 0, 0, 0); }
                }
                for (int i = tid; i < 2048; i += 256) sts128(sb + O_RING + i * 16, 0, 0, 0, 0);
                if (tid == 0) for (int i = 0; i < 4; i++) { mbar_init(bar + i * 8, 1); mbar_init(bar + 32 + i * 8, 4); }
                bar_sync(1, 256);
            }
            const uint32_t ad = sb + (warp * 4 + (lane >> 3)) * 16;
#pragma unroll
            for (int q = 0; q < 18; q++) {
                sts32p(ad + d0[0] + wh * dw[0] + q * 512, v[q].x, d0[0] >= 0);
                sts32p(ad + d0[1] + wh * dw[1] + q * 512, v[q].y, d0[1] >= 0);
                sts32p(ad + d0[2] + wh * dw[2] + q * 512, v[q].z, d0[2] >= 0);
                sts32p(ad + d0[3] + wh * dw[3] + q * 512, v[q].w, d0[3] >= 0);
            }
        }
        fence_async_smem();
        bar_sync(1, 256);
    }
    TRG(79, 1);
    const int wq = warp & 3;

    if (warp < 4) {
        asm volatile("setmaxnreg.inc.sync.aligned.u32 256;");
        if (b < 24) {
            const int kg = b / 3, ng = b % 3;
            const uint32_t blo = ((sb >> 4) & 0x3fff) | (8u << 16);
            uint4 a[32];
            bool pre = false;
#pragma unroll 1
            for (int u = 0; u < NT; u++) {
                const uint32_t tag = ring_tag(u, ep);
                const uint4* src = g_o + (((u & (RING - 1)) * 4 + wq) * 256 + kg * 32) * 32 + lane;
                if (!pre) {
                    cnt_wait(g_cnt + (C_O + u * 8 + kg) * 8, 12 * (ep + 1));
#pragma unroll
                    for (int i = 0; i < VG; i++) a[i] = ldg_pkt(src + i * 32);
                }
                TRG(u, 0);
                float d[96];
                validate<VG>(a, src, 512, tag);
#pragma unroll
                for (int i = VG; i < 32; i++) a[i] = ldg_pkt(src + i * 32);
                wg_fence();
#pragma unroll
                for (int i = 0; i < 32; i++) {
                    if (i == VG) { validate<32 - VG>(a + VG, src + VG * 32, 512, tag); wg_fence(); }
                    wgmma_rs192t(d, a[i].x, a[i].y, a[i].z, a[i].w, mkdesc(blo + i * 16, 512), i > 0);
                    if (i == 23 || i == 31) wg_commit();
                }
                wg_wait<1>();
                pre = u + 1 < NT && __all_sync(~0u, ldg_word(g_cnt + (C_O + (u + 1) * 8 + kg) * 8) >= 12 * (ep + 1));
                if (pre) {
                    const uint4* nx = g_o + ((((u + 1) & (RING - 1)) * 4 + wq) * 256 + kg * 32) * 32 + lane;
#pragma unroll
                    for (int i = 0; i < VG; i++) a[i] = ldg_pkt(nx + i * 32);
                }
                wg_wait<0>();
                TRG(u, 1);
                uint4* dst = g_pb + (((u & (RING - 1)) * 64 + wq * 16 + g) * 8 + kg) * 72 + ng * 24 + c;
#pragma unroll
                for (int m = 0; m < 6; m++) {
                    stg128(dst + 4 * m, (pk(d[16 * m], d[16 * m + 1]) & ~1u) | tag, pk(d[16 * m + 4], d[16 * m + 5]), pk(d[16 * m + 8], d[16 * m + 9]), pk(d[16 * m + 12], d[16 * m + 13]));
                    stg128(dst + 4 * m + 8 * 576, (pk(d[16 * m + 2], d[16 * m + 3]) & ~1u) | tag, pk(d[16 * m + 6], d[16 * m + 7]), pk(d[16 * m + 10], d[16 * m + 11]), pk(d[16 * m + 14], d[16 * m + 15]));
                }
                cnt_hint(g_cnt + (C_WB + u * 4 + wq) * 8, lane);
                TRG(u, 3);
            }
        } else {
            const int a = b - 24, f = wq >> 1;
            const uint32_t blo = ((sb >> 4) & 0x3fff) | (8u << 16), alo = (((sb + O_RING) >> 4) & 0x3fff) | (1u << 16);
            const bool m0 = 2 * c <= g, m1 = 2 * c + 1 <= g;
            const uint32_t M = (m0 ? 0xffffu : 0u) | (m1 ? 0xffff0000u : 0u);
            uint32_t kh[7], vh[7];
#pragma unroll
            for (int i = 0; i < 7; i++) kh[i] = vh[i] = 0;
            int it = 0;
#pragma unroll 1
            for (int u = 0; u < NT; u++) {
                float d[84];
#pragma unroll 1
                for (int kb = 0; kb < 9; kb++, it++) {
                    mbar_wait(bar + (it & 3) * 8, (it >> 2) & 1);
                    if (kb == 0) TRG(u, 0);
                    wg_fence();
#pragma unroll
                    for (int q = 0; q < 4; q++)
                        wgmma_ss168t(d, mkdesc(alo + (it & 3) * 512 + q * 2, km::DESC_HI), mkdesc(blo + (kb * 4 + q) * 16, A_SBO >> 4), kb + q > 0);
                    wg_commit();
                    wg_wait<1>();
                    mbar_arrive(bar + 32 + ((it - 1) & 3) * 8, lane == 0 && kb > 0);
                }
                wg_wait<0>();
                mbar_arrive(bar + 32 + ((it - 1) & 3) * 8, lane == 0);
                TRG(u, 1);
                const bool first = u == f * LAG;
                const uint32_t tag = ring_tag(u, ep);
                const uint32_t qt0 = pk(d[72], d[73]), qt1 = pk(d[74], d[75]), kt0 = pk(d[76], d[77]), kt1 = pk(d[78], d[79]);
                const uint32_t vt0 = movm(pk(d[80], d[81])), vt1 = movm(pk(d[82], d[83]));
                float ot[4] = {0, 0, 0, 0};
                uint4* dst = g_oa + (((u & (RING - 1)) * 4 + wq) * 44 + a * 4) * 32 + lane;
#pragma unroll
                for (int h = 0; h < 3; h++) {
                    const float* q = d + 8 * h; const float* k = d + 24 + 8 * h; const float* v = d + 48 + 8 * h;
                    const uint32_t q0 = pk(q[0], q[1]), q1 = pk(q[2], q[3]), q2 = pk(q[4], q[5]), q3 = pk(q[6], q[7]);
                    const uint32_t k0 = pk(k[0], k[1]), k1 = pk(k[4], k[5]), k2 = pk(k[2], k[3]), k3 = pk(k[6], k[7]);
                    const uint32_t v0 = movm(pk(v[0], v[1])), v1 = movm(pk(v[2], v[3])), v2 = movm(pk(v[4], v[5])), v3 = movm(pk(v[6], v[7]));
                    const uint32_t t0 = c == h ? qt0 : 0, t1 = c == h ? qt1 : 0;
                    float sp[4] = {0, 0, 0, 0}, sl[4] = {0, 0, 0, 0}, sh[4] = {0, 0, 0, 0};
                    mma16(sp, q0, q1, q2, q3, kh[2 * h], kh[2 * h + 1]); mma16(sl, q0, q1, q2, q3, k0, k1); mma16(sh, q0, q1, q2, q3, k2, k3);
                    mma8(sp, t0, t1, kh[6]); mma8(sl, t0, t1, kt0); mma8(sh, t0, t1, kt1);
                    float x0_ = m0 ? sl[0] : first ? -INFINITY : sp[0], x1_ = m1 ? sl[1] : first ? -INFINITY : sp[1];
                    float y0_ = m0 ? sh[2] : sl[2], y1_ = m1 ? sh[3] : sl[3];
                    float mx = fmaxf(x0_, x1_), my = fmaxf(y0_, y1_);
#pragma unroll
                    for (int o = 1; o < 4; o <<= 1) { mx = fmaxf(mx, __shfl_xor_sync(~0u, mx, o)); my = fmaxf(my, __shfl_xor_sync(~0u, my, o)); }
                    mx *= -SC; my *= -SC;
                    x0_ = ex2(fmaf(x0_, SC, mx)); x1_ = ex2(fmaf(x1_, SC, mx)); y0_ = ex2(fmaf(y0_, SC, my)); y1_ = ex2(fmaf(y1_, SC, my));
                    float lx = x0_ + x1_, ly = y0_ + y1_;
#pragma unroll
                    for (int o = 1; o < 4; o <<= 1) { lx += __shfl_xor_sync(~0u, lx, o); ly += __shfl_xor_sync(~0u, ly, o); }
                    lx = rcp(lx); ly = rcp(ly);
                    const uint32_t px = pk(x0_ * lx, x1_ * lx), py = pk(y0_ * ly, y1_ * ly);
                    const uint32_t hm = (g >> 1) == h ? ~0u : 0u;
                    float o0[4] = {0, 0, 0, 0}, o1[4] = {0, 0, 0, 0};
                    mma16(o0, px & M, py & ~M, 0, py & M, v0, v1); mma16(o1, px & M, py & ~M, 0, py & M, v2, v3);
                    mma16(ot, px & M, py & ~M, 0, py & M, vt0 & hm, vt1 & hm);
                    mma8(o0, px & ~M, 0, vh[2 * h]); mma8(o1, px & ~M, 0, vh[2 * h + 1]); mma8(ot, px & ~M, 0, vh[6] & hm);
                    stg128(dst + h * 32, (pk(o0[0], o0[1]) & ~1u) | tag, pk(o0[2], o0[3]), pk(o1[0], o1[1]), pk(o1[2], o1[3]));
                    kh[2 * h] = k2; kh[2 * h + 1] = k3; vh[2 * h] = v1; vh[2 * h + 1] = v3;
                }
                kh[6] = kt1; vh[6] = vt1;
                stg128(dst + 96, (pk(ot[0], ot[1]) & ~1u) | tag, pk(ot[2], ot[3]), 0, 0);
                cnt_hint(g_cnt + (C_A + u * 4 + wq) * 8, lane);
                TRG(u, 2);
            }
        }
    } else {
        asm volatile("setmaxnreg.dec.sync.aligned.u32 120;");
        if (b < 24) {
            const int kq = b / 6, nq = b % 6;
            const uint32_t blo = (((sb + O_WA) >> 4) & 0x3fff) | (8u << 16);
#pragma unroll 1
            for (int u = 0; u < NT; u++) {
                cnt_wait(g_cnt + (C_A + u * 4 + wq) * 8, 11 * (ep + 1));
                const uint32_t tag = ring_tag(u, ep);
                TRG(u, 0);
                const uint4* src = g_oa + (((u & (RING - 1)) * 4 + wq) * 44 + kq * 11) * 32 + lane;
                uint4 a[11];
                float d[48];
#pragma unroll
                for (int i = 0; i < 11; i++) a[i] = ldg_pkt(src + i * 32);
                validate<11>(a, src, 512, tag);
                wg_fence();
#pragma unroll
                for (int i = 0; i < 11; i++) wgmma_rs96t(d, a[i].x, a[i].y, a[i].z, a[i].w, mkdesc(blo + i * 16, 176), i > 0);
                wg_commit();
                wg_wait<0>();
                TRG(u, 1);
                uint4* dst = g_pa + (((u & (RING - 1)) * 64 + (wq >> 1) * 32 + 2 * g + (wq & 1)) * 4 + kq) * 72 + nq * 12 + c;
#pragma unroll
                for (int m = 0; m < 3; m++) {
                    stg128(dst + 4 * m, (pk(d[16 * m], d[16 * m + 1]) & ~1u) | tag, pk(d[16 * m + 4], d[16 * m + 5]), pk(d[16 * m + 8], d[16 * m + 9]), pk(d[16 * m + 12], d[16 * m + 13]));
                    stg128(dst + 4 * m + 16 * 288, (pk(d[16 * m + 2], d[16 * m + 3]) & ~1u) | tag, pk(d[16 * m + 6], d[16 * m + 7]), pk(d[16 * m + 10], d[16 * m + 11]), pk(d[16 * m + 14], d[16 * m + 15]));
                }
                cnt_hint(g_cnt + (C_WA + u * 4 + wq) * 8, lane);
                TRG(u, 3);
            }
        } else if (warp == 4) {
            int it = 0;
#pragma unroll 1
            for (int u = 0; u < NT; u++) {
                if (u < NSEG) cnt_wait(g_cnt + (C_N0 + u) * 8, 32 * (ep + 1));
                if (u >= LAG) cnt_wait(g_cnt + (C_RB + u - LAG) * 8, 64 * (ep + 1));
                TRG(u, 0);
                asm volatile("fence.proxy.async.global;" ::: "memory");
                const bool on = lane == 0 ? u < NSEG : lane == 1 && u >= LAG;
#pragma unroll 1
                for (int kb = 0; kb < 9; kb++, it++) {
                    if (it >= 4) mbar_wait(bar + 32 + (it & 3) * 8, ((it >> 2) - 1) & 1);
                    mbar_expect(bar + (it & 3) * 8, u < NSEG && u >= LAG ? 8192 : 4096, lane == 0);
                    asm volatile("{.reg .pred p; setp.ne.u32 p, %3, 0; @p cp.async.bulk.shared::cluster.global.mbarrier::complete_tx::bytes [%0], [%1], 4096, [%2];}"
                        :: "r"(sb + O_RING + (it & 3) * 8192 + (lane & 1) * 4096), "l"(g_xa + u * 4608 + (lane & 1) * 2304 + kb * 256), "r"(bar + (it & 3) * 8), "r"((uint32_t)on) : "memory");
                }
            }
        }
    }
}

extern "C" void kernel_launch(void* const* d_in, const int* in_sizes, int n_in, void* d_out, int out_size) {
    const __nv_bfloat16* x = (const __nv_bfloat16*)d_in[0];
    const __nv_bfloat16* wqkv = (const __nv_bfloat16*)d_in[1];
    const __nv_bfloat16* wo = (const __nv_bfloat16*)d_in[2];
    const __nv_bfloat16* mem0 = (const __nv_bfloat16*)d_in[4];
    const __nv_bfloat16* Wq = (const __nv_bfloat16*)d_in[5];
    const __nv_bfloat16* Wk = (const __nv_bfloat16*)d_in[6];
    const __nv_bfloat16* Wv = (const __nv_bfloat16*)d_in[7];
    const __nv_bfloat16* Wo = (const __nv_bfloat16*)d_in[8];
    cudaFuncSetAttribute(k_main, cudaFuncAttributeMaxDynamicSharedMemorySize, km::SMEM);
    cudaFuncSetAttribute(k_aux, cudaFuncAttributeMaxDynamicSharedMemorySize, ka::SMEM);
    cudaStream_t s = cudaStreamPerThread;
    k_main<<<96, 384, km::SMEM, s>>>(x, wqkv, wo, mem0, Wq, Wk, Wv, Wo);
    cudaLaunchConfig_t cfg = {};
    cudaLaunchAttribute at[1];
    at[0].id = cudaLaunchAttributeProgrammaticStreamSerialization;
    at[0].val.programmaticStreamSerializationAllowed = 1;
    cfg.stream = s; cfg.attrs = at; cfg.numAttrs = 1;
    cfg.gridDim = dim3(36); cfg.blockDim = dim3(384); cfg.dynamicSmemBytes = ka::SMEM;
    cudaLaunchKernelEx(&cfg, k_aux, x, wqkv, wo, Wo, (__nv_bfloat16*)d_out);
}
```

```cpp
#include <cuda_runtime.h>
#include <cuda_bf16.h>
#include <stdint.h>

#define LAG 8
constexpr int NSEG = 64;
constexpr int NT = NSEG + LAG;
#define RING_ 8
constexpr int RING = RING_;
constexpr int DM = 576;

__device__ __align__(1024) uint4 g_xt[NT * 2 * 9 * 256];
__device__ __align__(1024) uint4 g_o[RING * 4 * 256 * 32];
__device__ __align__(1024) uint4 g_ex[2 * 131072];
__device__ unsigned g_side[96];
__device__ __align__(1024) uint4 g_pb[RING * 64 * 8 * 72];
__device__ __align__(1024) uint4 g_pa[RING * 64 * 4 * 72];
__device__ __align__(1024) uint4 g_oa[RING * 4 * 44 * 32];
__device__ __align__(1024) uint4 g_xa[NT * 2 * 9 * 256];
__device__ __align__(1024) uint4 g_x[3 * 2048 * 72];

constexpr int C_X = 0;
constexpr int C_O = C_X + NT;
constexpr int C_WB = C_O + NT * 8;
constexpr int C_RB = C_WB + NT * 4;
constexpr int C_A = C_RB + NT;
constexpr int C_WA = C_A + NT * 4;
constexpr int C_N0 = C_WA + NT * 4;
constexpr int C_DONE = C_N0 + NSEG;
constexpr int C_TOTAL = C_DONE + 1;
__device__ __align__(1024) unsigned g_cnt[C_TOTAL * 8];
__device__ unsigned g_epoch;

#define TR(i)
#define TR1(i)
#define TR_ON(t)
#define TR_INIT(base)
#define TR_DUMP(slot)
#define TRG(t, i)
constexpr int TR_BYTES = 0;

#define DEVI __device__ __forceinline__
DEVI uint32_t smem_u32(const void* p) { return (uint32_t)__cvta_generic_to_shared(p); }
DEVI uint32_t pk(float lo, float hi) { uint32_t r; asm("cvt.rn.bf16x2.f32 %0, %1, %2;" : "=r"(r) : "f"(hi), "f"(lo)); return r; }
DEVI float bf_lo(uint32_t u) { return __uint_as_float(u << 16); }
DEVI float bf_hi(uint32_t u) { return __uint_as_float(u & 0xffff0000u); }
DEVI uint32_t add2(uint32_t a, uint32_t b) { uint32_t d; asm("add.rn.bf16x2 %0, %1, %2;" : "=r"(d) : "r"(a), "r"(b)); return d; }
DEVI uint32_t movm(uint32_t a) { uint32_t d; asm volatile("movmatrix.sync.aligned.m8n8.trans.b16 %0, %1;" : "=r"(d) : "r"(a)); return d; }
DEVI float ex2(float x) { float y; asm("ex2.approx.ftz.f32 %0, %1;" : "=f"(y) : "f"(x)); return y; }
DEVI float rcp(float x) { float y; asm("rcp.approx.ftz.f32 %0, %1;" : "=f"(y) : "f"(x)); return y; }
DEVI void mma16(float (&d)[4], uint32_t a0, uint32_t a1, uint32_t a2, uint32_t a3, uint32_t b0, uint32_t b1) {
    asm volatile("mma.sync.aligned.m16n8k16.row.col.f32.bf16.bf16.f32 {%0,%1,%2,%3}, {%4,%5,%6,%7}, {%8,%9}, {%0,%1,%2,%3};"
        : "+f"(d[0]), "+f"(d[1]), "+f"(d[2]), "+f"(d[3]) : "r"(a0), "r"(a1), "r"(a2), "r"(a3), "r"(b0), "r"(b1));
}
DEVI void mma8(float (&d)[4], uint32_t a0, uint32_t a1, uint32_t b0) {
    asm volatile("mma.sync.aligned.m16n8k8.row.col.f32.bf16.bf16.f32 {%0,%1,%2,%3}, {%4,%5}, {%6}, {%0,%1,%2,%3};"
        : "+f"(d[0]), "+f"(d[1]), "+f"(d[2]), "+f"(d[3]) : "r"(a0), "r"(a1), "r"(b0));
}
DEVI uint4 lds128(uint32_t a) { uint4 v; asm volatile("ld.shared.v4.u32 {%0,%1,%2,%3}, [%4];" : "=r"(v.x), "=r"(v.y), "=r"(v.z), "=r"(v.w) : "r"(a) : "memory"); return v; }
DEVI uint2 lds64(uint32_t a) { uint2 v; asm volatile("ld.shared.v2.u32 {%0,%1}, [%2];" : "=r"(v.x), "=r"(v.y) : "r"(a) : "memory"); return v; }
DEVI uint32_t lds32(uint32_t a) { uint32_t v; asm volatile("ld.shared.u32 %0, [%1];" : "=r"(v) : "r"(a) : "memory"); return v; }
DEVI uint32_t lds32v(uint32_t a) { uint32_t v; asm volatile("ld.volatile.shared.u32 %0, [%1];" : "=r"(v) : "r"(a) : "memory"); return v; }
DEVI uint4 lds128v(uint32_t a) { uint4 v; asm volatile("ld.volatile.shared.v4.u32 {%0,%1,%2,%3}, [%4];" : "=r"(v.x), "=r"(v.y), "=r"(v.z), "=r"(v.w) : "r"(a) : "memory"); return v; }
DEVI uint32_t lds16(uint32_t a) { uint32_t v; asm volatile("ld.shared.u16 %0, [%1];" : "=r"(v) : "r"(a) : "memory"); return v; }
DEVI uint4 ldsm4(uint32_t a) { uint4 v; asm volatile("ldmatrix.sync.aligned.m8n8.x4.shared.b16 {%0,%1,%2,%3}, [%4];" : "=r"(v.x), "=r"(v.y), "=r"(v.z), "=r"(v.w) : "r"(a) : "memory"); return v; }
DEVI uint4 ldsm4t(uint32_t a) { uint4 v; asm volatile("ldmatrix.sync.aligned.m8n8.x4.trans.shared.b16 {%0,%1,%2,%3}, [%4];" : "=r"(v.x), "=r"(v.y), "=r"(v.z), "=r"(v.w) : "r"(a) : "memory"); return v; }
DEVI uint2 ldsm2(uint32_t a) { uint2 v; asm volatile("ldmatrix.sync.aligned.m8n8.x2.shared.b16 {%0,%1}, [%2];" : "=r"(v.x), "=r"(v.y) : "r"(a) : "memory"); return v; }
DEVI void stsm4t(uint32_t a, uint32_t x, uint32_t y, uint32_t z, uint32_t w) { asm volatile("stmatrix.sync.aligned.m8n8.x4.trans.shared.b16 [%0], {%1,%2,%3,%4};" :: "r"(a), "r"(x), "r"(y), "r"(z), "r"(w) : "memory"); }
DEVI void sts128(uint32_t a, uint32_t x, uint32_t y, uint32_t z, uint32_t w) { asm volatile("st.shared.v4.u32 [%0], {%1,%2,%3,%4};" :: "r"(a), "r"(x), "r"(y), "r"(z), "r"(w) : "memory"); }
DEVI void sts64(uint32_t a, uint32_t x, uint32_t y) { asm volatile("st.shared.v2.u32 [%0], {%1,%2};" :: "r"(a), "r"(x), "r"(y) : "memory"); }
DEVI void sts32(uint32_t a, uint32_t x) { asm volatile("st.shared.u32 [%0], %1;" :: "r"(a), "r"(x) : "memory"); }
DEVI void sts32p(uint32_t a, uint32_t x, bool pred) { asm volatile("{.reg .pred p; setp.ne.u32 p, %2, 0; @p st.shared.u32 [%0], %1;}" :: "r"(a), "r"(x), "r"((uint32_t)pred) : "memory"); }
DEVI void sta128(uint32_t a, uint32_t x, uint32_t y, uint32_t z, uint32_t w, uint32_t bar) {
    asm volatile("st.async.weak.shared::cluster.mbarrier::complete_tx::bytes.v4.b32 [%0], {%1,%2,%3,%4}, [%5];" :: "r"(a), "r"(x), "r"(y), "r"(z), "r"(w), "r"(bar) : "memory");
}
DEVI void sta128p(uint32_t a, uint32_t x, uint32_t y, uint32_t z, uint32_t w, uint32_t bar, bool pred) {
    asm volatile("{.reg .pred p; setp.ne.u32 p, %6, 0; @p st.async.weak.shared::cluster.mbarrier::complete_tx::bytes.v4.b32 [%0], {%1,%2,%3,%4}, [%5];}" :: "r"(a), "r"(x), "r"(y), "r"(z), "r"(w), "r"(bar), "r"((uint32_t)pred) : "memory");
}
DEVI void sta64(uint32_t a, uint32_t x, uint32_t y, uint32_t bar) {
    asm volatile("st.async.weak.shared::cluster.mbarrier::complete_tx::bytes.v2.b32 [%0], {%1,%2}, [%3];" :: "r"(a), "r"(x), "r"(y), "r"(bar) : "memory");
}
DEVI void sta32(uint32_t a, uint32_t x, uint32_t bar) {
    asm volatile("st.async.weak.shared::cluster.mbarrier::complete_tx::bytes.b32 [%0], %1, [%2];" :: "r"(a), "r"(x), "r"(bar) : "memory");
}
DEVI uint4 ldg_pkt(const void* p) {
    uint4 v;
    asm volatile("ld.relaxed.gpu.global.v4.u32 {%0,%1,%2,%3}, [%4];" : "=r"(v.x), "=r"(v.y), "=r"(v.z), "=r"(v.w) : "l"(p) : "memory");
    return v;
}
DEVI void ldg_pkt_if(uint4& v, const void* p, bool pred) {
    asm volatile("{.reg .pred p; setp.ne.u32 p, %5, 0; @p ld.relaxed.gpu.global.v4.u32 {%0,%1,%2,%3}, [%4];}"
        : "+r"(v.x), "+r"(v.y), "+r"(v.z), "+r"(v.w) : "l"(p), "r"((uint32_t)pred) : "memory");
}
DEVI void ldg_pkt_retry(uint4& v, const void* p, uint32_t tag) {
    asm volatile("{.reg .pred p; .reg .b32 t; lop3.b32 t, %0, %5, 1, 0x28; setp.ne.u32 p, t, 0; @p ld.relaxed.gpu.global.v4.u32 {%0,%1,%2,%3}, [%4];}"
        : "+r"(v.x), "+r"(v.y), "+r"(v.z), "+r"(v.w) : "l"(p), "r"(tag) : "memory");
}
DEVI void stg_pkt(void* p, uint32_t x, uint32_t y, uint32_t z, uint32_t w) {
    asm volatile("st.relaxed.gpu.global.v4.u32 [%0], {%1,%2,%3,%4};" :: "l"(p), "r"(x), "r"(y), "r"(z), "r"(w) : "memory");
}
DEVI uint32_t ldg_word(const void* p) { uint32_t v; asm volatile("ld.relaxed.gpu.global.u32 %0, [%1];" : "=r"(v) : "l"(p) : "memory"); return v; }
DEVI void stg_word(void* p, uint32_t x, bool pred) {
    asm volatile("{.reg .pred p; setp.ne.u32 p, %2, 0; @p st.relaxed.gpu.global.u32 [%0], %1;}" :: "l"(p), "r"(x), "r"((uint32_t)pred) : "memory");
}
DEVI uint2 ldg64nc(const void* p) { uint2 v; asm volatile("ld.global.nc.L1::no_allocate.v2.u32 {%0,%1}, [%2];" : "=r"(v.x), "=r"(v.y) : "l"(p)); return v; }
DEVI void prefetch_l2(const void* p, uint32_t bytes) { asm volatile("cp.async.bulk.prefetch.L2.global [%0], %1;" :: "l"(p), "r"(bytes) : "memory"); }
DEVI uint4 ldg128(const void* p) { uint4 v; asm volatile("ld.global.cg.v4.u32 {%0,%1,%2,%3}, [%4];" : "=r"(v.x), "=r"(v.y), "=r"(v.z), "=r"(v.w) : "l"(p) : "memory"); return v; }
DEVI uint2 ldg64(const void* p) { uint2 v; asm volatile("ld.global.cg.v2.u32 {%0,%1}, [%2];" : "=r"(v.x), "=r"(v.y) : "l"(p) : "memory"); return v; }
DEVI uint32_t ldg32(const void* p) { uint32_t v; asm volatile("ld.global.cg.u32 %0, [%1];" : "=r"(v) : "l"(p) : "memory"); return v; }
DEVI void stg128(void* p, uint32_t x, uint32_t y, uint32_t z, uint32_t w) { asm volatile("st.global.cg.v4.u32 [%0], {%1,%2,%3,%4};" :: "l"(p), "r"(x), "r"(y), "r"(z), "r"(w) : "memory"); }
DEVI void stg128p(void* p, uint32_t x, uint32_t y, uint32_t z, uint32_t w, bool pred) { asm volatile("{.reg .pred p; setp.ne.u32 p, %5, 0; @p st.global.cg.v4.u32 [%0], {%1,%2,%3,%4};}" :: "l"(p), "r"(x), "r"(y), "r"(z), "r"(w), "r"((uint32_t)pred) : "memory"); }
DEVI void stg64(void* p, uint32_t x, uint32_t y) { asm volatile("st.global.cg.v2.u32 [%0], {%1,%2};" :: "l"(p), "r"(x), "r"(y) : "memory"); }
DEVI void stg32(void* p, uint32_t x) { asm volatile("st.global.cg.u32 [%0], %1;" :: "l"(p), "r"(x) : "memory"); }
DEVI void cp16(uint32_t dst, const void* src) { asm volatile("cp.async.cg.shared.global [%0], [%1], 16;" :: "r"(dst), "l"(src) : "memory"); }
DEVI void cp16_if(uint32_t dst, const void* src, bool pred) { asm volatile("{.reg .pred p; setp.ne.u32 p, %2, 0; @p cp.async.cg.shared.global [%0], [%1], 16;}" :: "r"(dst), "l"(src), "r"((uint32_t)pred) : "memory"); }
DEVI void cp_commit() { asm volatile("cp.async.commit_group;" ::: "memory"); }
DEVI void cp4(uint32_t dst, const void* src) { asm volatile("cp.async.ca.shared.global [%0], [%1], 4;" :: "r"(dst), "l"(src) : "memory"); }
template <int N> DEVI void cp_wait() { asm volatile("cp.async.wait_group %0;" :: "n"(N) : "memory"); }
DEVI void cp_wait_all() { asm volatile("cp.async.wait_all;" ::: "memory"); }
DEVI void bar_sync(int id, int n) { asm volatile("bar.sync %0, %1;" :: "r"(id), "r"(n) : "memory"); }
DEVI void bar_arrive(int id, int n) { asm volatile("bar.arrive %0, %1;" :: "r"(id), "r"(n) : "memory"); }
DEVI void fence_async_smem() { asm volatile("fence.proxy.async.shared::cta;" ::: "memory"); }
DEVI void fence_async_global() { asm volatile("fence.proxy.async.global;" ::: "memory"); }
DEVI void mbar_init(uint32_t b, int n) { asm volatile("mbarrier.init.shared.b64 [%0], %1;" :: "r"(b), "r"(n) : "memory"); }
DEVI void mbar_expect(uint32_t b, uint32_t bytes, bool pred) {
    asm volatile("{.reg .pred p; setp.ne.u32 p, %2, 0; @p mbarrier.arrive.expect_tx.shared.b64 _, [%0], %1;}" :: "r"(b), "r"(bytes), "r"((uint32_t)pred) : "memory");
}
DEVI void mbar_arrive(uint32_t b, bool pred) { asm volatile("{.reg .pred p; setp.ne.u32 p, %1, 0; @p mbarrier.arrive.shared.b64 _, [%0];}" :: "r"(b), "r"((uint32_t)pred) : "memory"); }
DEVI void mbar_arrive_all3(uint32_t b, uint32_t lane) {
    asm volatile("{.reg .pred p; .reg .u32 a; setp.lt.u32 p, %1, 3; @p mapa.shared::cluster.u32 a, %0, %1; @p mbarrier.arrive.relaxed.cluster.shared::cluster.b64 _, [a];}" :: "r"(b), "r"(lane) : "memory");
}
#define FAULT "or.b32 n, n, 1; st.volatile.shared.u32 [n], n;\n"
#define LIM1 "400000"
#define LIM2 "2000000"
DEVI void fault_if(bool p, uint32_t n) { asm volatile("{.reg .pred p; setp.ne.u32 p, %0, 0; @p st.volatile.shared.u32 [%1], %1;}" :: "r"((uint32_t)p), "r"(n | 1) : "memory"); }
DEVI void mbar_wait(uint32_t b, uint32_t parity) {
    asm volatile("{.reg .pred p; .reg .u32 n;\n"
        "mbarrier.try_wait.parity.shared::cta.b64 p, [%0], %1;\n"
        "@p bra.uni D%=;\n"
        "mov.u32 n, 0;\n"
        "W%=: mbarrier.try_wait.parity.shared::cta.b64 p, [%0], %1;\n"
        "@p bra.uni D%=;\n"
        "add.u32 n, n, 1; setp.lt.u32 p, n, " LIM1 "; @p bra.uni W%=;\n"
        FAULT
        "D%=:}" :: "r"(b), "r"(parity) : "memory");
}
constexpr int POLL_LIMIT = 2000000;
DEVI void cnt_wait(const unsigned* c, unsigned target) {
    asm volatile("{.reg .pred p; .reg .u32 n, v;\n"
        "ld.acquire.gpu.global.u32 v, [%0];\n"
        "setp.ge.u32 p, v, %1; vote.sync.all.pred p, p, 0xffffffff; @p bra.uni D%=;\n"
        "mov.u32 n, 0;\n"
        "W%=: ld.acquire.gpu.global.u32 v, [%0];\n"
        "setp.ge.u32 p, v, %1; vote.sync.all.pred p, p, 0xffffffff; @p bra.uni D%=;\n"
        "add.u32 n, n, 1; setp.lt.u32 p, n, " LIM2 "; @p bra.uni W%=;\n"
        FAULT
        "D%=:}" :: "l"(c), "r"(target) : "memory");
}
DEVI void cnt_add(unsigned* c, int lane) {
    asm volatile("{.reg .pred p; setp.eq.u32 p, %1, 0; fence.acq_rel.gpu; bar.warp.sync 0xffffffff; @p red.relaxed.gpu.global.add.u32 [%0], 1;}" :: "l"(c + lane), "r"(lane) : "memory");
}
DEVI void cnt_hint(unsigned* c, int lane) {
    asm volatile("{.reg .pred p; setp.eq.u32 p, %1, 0; @p red.relaxed.gpu.global.add.u32 [%0], 1;}" :: "l"(c + lane), "r"(lane) : "memory");
}
DEVI uint32_t ring_tag(int u, uint32_t ep) { return (u / RING + ep * ((NT - 1 - u % RING) / RING + 1) + 1) & 1; }
DEVI uint32_t lop_bad(uint32_t acc, uint32_t x, uint32_t y, uint32_t tag) {
    uint32_t d; asm("{.reg .b32 t; lop3.b32 t, %2, %3, %4, 0x7e; or.b32 %0, t, %1;}" : "=r"(d) : "r"(acc), "r"(x), "r"(y), "r"(tag)); return d;
}
template <int N> DEVI void validate(uint4* v, const void* p, int step, uint32_t tag) {
    for (int n = 0;; n++) {
        uint32_t bad = 0;
#pragma unroll
        for (int i = 0; i < N; i += 2) bad = lop_bad(bad, v[i].x, v[i + 1 < N ? i + 1 : i].x, tag);
        if (!__any_sync(~0u, bad & 1)) break;
#pragma unroll
        for (int i = 0; i < N; i++) v[i] = ldg_pkt(static_cast<const char*>(p) + i * step);
        fault_if(n > POLL_LIMIT, n);
    }
}
DEVI uint32_t page_par(uint32_t off) { return __popc((off >> 12) & 0xb2) & 1; }
DEVI uint32_t inbox_off(int b) { return (b >> 1) * 32768 + (b & 1) * 8192; }
DEVI uint32_t mem_off(int w, int i) { return 0x180000 + w * 1024 + (i & 1) * 512 + (i & 3) * 16384 + (i < 4 ? 0 : i < 8 ? 0x30000 : 0x40000); }
DEVI void sched_fence(uint32_t zero, uint32_t id) { asm volatile("{.reg .pred p; setp.ne.u32 p, %0, %1; @p bra.uni D%=; exit; D%=:}" :: "r"(zero), "r"(id) : "memory"); }
DEVI uint32_t clk() { uint32_t c; asm volatile("mov.u32 %0, %%clock;" : "=r"(c) :: "memory"); return c; }
DEVI void delay(uint32_t n) {
    if (n) asm volatile("{.reg .pred p; .reg .u32 c, e; mov.u32 e, %%clock;\n W%=: mov.u32 c, %%clock; sub.u32 c, c, e; setp.lt.u32 p, c, %0; @p bra.uni W%=;}" :: "r"(n) : "memory");
}
DEVI void wg_fence() { asm volatile("wgmma.fence.sync.aligned;" ::: "memory"); }
DEVI void wg_commit() { asm volatile("wgmma.commit_group.sync.aligned;" ::: "memory"); }
template <int N> DEVI void wg_wait() { asm volatile("wgmma.wait_group.sync.aligned %0;" :: "n"(N) : "memory"); }
DEVI uint64_t mkdesc(uint32_t lo, uint32_t hi) { uint64_t d; asm("mov.b64 %0, {%1,%2};" : "=l"(d) : "r"(lo), "r"(hi)); return d; }
DEVI void cluster_arrive() { asm volatile("barrier.cluster.arrive.relaxed.aligned;" ::: "memory"); }
DEVI void cluster_wait() { asm volatile("barrier.cluster.wait.aligned;" ::: "memory"); }
DEVI void cluster_sync() { asm volatile("barrier.cluster.arrive.aligned;\n barrier.cluster.wait.aligned;" ::: "memory"); }
DEVI void wgmma_ss16t(float (&d)[8], uint64_t da, uint64_t db, int acc) {
    asm volatile("{.reg .pred p; setp.ne.b32 p, %10, 0;\n"
        "wgmma.mma_async.sync.aligned.m64n16k16.f32.bf16.bf16 {%0,%1,%2,%3,%4,%5,%6,%7}, %8, %9, p, 1, 1, 0, 1;}"
        : "+f"(d[0]), "+f"(d[1]), "+f"(d[2]), "+f"(d[3]), "+f"(d[4]), "+f"(d[5]), "+f"(d[6]), "+f"(d[7])
        : "l"(da), "l"(db), "r"(acc));
}
DEVI void wgmma_ss16a(float (&d)[8], uint64_t da, uint64_t db, int acc) {
    asm volatile("{.reg .pred p; setp.ne.b32 p, %10, 0;\n"
        "wgmma.mma_async.sync.aligned.m64n16k16.f32.bf16.bf16 {%0,%1,%2,%3,%4,%5,%6,%7}, %8, %9, p, 1, 1, 1, 0;}"
        : "+f"(d[0]), "+f"(d[1]), "+f"(d[2]), "+f"(d[3]), "+f"(d[4]), "+f"(d[5]), "+f"(d[6]), "+f"(d[7])
        : "l"(da), "l"(db), "r"(acc));
}
DEVI void wgmma_ss64(float (&d)[32], uint64_t da, uint64_t db, int acc) {
    asm volatile("{.reg .pred p; setp.ne.b32 p, %34, 0;\n"
        "wgmma.mma_async.sync.aligned.m64n64k16.f32.bf16.bf16 {%0,%1,%2,%3,%4,%5,%6,%7,%8,%9,%10,%11,%12,%13,%14,%15,%16,%17,%18,%19,%20,%21,%22,%23,%24,%25,%26,%27,%28,%29,%30,%31}, %32, %33, p, 1, 1, 0, 0;}"
        : "+f"(d[0]), "+f"(d[1]), "+f"(d[2]), "+f"(d[3]), "+f"(d[4]), "+f"(d[5]), "+f"(d[6]), "+f"(d[7]), "+f"(d[8]), "+f"(d[9]), "+f"(d[10]), "+f"(d[11]), "+f"(d[12]), "+f"(d[13]), "+f"(d[14]), "+f"(d[15]), "+f"(d[16]), "+f"(d[17]), "+f"(d[18]), "+f"(d[19]), "+f"(d[20]), "+f"(d[21]), "+f"(d[22]), "+f"(d[23]), "+f"(d[24]), "+f"(d[25]), "+f"(d[26]), "+f"(d[27]), "+f"(d[28]), "+f"(d[29]), "+f"(d[30]), "+f"(d[31])
        : "l"(da), "l"(db), "r"(acc));
}
DEVI void wgmma_rs16t(float (&d)[8], uint32_t a0, uint32_t a1, uint32_t a2, uint32_t a3, uint64_t db, int acc) {
    asm volatile("{.reg .pred p; setp.ne.b32 p, %13, 0;\n"
        "wgmma.mma_async.sync.aligned.m64n16k16.f32.bf16.bf16 {%0,%1,%2,%3,%4,%5,%6,%7}, {%8,%9,%10,%11}, %12, p, 1, 1, 1;}"
        : "+f"(d[0]), "+f"(d[1]), "+f"(d[2]), "+f"(d[3]), "+f"(d[4]), "+f"(d[5]), "+f"(d[6]), "+f"(d[7])
        : "r"(a0), "r"(a1), "r"(a2), "r"(a3), "l"(db), "r"(acc));
}
DEVI void wgmma_rs64(float (&d)[32], uint32_t a0, uint32_t a1, uint32_t a2, uint32_t a3, uint64_t db, int acc) {
    asm volatile("{.reg .pred p; setp.ne.b32 p, %37, 0;\n"
        "wgmma.mma_async.sync.aligned.m64n64k16.f32.bf16.bf16 {%0,%1,%2,%3,%4,%5,%6,%7,%8,%9,%10,%11,%12,%13,%14,%15,%16,%17,%18,%19,%20,%21,%22,%23,%24,%25,%26,%27,%28,%29,%30,%31}, {%32,%33,%34,%35}, %36, p, 1, 1, 0;}"
        : "+f"(d[0]), "+f"(d[1]), "+f"(d[2]), "+f"(d[3]), "+f"(d[4]), "+f"(d[5]), "+f"(d[6]), "+f"(d[7]), "+f"(d[8]), "+f"(d[9]), "+f"(d[10]), "+f"(d[11]), "+f"(d[12]), "+f"(d[13]), "+f"(d[14]), "+f"(d[15]), "+f"(d[16]), "+f"(d[17]), "+f"(d[18]), "+f"(d[19]), "+f"(d[20]), "+f"(d[21]), "+f"(d[22]), "+f"(d[23]), "+f"(d[24]), "+f"(d[25]), "+f"(d[26]), "+f"(d[27]), "+f"(d[28]), "+f"(d[29]), "+f"(d[30]), "+f"(d[31])
        : "r"(a0), "r"(a1), "r"(a2), "r"(a3), "l"(db), "r"(acc));
}
DEVI void wgmma_ss168t(float (&d)[84], uint64_t da, uint64_t db, int acc) {
    asm volatile("{.reg .pred p; setp.ne.b32 p, %86, 0;\n"
        "wgmma.mma_async.sync.aligned.m64n168k16.f32.bf16.bf16 {%0,%1,%2,%3,%4,%5,%6,%7,%8,%9,%10,%11,%12,%13,%14,%15,%16,%17,%18,%19,%20,%21,%22,%23,%24,%25,%26,%27,%28,%29,%30,%31,%32,%33,%34,%35,%36,%37,%38,%39,%40,%41,%42,%43,%44,%45,%46,%47,%48,%49,%50,%51,%52,%53,%54,%55,%56,%57,%58,%59,%60,%61,%62,%63,%64,%65,%66,%67,%68,%69,%70,%71,%72,%73,%74,%75,%76,%77,%78,%79,%80,%81,%82,%83}, %84, %85, p, 1, 1, 0, 1;}"
        : "+f"(d[0]), "+f"(d[1]), "+f"(d[2]), "+f"(d[3]), "+f"(d[4]), "+f"(d[5]), "+f"(d[6]), "+f"(d[7]), "+f"(d[8]), "+f"(d[9]), "+f"(d[10]), "+f"(d[11]), "+f"(d[12]), "+f"(d[13]), "+f"(d[14]), "+f"(d[15]), "+f"(d[16]), "+f"(d[17]), "+f"(d[18]), "+f"(d[19]), "+f"(d[20]), "+f"(d[21]), "+f"(d[22]), "+f"(d[23]), "+f"(d[24]), "+f"(d[25]), "+f"(d[26]), "+f"(d[27]), "+f"(d[28]), "+f"(d[29]), "+f"(d[30]), "+f"(d[31]), "+f"(d[32]), "+f"(d[33]), "+f"(d[34]), "+f"(d[35]), "+f"(d[36]), "+f"(d[37]), "+f"(d[38]), "+f"(d[39]), "+f"(d[40]), "+f"(d[41]), "+f"(d[42]), "+f"(d[43]), "+f"(d[44]), "+f"(d[45]), "+f"(d[46]), "+f"(d[47]), "+f"(d[48]), "+f"(d[49]), "+f"(d[50]), "+f"(d[51]), "+f"(d[52]), "+f"(d[53]), "+f"(d[54]), "+f"(d[55]), "+f"(d[56]), "+f"(d[57]), "+f"(d[58]), "+f"(d[59]), "+f"(d[60]), "+f"(d[61]), "+f"(d[62]), "+f"(d[63]), "+f"(d[64]), "+f"(d[65]), "+f"(d[66]), "+f"(d[67]), "+f"(d[68]), "+f"(d[69]), "+f"(d[70]), "+f"(d[71]), "+f"(d[72]), "+f"(d[73]), "+f"(d[74]), "+f"(d[75]), "+f"(d[76]), "+f"(d[77]), "+f"(d[78]), "+f"(d[79]), "+f"(d[80]), "+f"(d[81]), "+f"(d[82]), "+f"(d[83])
        : "l"(da), "l"(db), "r"(acc));
}
DEVI void wgmma_rs96t(float (&d)[48], uint32_t a0, uint32_t a1, uint32_t a2, uint32_t a3, uint64_t db, int acc) {
    asm volatile("{.reg .pred p; setp.ne.b32 p, %53, 0;\n"
        "wgmma.mma_async.sync.aligned.m64n96k16.f32.bf16.bf16 {%0,%1,%2,%3,%4,%5,%6,%7,%8,%9,%10,%11,%12,%13,%14,%15,%16,%17,%18,%19,%20,%21,%22,%23,%24,%25,%26,%27,%28,%29,%30,%31,%32,%33,%34,%35,%36,%37,%38,%39,%40,%41,%42,%43,%44,%45,%46,%47}, {%48,%49,%50,%51}, %52, p, 1, 1, 1;}"
        : "+f"(d[0]), "+f"(d[1]), "+f"(d[2]), "+f"(d[3]), "+f"(d[4]), "+f"(d[5]), "+f"(d[6]), "+f"(d[7]), "+f"(d[8]), "+f"(d[9]), "+f"(d[10]), "+f"(d[11]), "+f"(d[12]), "+f"(d[13]), "+f"(d[14]), "+f"(d[15]), "+f"(d[16]), "+f"(d[17]), "+f"(d[18]), "+f"(d[19]), "+f"(d[20]), "+f"(d[21]), "+f"(d[22]), "+f"(d[23]), "+f"(d[24]), "+f"(d[25]), "+f"(d[26]), "+f"(d[27]), "+f"(d[28]), "+f"(d[29]), "+f"(d[30]), "+f"(d[31]), "+f"(d[32]), "+f"(d[33]), "+f"(d[34]), "+f"(d[35]), "+f"(d[36]), "+f"(d[37]), "+f"(d[38]), "+f"(d[39]), "+f"(d[40]), "+f"(d[41]), "+f"(d[42]), "+f"(d[43]), "+f"(d[44]), "+f"(d[45]), "+f"(d[46]), "+f"(d[47])
        : "r"(a0), "r"(a1), "r"(a2), "r"(a3), "l"(db), "r"(acc));
}
DEVI void wgmma_rs192t(float (&d)[96], uint32_t a0, uint32_t a1, uint32_t a2, uint32_t a3, uint64_t db, int acc) {
    asm volatile("{.reg .pred p; setp.ne.b32 p, %101, 0;\n"
        "wgmma.mma_async.sync.aligned.m64n192k16.f32.bf16.bf16 {%0,%1,%2,%3,%4,%5,%6,%7,%8,%9,%10,%11,%12,%13,%14,%15,%16,%17,%18,%19,%20,%21,%22,%23,%24,%25,%26,%27,%28,%29,%30,%31,%32,%33,%34,%35,%36,%37,%38,%39,%40,%41,%42,%43,%44,%45,%46,%47,%48,%49,%50,%51,%52,%53,%54,%55,%56,%57,%58,%59,%60,%61,%62,%63,%64,%65,%66,%67,%68,%69,%70,%71,%72,%73,%74,%75,%76,%77,%78,%79,%80,%81,%82,%83,%84,%85,%86,%87,%88,%89,%90,%91,%92,%93,%94,%95}, {%96,%97,%98,%99}, %100, p, 1, 1, 1;}"
        : "+f"(d[0]), "+f"(d[1]), "+f"(d[2]), "+f"(d[3]), "+f"(d[4]), "+f"(d[5]), "+f"(d[6]), "+f"(d[7]), "+f"(d[8]), "+f"(d[9]), "+f"(d[10]), "+f"(d[11]), "+f"(d[12]), "+f"(d[13]), "+f"(d[14]), "+f"(d[15]), "+f"(d[16]), "+f"(d[17]), "+f"(d[18]), "+f"(d[19]), "+f"(d[20]), "+f"(d[21]), "+f"(d[22]), "+f"(d[23]), "+f"(d[24]), "+f"(d[25]), "+f"(d[26]), "+f"(d[27]), "+f"(d[28]), "+f"(d[29]), "+f"(d[30]), "+f"(d[31]), "+f"(d[32]), "+f"(d[33]), "+f"(d[34]), "+f"(d[35]), "+f"(d[36]), "+f"(d[37]), "+f"(d[38]), "+f"(d[39]), "+f"(d[40]), "+f"(d[41]), "+f"(d[42]), "+f"(d[43]), "+f"(d[44]), "+f"(d[45]), "+f"(d[46]), "+f"(d[47]), "+f"(d[48]), "+f"(d[49]), "+f"(d[50]), "+f"(d[51]), "+f"(d[52]), "+f"(d[53]), "+f"(d[54]), "+f"(d[55]), "+f"(d[56]), "+f"(d[57]), "+f"(d[58]), "+f"(d[59]), "+f"(d[60]), "+f"(d[61]), "+f"(d[62]), "+f"(d[63]), "+f"(d[64]), "+f"(d[65]), "+f"(d[66]), "+f"(d[67]), "+f"(d[68]), "+f"(d[69]), "+f"(d[70]), "+f"(d[71]), "+f"(d[72]), "+f"(d[73]), "+f"(d[74]), "+f"(d[75]), "+f"(d[76]), "+f"(d[77]), "+f"(d[78]), "+f"(d[79]), "+f"(d[80]), "+f"(d[81]), "+f"(d[82]), "+f"(d[83]), "+f"(d[84]), "+f"(d[85]), "+f"(d[86]), "+f"(d[87]), "+f"(d[88]), "+f"(d[89]), "+f"(d[90]), "+f"(d[91]), "+f"(d[92]), "+f"(d[93]), "+f"(d[94]), "+f"(d[95])
        : "r"(a0), "r"(a1), "r"(a2), "r"(a3), "l"(db), "r"(acc));
}

#define TRD(t, i)
namespace km {
#define NSS 6
#define RG "184"
#define RW "136"
#define NFL 3
#define NR1 3
#define NR2 3
#define FK 5
#define NGAP 8
constexpr int O_H = 0;
constexpr int O_MB = 73728;
constexpr int O_VX = 96768;
constexpr int O_KX = 113152;
constexpr int O_QX = 119296;
constexpr int O_VM = 125440;
constexpr int O_KM = 129536;
constexpr int O_QM = 131072;
constexpr int O_SM = 132608;
constexpr int O_ST = 135168;
constexpr int O_OX = 145408;
constexpr int O_WO = 149504;
constexpr int O_OS = O_WO;
constexpr int O_WS = O_WO + 49152;
constexpr int O_BAR = O_WS + NSS * 4096;
constexpr int SMEM = O_BAR + 128 + 1024 + TR_BYTES;
enum { B_X = 0, B_XFREE = 8, B_WIN = 16, B_VX = 24, B_SM = 32, B_ST = 40, B_SU = 48, B_EP = 56 };
#define DLY1 (100 * w)
#define DLY2 300
#define XON 1
#define GON 1
#define DLY0 1000
#define PFON 0
#define PLACE 1
#define XST 0
#define IV1 200
#define IV2 200
constexpr uint32_t DESC_HI = (1024 >> 4) | (1u << 30);
constexpr float SC = 0.08838834764831845f * 1.4426950408889634f;
}

__global__ void __cluster_dims__(3, 1, 1) __launch_bounds__(384, 1)
k_main(const __nv_bfloat16* __restrict__ x0, const __nv_bfloat16* __restrict__ wqkv, const __nv_bfloat16* __restrict__ wo,
       const __nv_bfloat16* __restrict__ mem0, const __nv_bfloat16* __restrict__ Wq, const __nv_bfloat16* __restrict__ Wk,
       const __nv_bfloat16* __restrict__ Wv, const __nv_bfloat16* __restrict__ Wo) {
    using namespace km;
    extern __shared__ unsigned char smem_raw[];
    const uint32_t sb = (smem_u32(smem_raw) + 1023) & ~1023u;
    const int tid = threadIdx.x, lane = tid & 31, warp = __shfl_sync(~0u, tid >> 5, 0);
    uint32_t l16 = __shfl_sync(~0u, lane * 16, lane);
#define OPQ() asm volatile("" : "+r"(l16))
    const int b = blockIdx.x, h = b / 3, r = b % 3;
    const int nq = r == 2 ? 2 : 3;
    const uint32_t bar = sb + O_BAR;
    asm volatile("griddepcontrol.launch_dependents;");
    if (tid == 352) {
        prefetch_l2(wqkv + b * (6 * 1728), 6 * 3456); prefetch_l2(x0 + b * (2 * DM), 2 * 1152); prefetch_l2(wo + b * (6 * DM), 6 * 1152);
    }
    if (tid == 320) sts32(bar + 64, ldg32(&g_epoch));
#define EP lds32(bar + 64)
    TR_INIT(bar + 128);
    TRG(79, 0);
    uint32_t roff0, roff1;
    {
        uint32_t y0, y1;
        asm("mapa.shared::cluster.u32 %0, %1, %2;" : "=r"(y0) : "r"(sb), "r"((r + 1) % 3));
        asm("mapa.shared::cluster.u32 %0, %1, %2;" : "=r"(y1) : "r"(sb), "r"((r + 2) % 3));
        roff0 = y0 - sb; roff1 = y1 - sb;
    }
#define LSWAP ((l16 & 0x70) | ((l16 & 0x80) << 1) | ((l16 & 0x100) >> 1))
    const uint32_t nv_remote = 8 - (8 - 2 * nq);

    if (warp < 8) {
        asm volatile("setmaxnreg.inc.sync.aligned.u32 " RG ";");
        constexpr int SSP = 36 / NSS;
#define IS_SS(kk) ((kk) % SSP == 3)
#define AI(kk) (4 * ((kk) - ((kk) + SSP - 4) / SSP))
        uint32_t a[144 - 4 * NSS];
        {
            const int ci = tid & 15, slot = ci >> 1, d0 = tid >> 4;
            const __nv_bfloat16* src = slot < nq ? Wq + (3 * r + slot) * 16 : slot < 2 * nq ? Wk + (3 * r + slot - nq) * 16 : Wv + (2 * r + slot - 2 * nq) * 16;
            src += h * 128 + (ci & 1) * 8 + d0 * 4096;
            delay(DLY0);
            auto issue = [&](int q) {
#pragma unroll
                for (int i = 0; i < 3; i++) if (q < 12) cp16(sb + (q * 3 + i) * 4096 + d0 * 256 + ((ci ^ (d0 & 7)) << 4), src + (size_t)(q * 3 + i) * 65536);
                asm volatile("cp.async.commit_group;" ::: "memory");
            };
#pragma unroll
            for (int q = 0; q < NFL; q++) issue(q);
            TR1(1);
            const int mi = lane >> 3;
            const uint32_t ad = sb + ((mi >> 1) * 8 + (lane & 7)) * 256 + (((warp * 2 + (mi & 1)) ^ (lane & 7)) << 4);
#pragma unroll
            for (int kk = 0; kk < 36; kk++) {
                if (kk % 3 == 0) { cp_wait<NFL - 1>(); issue(kk / 3 + NFL); bar_sync(10, 256); }
                const uint4 f = ldsm4t(ad + kk * 4096);
                if (IS_SS(kk)) {
                    const uint32_t o0 = sb + O_WS + (kk / SSP) * 4096 + warp * 512 + lane * 4;
                    sts32(o0, f.x); sts32(o0 + 256, f.y); sts32(o0 + 128, f.z); sts32(o0 + 384, f.w);
                } else { a[AI(kk)] = f.x; a[AI(kk) + 1] = f.y; a[AI(kk) + 2] = f.z; a[AI(kk) + 3] = f.w; }
            }
            TR1(2);
            bar_sync(9, 384);
#pragma unroll
            for (int i = 0; i < 9; i++) sts128(sb + O_H + i * 8192 + 4096 + tid * 16, 0, 0, 0, 0);
#pragma unroll
            for (int i = 0; i < 8; i++) if (i * 256 + tid < (O_OX - O_KX) / 16) sts128(sb + O_KX + i * 4096 + tid * 16, 0, 0, 0, 0);
            fence_async_smem();
            cluster_sync();
        }
        TR1(3);
        const int kind = warp < nq ? 0 : warp < 2 * nq ? 1 : 2;
        const int sl = kind == 0 ? warp : kind == 1 ? warp - nq : 2 * r + warp - 2 * nq;
        const uint32_t adX0 = sb + (kind == 0 ? O_QX : kind == 1 ? O_KX : O_VX) + sl * 2048;
        const uint32_t adM0 = sb + (kind == 0 ? O_QM : kind == 1 ? O_KM : O_VM) + sl * 512;
        const uint32_t hlo = (((sb + O_H) >> 4) & 0x3fff) | (1u << 16);
        const uint32_t mlo = (((sb + O_MB) >> 4) & 0x3fff) | (16u << 16);
        const uint32_t wlo = (((sb + O_WS + (warp >> 2) * 2048) >> 4) & 0x3fff) | (8u << 16);
        const int L = (warp >> 1) & 1, qh = warp & 1;
        const uint32_t st = sb + O_ST + warp * 1280;
        float s[5][4];

#pragma unroll 1
        for (int t = -1;; t++) {
            TR_ON(t);
            OPQ();
            const uint32_t adX = adX0 + l16, adM = adM0 + l16, l8 = l16 >> 1;
            const uint32_t lq = LSWAP;
            if (t >= 0) {
                {
                    float d0[8], d1[8];
#pragma unroll
                    for (int G = 0; G < 3; G++) {
                        if (warp < 4) bar_sync(1 + G, 160); else bar_sync(12 + G, 160);
                        if (G == 0) wg_fence();
#pragma unroll
                        for (int q = 0; q < 12; q++) {
                            const int kk = 12 * G + q;
                            const uint64_t db = mkdesc(mlo + kk * 32, 8);
                            if (IS_SS(kk)) wgmma_ss16t((kk & 1) ? d1 : d0, mkdesc(wlo + (kk / SSP) * 256, 16), db, 1);
                            else wgmma_rs16t((kk & 1) ? d1 : d0, a[AI(kk)], a[AI(kk) + 1], a[AI(kk) + 2], a[AI(kk) + 3], db, kk >= 2);
                            if (kk == 0) TR(0);
                        }
                    }
                    wg_commit(); wg_wait<0>();
                    TR(1);
                    const uint32_t p0 = pk(d0[0] + d1[0], d0[1] + d1[1]), p1 = pk(d0[2] + d1[2], d0[3] + d1[3]);
                    const uint32_t p2 = pk(d0[4] + d1[4], d0[5] + d1[5]), p3 = pk(d0[6] + d1[6], d0[7] + d1[7]);
                    if (kind == 2) {
                        sts128(adM, p0, p1, p2, p3);
                        bar_arrive(4, 384);
                        sta128(adM + roff0, p0, p1, p2, p3, bar + B_SM + roff0);
                        sta128(adM + roff1, p0, p1, p2, p3, bar + B_SM + roff1);
                    } else {
                        stsm4t(adM, p0, p1, p2, p3);
                        bar_arrive(4, 384);
                    }
                }
                if (warp < 4) {
                    {
                        uint4 q[3];
                        s[4][0] = s[4][1] = s[4][2] = s[4][3] = 0.f;
                        mbar_wait(bar + B_ST, t & 1);
                        bar_sync(5, 256);
                        const uint4 k01 = ldsm4(sb + O_KM + L * 256 + l16 + (l16 & 256));
                        const uint2 k2 = ldsm2(sb + O_KM + 1024 + L * 256 + l16);
#pragma unroll
                        for (int m = 0; m < 3; m++) q[m] = ldsm4(sb + O_QX + m * 2048 + warp * 512 + lq);
                        mma16(s[4], q[0].x, q[0].y, q[0].z, q[0].w, k01.x, k01.y);
                        mma16(s[4], q[1].x, q[1].y, q[1].z, q[1].w, k01.z, k01.w);
                        mma16(s[4], q[2].x, q[2].y, q[2].z, q[2].w, k2.x, k2.y);
                        const uint32_t w0 = pk(s[4][0], s[4][1]), w1 = pk(s[4][2], s[4][3]);
                        bar_arrive(11, 256);
                        sta64(st + l8 + 5120 + 1024 + roff0, w0, w1, bar + B_SU + roff0);
                        sta64(st + l8 + 1024 + roff1, w0, w1, bar + B_SU + roff1);
                    }
                    TR(2);
#pragma unroll
                    for (int src = 0; src < 2; src++) {
                        const uint4 u = lds128(st + src * 5120 + l16), v = lds128(st + src * 5120 + 512 + l16);
                        s[0][0] += bf_lo(u.x); s[0][1] += bf_hi(u.x); s[0][2] += bf_lo(u.y); s[0][3] += bf_hi(u.y);
                        s[1][0] += bf_lo(u.z); s[1][1] += bf_hi(u.z); s[1][2] += bf_lo(u.w); s[1][3] += bf_hi(u.w);
                        s[2][0] += bf_lo(v.x); s[2][1] += bf_hi(v.x); s[2][2] += bf_lo(v.y); s[2][3] += bf_hi(v.y);
                        s[3][0] += bf_lo(v.z); s[3][1] += bf_hi(v.z); s[3][2] += bf_lo(v.w); s[3][3] += bf_hi(v.w);
                    }
                    uint4 v0[3], v1[3];
#pragma unroll
                    for (int m = 0; m < 3; m++) {
                        v0[m] = lds128(sb + O_VX + (3 * r + m) * 2048 + L * 1024 + l16);
                    }
                    mbar_wait(bar + B_SM, t & 1);
                    mbar_wait(bar + B_SU, t & 1);
                    TR(3);
                    {
                        const uint2 x = lds64(st + 1024 + l8), y = lds64(st + 5120 + 1024 + l8);
                        s[4][0] += bf_lo(x.x) + bf_lo(y.x); s[4][1] += bf_hi(x.x) + bf_hi(y.x); s[4][2] += bf_lo(x.y) + bf_lo(y.y); s[4][3] += bf_hi(x.y) + bf_hi(y.y);
                    }
                    float mx0 = fmaxf(s[4][0], s[4][1]), mx1 = fmaxf(s[4][2], s[4][3]);
#pragma unroll
                    for (int n = 0; n < 4; n++) { mx0 = fmaxf(mx0, fmaxf(s[n][0], s[n][1])); mx1 = fmaxf(mx1, fmaxf(s[n][2], s[n][3])); }
#pragma unroll
                    for (int o = 1; o < 4; o <<= 1) { mx0 = fmaxf(mx0, __shfl_xor_sync(~0u, mx0, o)); mx1 = fmaxf(mx1, __shfl_xor_sync(~0u, mx1, o)); }
                    mx0 *= -SC; mx1 *= -SC;
                    float l0 = 0.f, l1 = 0.f;
                    uint32_t p[10];
#pragma unroll
                    for (int n = 0; n < 5; n++) {
                        const float e0 = ex2(fmaf(s[n][0], SC, mx0)), e1 = ex2(fmaf(s[n][1], SC, mx0));
                        const float e2 = ex2(fmaf(s[n][2], SC, mx1)), e3 = ex2(fmaf(s[n][3], SC, mx1));
                        l0 += e0 + e1; l1 += e2 + e3;
                        p[2 * n] = pk(e0, e1); p[2 * n + 1] = pk(e2, e3);
                    }
#pragma unroll
                    for (int o = 1; o < 4; o <<= 1) { l0 += __shfl_xor_sync(~0u, l0, o); l1 += __shfl_xor_sync(~0u, l1, o); }
                    l0 = rcp(l0); l1 = rcp(l1);
                    const uint32_t otag = ring_tag(t, EP);
#pragma unroll
                    for (int m = 0; m < 3; m++) {
                        float o0[4] = {0, 0, 0, 0}, o1[4] = {0, 0, 0, 0};
                        v1[m] = lds128(sb + O_VX + (3 * r + m) * 2048 + L * 1024 + 512 + l16);
                        const uint2 vm = lds64(sb + O_VM + (3 * r + m) * 512 + l16 + L * 8);
                        mma8(o0, p[0], p[1], v0[m].x); mma8(o1, p[0], p[1], v0[m].y); mma8(o0, p[2], p[3], v0[m].z); mma8(o1, p[2], p[3], v0[m].w);
                        mma8(o0, p[4], p[5], v1[m].x); mma8(o1, p[4], p[5], v1[m].y); mma8(o0, p[6], p[7], v1[m].z); mma8(o1, p[6], p[7], v1[m].w);
                        mma8(o0, p[8], p[9], vm.x); mma8(o1, p[8], p[9], vm.y);
                        sts128(sb + O_OS + warp * 1536 + m * 512 + l16, (pk(o0[0] * l0, o0[1] * l0) & ~1u) | otag, pk(o0[2] * l1, o0[3] * l1), pk(o1[0] * l0, o1[1] * l0), pk(o1[2] * l1, o1[3] * l1));
                    }
                    TR(4);
                }
            }
            if (t + 1 >= NT) break;
            {
                float d[32];
                mbar_wait(bar + B_X, (t + 1) & 1);
                if (warp < 4) bar_sync(7, 384); else if (t >= 0) bar_sync(11, 256);
                wg_fence();
                TR(6);
#pragma unroll
                for (int kk = 0; kk < 36; kk++) {
                    if (kk == NGAP) asm volatile("{.reg .pred p; setp.ge.u32 p, %0, 4; @p bar.sync 7, 384;}" :: "r"(warp) : "memory");
                    const uint64_t db = mkdesc(hlo + ((kk >> 2) * 8192 + (kk & 3) * 32) / 16, DESC_HI);
                    if (IS_SS(kk)) wgmma_ss64(d, mkdesc(wlo + (kk / SSP) * 256, 16), db, 1);
                    else wgmma_rs64(d, a[AI(kk)], a[AI(kk) + 1], a[AI(kk) + 2], a[AI(kk) + 3], db, kk > 0);
                }
                wg_commit();
                TR(5);
                mbar_wait(bar + B_WIN, (t + 1) & 1);
                wg_wait<0>();
                TR(7);
                mbar_arrive_all3(bar + B_XFREE, l16 >> 4);
                uint32_t p[16];
#pragma unroll
                for (int u = 0; u < 16; u++) p[u] = pk(d[2 * u], d[2 * u + 1]);
                if (kind == 2) {
#pragma unroll
                    for (int u = 0; u < 4; u++) sts128(adX + u * 512, p[4 * u], p[4 * u + 1], p[4 * u + 2], p[4 * u + 3]);
                } else {
#pragma unroll
                    for (int u = 0; u < 4; u++) stsm4t(adX + u * 512, p[4 * u], p[4 * u + 1], p[4 * u + 2], p[4 * u + 3]);
                }
                __syncwarp();
                asm volatile("{.reg .pred p; setp.eq.u32 p, %1, 0; @p mbarrier.arrive.shared.b64 _, [%0];}" :: "r"(bar + B_EP), "r"(l16) : "memory");
                if (kind == 2) {
                    fence_async_smem();
                    __syncwarp();
                    asm volatile("{.reg .pred p; setp.eq.u32 p, %5, 0;\n"
                        "@p cp.async.bulk.shared::cluster.shared::cta.mbarrier::complete_tx::bytes [%0], [%2], 2048, [%3];\n"
                        "@p cp.async.bulk.shared::cluster.shared::cta.mbarrier::complete_tx::bytes [%1], [%2], 2048, [%4];}"
                        :: "r"(adX0 + roff0), "r"(adX0 + roff1), "r"(adX0), "r"(bar + B_VX + roff0), "r"(bar + B_VX + roff1), "r"(l16) : "memory");
                }
                TR(8);
                {
                    const int lim = 16 * qh + (int)(l16 >> 6) - (int)((l16 >> 3) & 6);
#pragma unroll
                    for (int n = 0; n < 4; n++)
#pragma unroll
                        for (int j = 0; j < 4; j++) s[n][j] = (n == 0 && j >= 2) || 8 * (n - (j >> 1)) + (j & 1) <= lim ? 0.f : -1e30f;
                }
                if (warp < 4) {
                    mbar_wait(bar + B_EP, (t + 1) & 1);
#pragma unroll
                    for (int m = 0; m < 3; m++) {
                        const uint4 q = ldsm4(sb + O_QX + m * 2048 + warp * 512 + lq);
                        const uint4 k0 = ldsm4(sb + O_KX + m * 2048 + L * 1024 + l16);
                        const uint4 k1 = ldsm4(sb + O_KX + m * 2048 + L * 1024 + 512 + l16);
                        mma16(s[0], q.x, q.y, q.z, q.w, k0.x, k0.y);
                        mma16(s[1], q.x, q.y, q.z, q.w, k0.z, k0.w);
                        mma16(s[2], q.x, q.y, q.z, q.w, k1.x, k1.y);
                        mma16(s[3], q.x, q.y, q.z, q.w, k1.z, k1.w);
                    }
                    uint32_t w0 = pk(s[0][0], s[0][1]), w1 = pk(s[0][2], s[0][3]), w2 = pk(s[1][0], s[1][1]), w3 = pk(s[1][2], s[1][3]);
                    sta128(st + l16 + 5120 + roff0, w0, w1, w2, w3, bar + B_ST + roff0);
                    sta128(st + l16 + roff1, w0, w1, w2, w3, bar + B_ST + roff1);
                    w0 = pk(s[2][0], s[2][1]); w1 = pk(s[2][2], s[2][3]); w2 = pk(s[3][0], s[3][1]); w3 = pk(s[3][2], s[3][3]);
                    sta128p(st + l16 + 5120 + 512 + roff0, w0, w1, w2, w3, bar + B_ST + roff0, qh);
                    sta128p(st + l16 + 512 + roff1, w0, w1, w2, w3, bar + B_ST + roff1, qh);
                    TR(9);
                }
            }
        }
        if (warp >= 4) bar_sync(11, 256); else bar_arrive(7, 160);
        cluster_sync();
    } else {
        asm volatile("setmaxnreg.dec.sync.aligned.u32 " RW ";");
        const int w = warp - 8, t2 = tid - 256;
        if (t2 == 0) {
            mbar_init(bar + B_X, 1); mbar_init(bar + B_XFREE, 24); mbar_init(bar + B_WIN, 3);
            mbar_init(bar + B_VX, 1); mbar_init(bar + B_SM, 1); mbar_init(bar + B_ST, 1); mbar_init(bar + B_SU, 1); mbar_init(bar + B_EP, 8);
            asm volatile("fence.mbarrier_init.release.cluster;" ::: "memory");
        }
        char* const ex = reinterpret_cast<char*>((reinterpret_cast<uintptr_t>(g_ex) + 0x1fffff) & ~(uintptr_t)0x1fffff);
        char* rbase; uint32_t side;
        {
            uint32_t m0[5][4];
#pragma unroll
            for (int i = 0; i < 5; i++) {
                const unsigned short* m = reinterpret_cast<const unsigned short*>(mem0) + min(i * 128 + t2, DM - 1);
#pragma unroll
                for (int j = 0; j < 4; j++) m0[i][j] = m[2 * j * DM] | (m[(2 * j + 1) * DM] << 16);
            }
            if (w < 2) {
                unsigned* pp = reinterpret_cast<unsigned*>(ex + inbox_off(b) + 16384 + w * 4096 + 2048);
                uint32_t best = ~0u, v = 0;
                if (lane == 0) {
#pragma unroll 1
                    for (int i = 0; i < 6; i++) {
                        const uint32_t c0 = clk();
                        v = atomicAdd(pp + (v >> 31), 0);
                        asm volatile("" :: "r"(v) : "memory");
                        sts32(bar + 80, v);
                        best = min(best, clk() - c0);
                    }
                    sts32(bar + 72 + w * 4, best);
                }
            }
            bar_sync(6, 128);
            const uint32_t xs = PLACE ? lds32(bar + 76) < lds32(bar + 72) : 0, ep = EP;
            side = PLACE ? xs ^ page_par(inbox_off(b)) : 0;
            rbase = ex + inbox_off(b) + xs * 4096;
            const uint32_t inv = (ep * (NT - 1)) & 1;
#pragma unroll
            for (int G = 0; G < 3; G++) stg128(rbase + (G == 2 ? 16384 : G * 2048) + t2 * 16, inv, 0, 0, 0);
            __threadfence();
            bar_sync(6, 128);
            if (t2 == 0) stg_word(g_side + b, (ep + 1) * 2 + xs, true);
            if (t2 >= 96 && t2 < 99 && PFON) prefetch_l2((t2 == 96 ? Wq : t2 == 97 ? Wk : Wv) + b * (6 * 4096), 6 * 8192);
            delay(DLY0 * 6);
#pragma unroll 4
            for (int i = t2; i < 128 * 24; i += 128) {
                const int e = (i >> 3) & 127, G = i >> 10, q = i & 7;
                cp16(sb + O_WO + G * 16384 + e * 128 + ((q ^ (e & 7) ^ ((h >> 1) & 1)) << 4), Wo + (size_t)(h * 128 + e) * DM + G * 192 + r * 64 + q * 8);
            }
            bar_sync(9, 384);
#pragma unroll
            for (int i = 0; i < 5; i++) {
                const int k = min(i * 128 + t2, DM - 1);
                const uint32_t ad = sb + O_MB + (k >> 3) * 256 + (k & 7) * 16;
                sts128(ad, m0[i][0], m0[i][1], m0[i][2], m0[i][3]); sts128(ad + 128, m0[i][0], m0[i][1], m0[i][2], m0[i][3]);
            }
            fence_async_smem();
        }
        auto arm = [&]() {
            const uint32_t ln = l16 >> 4;
            mbar_expect(bar + B_VX + (ln & 3) * 8, ln == 0 ? nv_remote * 2048 : ln == 1 ? nv_remote * 512 + 2560 : ln == 2 ? 6144 : 2048, ln < 4);
        };
        if (w == 3) arm();
        cluster_sync();
        TR1(3);
        const int L = w >> 1, hf = w & 1;
        const uint32_t rd = hf ? roff1 : roff0;
        const uint32_t rzero = gridDim.y + 100;
#define WOAD (sb + O_WO + ((l16 & 0x100) << 2) + ((l16 & 0x70) << 3) + (((w * 32) | ((l16 >> 3) & 16)) ^ (l16 & 0x70)))

        auto fetch_tile = [&](int u) {
            const bool a0 = u < NSEG && (XON || u < 8), a1 = u >= LAG && (XON || u < 8);
            mbar_expect(bar + B_X, ((int)a0 + (int)a1) * 36864, l16 == 0);
            const int kb = (l16 >> 5) * 3 + r, hl = (l16 >> 4) & 1;
            asm volatile("{.reg .pred p; setp.ne.u32 p, %4, 0;\n"
                "@p cp.async.bulk.shared::cluster.global.mbarrier::complete_tx::bytes.multicast::cluster [%0], [%1], 4096, [%2], %3;}"
                :: "r"(sb + O_H + kb * 8192 + hl * 4096), "l"(g_xt + ((u * 2 + hl) * 9 + kb) * 256), "r"(bar + B_X), "h"((uint16_t)7),
                   "r"((uint32_t)(l16 < 96 && (hl ? a1 : a0))) : "memory");
        };
        auto store_o = [&](int u) {
            asm volatile("{.reg .pred p; setp.lt.u32 p, %3, 64;\n"
                "@p cp.async.bulk.global.shared::cta.bulk_group [%0], [%1], %2;\n cp.async.bulk.commit_group;}"
                :: "l"(g_o + (((u & (RING - 1)) * 4 + ((l16 >> 4) & 3)) * 256 + h * 8 + 3 * r) * 32), "r"(sb + O_OS + (l16 & 48) * 96), "r"(nq * 512), "r"(l16) : "memory");
        };
        auto hint_o = [&](int u) {
            asm volatile("cp.async.bulk.wait_group 0;" ::: "memory");
            __syncwarp();
            cnt_hint(g_cnt + (C_O + u * 8 + (h >> 2)) * 8, l16);
            TRG(u, 2);
        };
        bar_arrive(7, 384);
        if (w < 3) { bar_arrive(1 + w, 160); bar_arrive(12 + w, 160); if (w == 0) bar_arrive(8, 64); }
        else {
            mbar_arrive_all3(bar + B_WIN, l16 >> 4);
            cnt_wait(g_cnt + C_X * 8, 64 * (EP + 1)); fence_async_global();
            TRG(0, 0);
            fetch_tile(0);
            TRG(0, 1);
            cnt_wait(g_cnt + (C_X + 1) * 8, 64 * (EP + 1)); fence_async_global();
            TRG(1, 0);
        }
        cp_wait_all();
        bar_sync(6, 128);
        uint32_t poff;
        {
            const int rb = r * 32 + w * 8 + (lane >> 2);
            const uint32_t want = EP + 1;
            uint32_t v;
            for (int n = 0; __any_sync(~0u, ((v = ldg_word(g_side + rb)) >> 1) != want); n++) fault_if(n > POLL_LIMIT, n);
            __threadfence();
            poff = inbox_off(rb) + (v & 1) * 4096 + h * 64 + (lane & 3) * 16;
        }
        side = __shfl_sync(~0u, side, 0);
        const uint32_t roff = __shfl_sync(~0u, (uint32_t)(rbase - ex), 0) + (w == 2 ? 16384 : (w & 1) * 2048);
        uint4 a0[8];
#pragma unroll
        for (int kk = 0; kk < 8; kk++) a0[kk] = ldsm4t(WOAD + kk * 2048);
#pragma unroll 1
        for (int t = 0;; t++) {
            TR_ON(t);
            OPQ();
            mbar_wait(bar + B_EP, t & 1);
            uint4 kx[3][2], vx[4][2];
            const uint32_t lp = LSWAP;
#pragma unroll
            for (int m = 0; m < 3; m++) {
                kx[m][0] = ldsm4(sb + O_KX + m * 2048 + L * 1024 + lp);
                kx[m][1] = ldsm4(sb + O_KX + m * 2048 + L * 1024 + 512 + lp);
            }
            mbar_wait(bar + B_VX, t & 1);
            if (w == 3) {
                mbar_wait(bar + B_XFREE, t & 1);
                bar_sync(8, 64);
                TR(6);
                if (t + 1 < NT) { fetch_tile(t + 1); TRG(t + 1, 1); }
                if (t > 0) store_o(t - 1);
                TR(7);
            }
            TR(0);
            bar_sync(4, 384);
            float s0[4] = {0, 0, 0, 0}, s1[4] = {0, 0, 0, 0}, sm[4] = {0, 0, 0, 0};
            {
                const uint4 q01 = ldsm4(sb + O_QM + L * 256 + l16 + (l16 & 256));
                const uint2 q2 = ldsm2(sb + O_QM + 1024 + L * 256 + l16);
                uint4 km_[3];
#pragma unroll
                for (int m = 0; m < 3; m++) km_[m] = ldsm4(sb + O_KM + m * 512 + (lp ^ (L << 8)));
                bar_arrive(5, 256);
                mma16(s0, kx[0][0].x, kx[0][0].y, kx[0][0].z, kx[0][0].w, q01.x, q01.y);
                mma16(s1, kx[0][1].x, kx[0][1].y, kx[0][1].z, kx[0][1].w, q01.x, q01.y);
                mma16(sm, km_[0].x, km_[0].y, km_[0].z, km_[0].w, q01.x, q01.y);
                mma16(s0, kx[1][0].x, kx[1][0].y, kx[1][0].z, kx[1][0].w, q01.z, q01.w);
                mma16(s1, kx[1][1].x, kx[1][1].y, kx[1][1].z, kx[1][1].w, q01.z, q01.w);
                mma16(sm, km_[1].x, km_[1].y, km_[1].z, km_[1].w, q01.z, q01.w);
                mma16(s0, kx[2][0].x, kx[2][0].y, kx[2][0].z, kx[2][0].w, q2.x, q2.y);
                mma16(s1, kx[2][1].x, kx[2][1].y, kx[2][1].z, kx[2][1].w, q2.x, q2.y);
                mma16(sm, km_[2].x, km_[2].y, km_[2].z, km_[2].w, q2.x, q2.y);
                const uint32_t ad = sb + O_SM + (1 - hf) * 1280 + L * 640 + rd;
                sta128(ad + l16, pk(s0[0], s0[1]), pk(s0[2], s0[3]), pk(s1[0], s1[1]), pk(s1[2], s1[3]), bar + B_SM + rd);
                sta32(ad + 512 + (l16 >> 2), pk(sm[0], sm[1]), bar + B_SM + rd);
            }
            TR(1);
            if (w == 3 && t > 0) hint_o(t - 1);
            if (t + 1 == NT) break;
#pragma unroll
            for (int m = 0; m < 8; m++) vx[m >> 1][m & 1] = lds128(sb + O_VX + (hf * 4 + (m >> 1)) * 2048 + L * 1024 + (m & 1) * 512 + l16);
            const uint32_t tag = (t + EP * (NT - 1) + 1) & 1;
            mbar_wait(bar + B_SM, t & 1);
            TR(2);
            {
                const uint32_t ad = sb + O_SM + L * 640;
                const uint4 u = lds128(ad + l16), v = lds128(ad + 1280 + l16);
                const uint32_t x = lds32(ad + 512 + (l16 >> 2)), y = lds32(ad + 1280 + 512 + (l16 >> 2));
                s0[0] += bf_lo(u.x) + bf_lo(v.x); s0[1] += bf_hi(u.x) + bf_hi(v.x); s0[2] += bf_lo(u.y) + bf_lo(v.y); s0[3] += bf_hi(u.y) + bf_hi(v.y);
                s1[0] += bf_lo(u.z) + bf_lo(v.z); s1[1] += bf_hi(u.z) + bf_hi(v.z); s1[2] += bf_lo(u.w) + bf_lo(v.w); s1[3] += bf_hi(u.w) + bf_hi(v.w);
                sm[0] += bf_lo(x) + bf_lo(y); sm[1] += bf_hi(x) + bf_hi(y);
            }
            uint2 vm[4];
#pragma unroll
            for (int m = 0; m < 4; m++) vm[m] = lds64(sb + O_VM + (hf * 4 + m) * 512 + l16 + L * 8);
            float mx0 = fmaxf(fmaxf(fmaxf(s0[0], s0[2]), fmaxf(s1[0], s1[2])), sm[0]);
            float mx1 = fmaxf(fmaxf(fmaxf(s0[1], s0[3]), fmaxf(s1[1], s1[3])), sm[1]);
#pragma unroll
            for (int o = 4; o < 32; o <<= 1) { mx0 = fmaxf(mx0, __shfl_xor_sync(~0u, mx0, o)); mx1 = fmaxf(mx1, __shfl_xor_sync(~0u, mx1, o)); }
            mx0 *= -SC; mx1 *= -SC;
            s0[0] = ex2(fmaf(s0[0], SC, mx0)); s0[1] = ex2(fmaf(s0[1], SC, mx1));
            s0[2] = ex2(fmaf(s0[2], SC, mx0)); s0[3] = ex2(fmaf(s0[3], SC, mx1));
            const uint32_t pb0 = movm(pk(s0[0], s0[1])), pb1 = movm(pk(s0[2], s0[3]));
            s1[0] = ex2(fmaf(s1[0], SC, mx0)); s1[1] = ex2(fmaf(s1[1], SC, mx1));
            s1[2] = ex2(fmaf(s1[2], SC, mx0)); s1[3] = ex2(fmaf(s1[3], SC, mx1));
            const uint32_t pb2 = movm(pk(s1[0], s1[1])), pb3 = movm(pk(s1[2], s1[3]));
            sm[0] = ex2(fmaf(sm[0], SC, mx0)); sm[1] = ex2(fmaf(sm[1], SC, mx1));
            const uint32_t pm = movm(pk(sm[0], sm[1]));
            float l0 = (s0[0] + s0[2]) + (s1[0] + s1[2]) + sm[0], l1 = (s0[1] + s0[3]) + (s1[1] + s1[3]) + sm[1];
            float o[4][4];
#pragma unroll
            for (int m = 0; m < 4; m++) { o[m][0] = o[m][1] = o[m][2] = o[m][3] = 0.f; mma16(o[m], vx[m][0].x, vx[m][0].y, vx[m][0].z, vx[m][0].w, pb0, pb1); }
            l0 += __shfl_xor_sync(~0u, l0, 4); l1 += __shfl_xor_sync(~0u, l1, 4);
#pragma unroll
            for (int m = 0; m < 4; m++) mma16(o[m], vx[m][1].x, vx[m][1].y, vx[m][1].z, vx[m][1].w, pb2, pb3);
            l0 += __shfl_xor_sync(~0u, l0, 8); l1 += __shfl_xor_sync(~0u, l1, 8);
#pragma unroll
            for (int m = 0; m < 4; m++) mma8(o[m], vm[m].x, vm[m].y, pm);
            l0 += __shfl_xor_sync(~0u, l0, 16); l1 += __shfl_xor_sync(~0u, l1, 16);
            l0 = rcp(l0); l1 = rcp(l1);
#pragma unroll
            for (int m = 0; m < 4; m += 2)
                stsm4t(sb + O_OX + (hf * 4 + m) * 512 + (L ^ ((h >> 2) & 1)) * 256   + ((l16 & 0x100) << 1) + (l16 & 0xf0),
                       pk(o[m][0] * l0, o[m][1] * l1), pk(o[m][2] * l0, o[m][3] * l1), pk(o[m + 1][0] * l0, o[m + 1][1] * l1), pk(o[m + 1][2] * l0, o[m + 1][3] * l1));
            TR(3);
            char* const pdst = ex + poff;
            bar_sync(6, 128);
            {
                uint4 bo[8], a1[8];
                const uint32_t wad = WOAD;
#pragma unroll
                for (int kk = 0; kk < 8; kk++) bo[kk] = ldsm4(sb + O_OX + kk * 512 + l16);
#pragma unroll
                for (int G = 0; G < 3; G++) {
                    float e[4][4];
#pragma unroll
                    for (int q = 0; q < 4; q++) e[q][0] = e[q][1] = e[q][2] = e[q][3] = 0.f;
#pragma unroll
                    for (int kk = 0; kk < 8; kk++) {
                        const uint4 f = G == 0 ? a0[kk] : a1[kk];
                        mma16(e[(kk & 1) * 2], f.x, f.y, f.z, f.w, bo[kk].x, bo[kk].y);
                        mma16(e[(kk & 1) * 2 + 1], f.x, f.y, f.z, f.w, bo[kk].z, bo[kk].w);
                        if (G == 1) a1[kk] = ldsm4t(wad + 32768 + kk * 2048);
                        if (G == 0 && kk == FK) {
                            sched_fence(rzero, 2);
#pragma unroll
                            for (int j = 0; j < 8; j++) a1[j] = ldsm4t(wad + 16384 + j * 2048);
                        }
                    }
                    stg_pkt(pdst + (G == 2 ? 16384 : G * 2048), (pk(e[0][0] + e[2][0], e[0][1] + e[2][1]) & ~1u) | tag, pk(e[0][2] + e[2][2], e[0][3] + e[2][3]),
                            pk(e[1][0] + e[3][0], e[1][1] + e[3][1]), pk(e[1][2] + e[3][2], e[1][3] + e[3][3]));
                    if (G == 0) { TR(9); TRD(t, 0); }
                    if (G < 2) sched_fence(rzero, 3 + G);
                }
            }
            TR(4);
            if (w < 3) {
                bar_arrive(7, 384);
                OPQ();
                const uint32_t tagm = tag;
                uint32_t m0v = 0;
                if (t + 1 <= LAG) {
                    const unsigned short* m = reinterpret_cast<const unsigned short*>(mem0) + ((l16 >> 3) & 6) * DM + 192 * w + 16 * (b >> 3) + (b & 7) + ((l16 >> 4) & 8);
                    m0v = m[0] | (m[DM] << 16);
                }
                const char* const rsrc = ex + roff + l16;
                uint4 v[4];
                delay(DLY1);
#pragma unroll
                for (int i = 0; i < 4; i++) v[i] = ldg_pkt(rsrc + i * 512);
                for (int n = 0; __any_sync(~0u, lop_bad(lop_bad(0, v[0].x, v[1].x, tagm), v[2].x, v[3].x, tagm) & 1); n++) {
#pragma unroll
                    for (int i = 0; i < 4; i++) v[i] = ldg_pkt(rsrc + i * 512);
                    fault_if(n > POLL_LIMIT, n);
                }
                TR(5); TRD(t, 1);
                float s[8];
                s[4] = (bf_lo(v[0].z) + bf_lo(v[1].z)) + (bf_lo(v[2].z) + bf_lo(v[3].z)); s[5] = (bf_hi(v[0].z) + bf_hi(v[1].z)) + (bf_hi(v[2].z) + bf_hi(v[3].z));
                s[6] = (bf_lo(v[0].w) + bf_lo(v[1].w)) + (bf_lo(v[2].w) + bf_lo(v[3].w)); s[7] = (bf_hi(v[0].w) + bf_hi(v[1].w)) + (bf_hi(v[2].w) + bf_hi(v[3].w));
                s[2] = (bf_lo(v[0].y) + bf_lo(v[1].y)) + (bf_lo(v[2].y) + bf_lo(v[3].y)); s[3] = (bf_hi(v[0].y) + bf_hi(v[1].y)) + (bf_hi(v[2].y) + bf_hi(v[3].y));
                s[0] = (bf_lo(v[0].x) + bf_lo(v[1].x)) + (bf_lo(v[2].x) + bf_lo(v[3].x)); s[1] = (bf_hi(v[0].x) + bf_hi(v[1].x)) + (bf_hi(v[2].x) + bf_hi(v[3].x));
#pragma unroll
                for (int j = 0; j < 4; j++) s[j] += __shfl_xor_sync(~0u, s[j + 4], 16);
#pragma unroll
                for (int j = 0; j < 2; j++) s[j] += __shfl_xor_sync(~0u, s[j + 2], 8);
#pragma unroll
                for (int j = 0; j < 2; j++) s[j] += __shfl_xor_sync(~0u, s[j], 4);
                char* const mem_w = ex + mem_off(w, 0);
                uint32_t res = t + 1 <= LAG && l16 >= 256 ? m0v : pk(s[0], s[1]);
                if ((l16 & 48) == 0) res = (res & ~1u) | tag;
                stg_word(mem_w + (mem_off(0, b >> 3) - mem_off(0, 0)) + (b & 7) * 16 + (((l16 & 64) << 6) + ((l16 & 128) << 1) + ((l16 & 256) >> 1) + ((l16 >> 2) & 12)), res, true);
                TR(6); TRD(t, 2);
                delay(DLY2);
                const char* src = mem_w + (side ^ page_par(0x180000)) * 4096 + l16;
                const uint32_t gdst = sb + O_MB + w * 6144 + l16;
                uint4 x[12];
#pragma unroll
                for (int i = 0; i < 12; i++) x[i] = ldg_pkt(src + (mem_off(0, i) - mem_off(0, 0)));
                for (int n = 0;; n++) {
                    uint32_t bad = 0;
#pragma unroll
                    for (int i = 0; i < 12; i += 2) bad = lop_bad(bad, x[i].x, x[i + 1].x, tagm);
                    if (!__any_sync(~0u, bad & 1)) break;
#pragma unroll
                    for (int i = 0; i < 12; i++) ldg_pkt_retry(x[i], src + (mem_off(0, i) - mem_off(0, 0)), tagm);
                    fault_if(n > POLL_LIMIT, n);
                }
#pragma unroll
                for (int i = 0; i < 12; i++) sts128(gdst + i * 512, x[i].x, x[i].y, x[i].z, x[i].w);
                TR(7); TRD(t, 3);
                fence_async_smem();
                bar_arrive(12 + w, 160);
                bar_arrive(1 + w, 160);
                if (w == XST) bar_arrive(8, 64);
                TR(8);
            } else {
                bar_sync(7, 384);
                fence_async_smem();
                arm();
                __syncwarp();
                mbar_arrive_all3(bar + B_WIN, l16 >> 4);
                if (t + 2 < NT) { cnt_wait(g_cnt + (C_X + t + 2) * 8, 64 * (EP + 1)); fence_async_global(); TRG(t + 2, 0); }
                TR(5);
            }
        }
        if (w == 3) { bar_sync(7, 160); fence_async_smem(); store_o(NT - 1); hint_o(NT - 1); }
        cluster_sync();
    }
    TR_DUMP(b);
}

#define VG 12
namespace ka {
constexpr int O_WA = 196608;
constexpr int A_SBO = 9232;
constexpr int O_RING = 194560;
constexpr int O_BAR = 230400;
constexpr int SMEM = O_BAR + 128 + 1024;
constexpr float SC = 0.23570226039551584f * 1.4426950408889634f;
}

template <int NP>
DEVI void row_task(const uint4* res, const uint4* part, uint4* xout, char* img, int pos, int lane, uint32_t tag) {
    const bool on = lane < 24;
    const int ln = on ? lane : 0;
    uint4 rv[3], pv[NP > 0 ? NP * 3 : 1];
#pragma unroll
    for (int i = 0; i < 3; i++) rv[i] = ldg128(res + i * 24 + ln);
#pragma unroll
    for (int i = 0; i < NP * 3; i++) pv[i] = ldg_pkt(part + i * 24 + ln);
    if (NP > 0) validate<NP * 3>(pv, part + ln, 384, tag);
#pragma unroll
    for (int q = 0; q < NP * 3 / 2; q++) {
        const uint4 y = pv[q + NP * 3 / 2];
        pv[q] = make_uint4(add2(pv[q].x, y.x), add2(pv[q].y, y.y), add2(pv[q].z, y.z), add2(pv[q].w, y.w));
    }
    float x[24];
#pragma unroll
    for (int i = 0; i < 3; i++) {
        x[8 * i] = bf_lo(rv[i].x); x[8 * i + 1] = bf_hi(rv[i].x); x[8 * i + 2] = bf_lo(rv[i].y); x[8 * i + 3] = bf_hi(rv[i].y);
        x[8 * i + 4] = bf_lo(rv[i].z); x[8 * i + 5] = bf_hi(rv[i].z); x[8 * i + 6] = bf_lo(rv[i].w); x[8 * i + 7] = bf_hi(rv[i].w);
    }
    if (NP > 0) {
#pragma unroll
        for (int q = 0; q < NP * 3 / 2; q++) {
            const int i = q % 3;
            x[8 * i] += bf_lo(pv[q].x); x[8 * i + 1] += bf_hi(pv[q].x); x[8 * i + 2] += bf_lo(pv[q].y); x[8 * i + 3] += bf_hi(pv[q].y);
            x[8 * i + 4] += bf_lo(pv[q].z); x[8 * i + 5] += bf_hi(pv[q].z); x[8 * i + 6] += bf_lo(pv[q].w); x[8 * i + 7] += bf_hi(pv[q].w);
        }
#pragma unroll
        for (int i = 0; i < 3; i++) {
            uint32_t w[4];
#pragma unroll
            for (int j = 0; j < 4; j++) { w[j] = pk(x[8 * i + 2 * j], x[8 * i + 2 * j + 1]); x[8 * i + 2 * j] = bf_lo(w[j]); x[8 * i + 2 * j + 1] = bf_hi(w[j]); }
            stg128p(xout + i * 24 + ln, w[0], w[1], w[2], w[3], on);
        }
    }
    if (img) {
        float s = 0.f;
#pragma unroll
        for (int j = 0; j < 24; j++) s += x[j];
        if (!on) s = 0.f;
#pragma unroll
        for (int o = 1; o < 32; o <<= 1) s += __shfl_xor_sync(~0u, s, o);
        const float mean = s * (1.f / DM);
        float v = 0.f;
#pragma unroll
        for (int j = 0; j < 24; j++) { x[j] -= mean; v = fmaf(x[j], x[j], v); }
        if (!on) v = 0.f;
#pragma unroll
        for (int o = 1; o < 32; o <<= 1) v += __shfl_xor_sync(~0u, v, o);
        const float rs = rsqrtf(v * (1.f / DM) + 1e-5f);
        char* dst = img + (ln >> 3) * 4096 + pos * 128 + (((ln ^ pos) & 7) << 4);
#pragma unroll
        for (int i = 0; i < 3; i++)
            stg128p(dst + i * 12288, pk(x[8 * i] * rs, x[8 * i + 1] * rs), pk(x[8 * i + 2] * rs, x[8 * i + 3] * rs),
                    pk(x[8 * i + 4] * rs, x[8 * i + 5] * rs), pk(x[8 * i + 6] * rs, x[8 * i + 7] * rs), on);
    }
}

__global__ void __launch_bounds__(384, 1)
k_aux(const __nv_bfloat16* __restrict__ x0, const __nv_bfloat16* __restrict__ wqkv, const __nv_bfloat16* __restrict__ wo,
      const __nv_bfloat16* __restrict__ Wo, __nv_bfloat16* __restrict__ out) {
    using namespace ka;
    extern __shared__ unsigned char smem_raw[];
    const uint32_t sb = (smem_u32(smem_raw) + 1023) & ~1023u;
    const int tid = threadIdx.x, lane = tid & 31, warp = __shfl_sync(~0u, tid >> 5, 0), g = lane >> 2, c = lane & 3;
    const int b = blockIdx.x;
    const uint32_t bar = sb + O_BAR;
    const uint32_t ep = __shfl_sync(~0u, ldg32(&g_epoch), 0);

    TRG(79, 0);
    if (warp >= 8) {
        asm volatile("setmaxnreg.dec.sync.aligned.u32 128;");
        const int rw = b * 4 + warp - 8;
        const uint4* xin = reinterpret_cast<const uint4*>(x0);
#pragma unroll 1
        for (int row = rw; row < 2048; row += 16) {
            row_task<0>(xin + row * 72, nullptr, nullptr, reinterpret_cast<char*>(g_xa + (row >> 5) * 4608), (row & 1) * 16 + ((row & 31) >> 1), lane, 0);
            cnt_add(g_cnt + (C_N0 + (row >> 5)) * 8, lane);
            if (rw < 128) break;
        }
        const int R = rw & 63, f = R >> 5, i = R & 31;
        if (rw < 64) {
#pragma unroll 1
            for (int u = 0; u < NT; u++) {
                const int seg = u - f * LAG, row = seg * 32 + i;
                if (seg >= 0 && seg < NSEG) {
                    cnt_wait(g_cnt + (C_WB + u * 4 + (R >> 4)) * 8, 24 * (ep + 1));
                    TRG(u, 0);
                    row_task<8>(g_x + (f * 4096 + row) * 72, g_pb + ((u & (RING - 1)) * 64 + R) * 576,
                                f ? reinterpret_cast<uint4*>(out) + row * 72 : g_x + (2048 + row) * 72,
                                f ? nullptr : reinterpret_cast<char*>(g_xa + (u + LAG) * 4608 + 2304), (i & 1) * 16 + (i >> 1), lane, ring_tag(u, ep));
                    TRG(u, 1);
                }
                cnt_add(g_cnt + (C_RB + u) * 8, lane);
                TRG(u, 2);
            }
            if (rw == 63) {
                asm volatile("griddepcontrol.wait;" ::: "memory");
                if (lane == 0) g_epoch = ep + 1;
            }
        } else if (rw < 128) {
#pragma unroll 1
            for (int u = 0; u < NT; u++) {
                const int seg = u - f * LAG, row = seg * 32 + i;
                if (seg >= 0 && seg < NSEG) {
                    cnt_wait(g_cnt + (C_WA + u * 4 + f * 2 + (i & 1)) * 8, 24 * (ep + 1));
                    TRG(u, 0);
                    row_task<4>((f ? g_x + 2048 * 72 : xin) + row * 72, g_pa + ((u & (RING - 1)) * 64 + R) * 288,
                                g_x + (f * 4096 + row) * 72, reinterpret_cast<char*>(g_xt + u * 4608 + f * 2304), i, lane, ring_tag(u, ep));
                    TRG(u, 1);
                }
                cnt_add(g_cnt + (C_X + u) * 8, lane);
                TRG(u, 2);
            }
        }
        return;
    }
    if (b == 35) return;

    if (b < 24) {
        if (warp >= 4) {
            const int kq = b / 6, nq = b % 6;
            uint4 v[17];
#pragma unroll
            for (int q = 0; q < 17; q++) {
                const int it = q * 4 + warp - 4, kr = (it / 3) * 8 + g, s = kq * 11 + (kr >> 4), a = s >> 2, j = s & 3, e = kr & 15;
                const int head = 3 * a + (j < 3 ? j : e >> 1), row = head * 18 + (j < 3 ? e : 16 + (e & 1));
                v[q] = make_uint4(0, 0, 0, 0);
                if (it < 66 && head < 32 && (j < 3 || e < 6)) v[q] = *reinterpret_cast<const uint4*>(wo + row * DM + nq * 96 + (it % 3) * 32 + c * 8);
            }
#pragma unroll
            for (int q = 0; q < 17; q++) {
                const int it = q * 4 + warp - 4;
                const uint32_t ad = sb + O_WA + (it % 3) * 4 * 2816 + (it / 3) * 128 + lane * 4;
                if (it < 66) { sts32(ad, v[q].x); sts32(ad + 2816, v[q].y); sts32(ad + 2 * 2816, v[q].z); sts32(ad + 3 * 2816, v[q].w); }
            }
        } else {
            const int kg = b / 3, ng = b % 3;
            delay(DLY0 * 7);
#pragma unroll 1
            for (int bt = 0; bt < 4; bt++) {
                uint4 v[24];
#pragma unroll
                for (int q = 0; q < 24; q++)
                    v[q] = *reinterpret_cast<const uint4*>(Wo + (size_t)(kg * 512 + (bt * 4 + q / 6) * 32 + warp * 8 + g) * DM + ng * 192 + (q % 6) * 32 + c * 8);
#pragma unroll
                for (int q = 0; q < 24; q++) {
                    const uint32_t ad = sb + (q % 6) * 4 * 8192 + ((bt * 4 + q / 6) * 4 + warp) * 128 + lane * 4;
                    sts32(ad, v[q].x); sts32(ad + 8192, v[q].y); sts32(ad + 2 * 8192, v[q].z); sts32(ad + 3 * 8192, v[q].w);
                }
            }
        }
        fence_async_smem();
        bar_sync(2 + (warp >> 2), 128);
    } else {
        const int a = b - 24, nw = a == 10 ? 18 : 27, ch = lane & 7, off = (a * 108) & 15;
        int d0[4], dw[4];
#pragma unroll
        for (int j = 0; j < 4; j++) {
            const int w = ch * 4 + j - (off >> 2), hh = w / 9, jj = w % 9;
            d0[j] = w < 0 || w >= nw ? -1 : jj < 8 ? (hh * 2 + (jj >> 2)) * A_SBO + (jj & 3) * 4 : 18 * A_SBO + hh * 4;
            dw[j] = jj < 8 ? 6 * A_SBO : A_SBO;
        }
        const bool any = ch * 4 - (off >> 2) < nw;
        const char* src = reinterpret_cast<const char*>(wqkv) + (warp * 4 + (lane >> 3)) * 3456 + a * 108 - off + (any ? ch * 16 : 0);
#pragma unroll 1
        for (int wh = 0; wh < 3; wh++) {
            uint4 v[18];
#pragma unroll
            for (int q = 0; q < 18; q++) v[q] = ldg128(src + q * 32 * 3456 + wh * 1152);
            sched_fence(gridDim.y, 2);
            TRG(78, wh);
            if (wh == 0) {
                for (int i = tid; i < 3 * A_SBO / 16; i += 256) {
                    sts128(sb + 18 * A_SBO + i * 16, 0, 0, 0, 0);
                    if (a == 10 && i < 2 * A_SBO / 16) { sts128(sb + 4 * A_SBO + i * 16, 0, 0, 0, 0); sts128(sb + 10 * A_SBO + i * 16, 0, 0, 0, 0); sts128(sb + 16 * A_SBO + i * 16, 0, 0, 0, 0); }
                }
                for (int i = tid; i < 2048; i += 256) sts128(sb + O_RING + i * 16, 0, 0, 0, 0);
                if (tid == 0) for (int i = 0; i < 4; i++) { mbar_init(bar + i * 8, 1); mbar_init(bar + 32 + i * 8, 4); }
                bar_sync(1, 256);
            }
            const uint32_t ad = sb + (warp * 4 + (lane >> 3)) * 16;
#pragma unroll
            for (int q = 0; q < 18; q++) {
                sts32p(ad + d0[0] + wh * dw[0] + q * 512, v[q].x, d0[0] >= 0);
                sts32p(ad + d0[1] + wh * dw[1] + q * 512, v[q].y, d0[1] >= 0);
                sts32p(ad + d0[2] + wh * dw[2] + q * 512, v[q].z, d0[2] >= 0);
                sts32p(ad + d0[3] + wh * dw[3] + q * 512, v[q].w, d0[3] >= 0);
            }
        }
        fence_async_smem();
        bar_sync(1, 256);
    }
    TRG(79, 1);
    const int wq = warp & 3;

    if (warp < 4) {
        asm volatile("setmaxnreg.inc.sync.aligned.u32 256;");
        if (b < 24) {
            const int kg = b / 3, ng = b % 3;
            const uint32_t blo = ((sb >> 4) & 0x3fff) | (8u << 16);
            uint4 a[32];
            bool pre = false;
#pragma unroll 1
            for (int u = 0; u < NT; u++) {
                const uint32_t tag = ring_tag(u, ep);
                const uint4* src = g_o + (((u & (RING - 1)) * 4 + wq) * 256 + kg * 32) * 32 + lane;
                if (!pre) {
                    cnt_wait(g_cnt + (C_O + u * 8 + kg) * 8, 12 * (ep + 1));
#pragma unroll
                    for (int i = 0; i < VG; i++) a[i] = ldg_pkt(src + i * 32);
                }
                TRG(u, 0);
                float d[96];
                validate<VG>(a, src, 512, tag);
#pragma unroll
                for (int i = VG; i < 32; i++) a[i] = ldg_pkt(src + i * 32);
                wg_fence();
#pragma unroll
                for (int i = 0; i < 32; i++) {
                    if (i == VG) { validate<32 - VG>(a + VG, src + VG * 32, 512, tag); wg_fence(); }
                    wgmma_rs192t(d, a[i].x, a[i].y, a[i].z, a[i].w, mkdesc(blo + i * 16, 512), i > 0);
                    if (i == 23 || i == 31) wg_commit();
                }
                wg_wait<1>();
                pre = u + 1 < NT && __all_sync(~0u, ldg_word(g_cnt + (C_O + (u + 1) * 8 + kg) * 8) >= 12 * (ep + 1));
                if (pre) {
                    const uint4* nx = g_o + ((((u + 1) & (RING - 1)) * 4 + wq) * 256 + kg * 32) * 32 + lane;
#pragma unroll
                    for (int i = 0; i < VG; i++) a[i] = ldg_pkt(nx + i * 32);
                }
                wg_wait<0>();
                TRG(u, 1);
                uint4* dst = g_pb + (((u & (RING - 1)) * 64 + wq * 16 + g) * 8 + kg) * 72 + ng * 24 + c;
#pragma unroll
                for (int m = 0; m < 6; m++) {
                    stg128(dst + 4 * m, (pk(d[16 * m], d[16 * m + 1]) & ~1u) | tag, pk(d[16 * m + 4], d[16 * m + 5]), pk(d[16 * m + 8], d[16 * m + 9]), pk(d[16 * m + 12], d[16 * m + 13]));
                    stg128(dst + 4 * m + 8 * 576, (pk(d[16 * m + 2], d[16 * m + 3]) & ~1u) | tag, pk(d[16 * m + 6], d[16 * m + 7]), pk(d[16 * m + 10], d[16 * m + 11]), pk(d[16 * m + 14], d[16 * m + 15]));
                }
                cnt_hint(g_cnt + (C_WB + u * 4 + wq) * 8, lane);
                TRG(u, 3);
            }
        } else {
            const int a = b - 24, f = wq >> 1;
            const uint32_t blo = ((sb >> 4) & 0x3fff) | (8u << 16), alo = (((sb + O_RING) >> 4) & 0x3fff) | (1u << 16);
            const bool m0 = 2 * c <= g, m1 = 2 * c + 1 <= g;
            const uint32_t M = (m0 ? 0xffffu : 0u) | (m1 ? 0xffff0000u : 0u);
            uint32_t kh[7], vh[7];
#pragma unroll
            for (int i = 0; i < 7; i++) kh[i] = vh[i] = 0;
            int it = 0;
#pragma unroll 1
            for (int u = 0; u < NT; u++) {
                float d[84];
#pragma unroll 1
                for (int kb = 0; kb < 9; kb++, it++) {
                    mbar_wait(bar + (it & 3) * 8, (it >> 2) & 1);
                    if (kb == 0) TRG(u, 0);
                    wg_fence();
#pragma unroll
                    for (int q = 0; q < 4; q++)
                        wgmma_ss168t(d, mkdesc(alo + (it & 3) * 512 + q * 2, km::DESC_HI), mkdesc(blo + (kb * 4 + q) * 16, A_SBO >> 4), kb + q > 0);
                    wg_commit();
                    wg_wait<1>();
                    mbar_arrive(bar + 32 + ((it - 1) & 3) * 8, lane == 0 && kb > 0);
                }
                wg_wait<0>();
                mbar_arrive(bar + 32 + ((it - 1) & 3) * 8, lane == 0);
                TRG(u, 1);
                const bool first = u == f * LAG;
                const uint32_t tag = ring_tag(u, ep);
                const uint32_t qt0 = pk(d[72], d[73]), qt1 = pk(d[74], d[75]), kt0 = pk(d[76], d[77]), kt1 = pk(d[78], d[79]);
                const uint32_t vt0 = movm(pk(d[80], d[81])), vt1 = movm(pk(d[82], d[83]));
                float ot[4] = {0, 0, 0, 0};
                uint4* dst = g_oa + (((u & (RING - 1)) * 4 + wq) * 44 + a * 4) * 32 + lane;
#pragma unroll
                for (int h = 0; h < 3; h++) {
                    const float* q = d + 8 * h; const float* k = d + 24 + 8 * h; const float* v = d + 48 + 8 * h;
                    const uint32_t q0 = pk(q[0], q[1]), q1 = pk(q[2], q[3]), q2 = pk(q[4], q[5]), q3 = pk(q[6], q[7]);
                    const uint32_t k0 = pk(k[0], k[1]), k1 = pk(k[4], k[5]), k2 = pk(k[2], k[3]), k3 = pk(k[6], k[7]);
                    const uint32_t v0 = movm(pk(v[0], v[1])), v1 = movm(pk(v[2], v[3])), v2 = movm(pk(v[4], v[5])), v3 = movm(pk(v[6], v[7]));
                    const uint32_t t0 = c == h ? qt0 : 0, t1 = c == h ? qt1 : 0;
                    float sp[4] = {0, 0, 0, 0}, sl[4] = {0, 0, 0, 0}, sh[4] = {0, 0, 0, 0};
                    mma16(sp, q0, q1, q2, q3, kh[2 * h], kh[2 * h + 1]); mma16(sl, q0, q1, q2, q3, k0, k1); mma16(sh, q0, q1, q2, q3, k2, k3);
                    mma8(sp, t0, t1, kh[6]); mma8(sl, t0, t1, kt0); mma8(sh, t0, t1, kt1);
                    float x0_ = m0 ? sl[0] : first ? -INFINITY : sp[0], x1_ = m1 ? sl[1] : first ? -INFINITY : sp[1];
                    float y0_ = m0 ? sh[2] : sl[2], y1_ = m1 ? sh[3] : sl[3];
                    float mx = fmaxf(x0_, x1_), my = fmaxf(y0_, y1_);
#pragma unroll
                    for (int o = 1; o < 4; o <<= 1) { mx = fmaxf(mx, __shfl_xor_sync(~0u, mx, o)); my = fmaxf(my, __shfl_xor_sync(~0u, my, o)); }
                    mx *= -SC; my *= -SC;
                    x0_ = ex2(fmaf(x0_, SC, mx)); x1_ = ex2(fmaf(x1_, SC, mx)); y0_ = ex2(fmaf(y0_, SC, my)); y1_ = ex2(fmaf(y1_, SC, my));
                    float lx = x0_ + x1_, ly = y0_ + y1_;
#pragma unroll
                    for (int o = 1; o < 4; o <<= 1) { lx += __shfl_xor_sync(~0u, lx, o); ly += __shfl_xor_sync(~0u, ly, o); }
                    lx = rcp(lx); ly = rcp(ly);
                    const uint32_t px = pk(x0_ * lx, x1_ * lx), py = pk(y0_ * ly, y1_ * ly);
                    const uint32_t hm = (g >> 1) == h ? ~0u : 0u;
                    float o0[4] = {0, 0, 0, 0}, o1[4] = {0, 0, 0, 0};
                    mma16(o0, px & M, py & ~M, 0, py & M, v0, v1); mma16(o1, px & M, py & ~M, 0, py & M, v2, v3);
                    mma16(ot, px & M, py & ~M, 0, py & M, vt0 & hm, vt1 & hm);
                    mma8(o0, px & ~M, 0, vh[2 * h]); mma8(o1, px & ~M, 0, vh[2 * h + 1]); mma8(ot, px & ~M, 0, vh[6] & hm);
                    stg128(dst + h * 32, (pk(o0[0], o0[1]) & ~1u) | tag, pk(o0[2], o0[3]), pk(o1[0], o1[1]), pk(o1[2], o1[3]));
                    kh[2 * h] = k2; kh[2 * h + 1] = k3; vh[2 * h] = v1; vh[2 * h + 1] = v3;
                }
                kh[6] = kt1; vh[6] = vt1;
                stg128(dst + 96, (pk(ot[0], ot[1]) & ~1u) | tag, pk(ot[2], ot[3]), 0, 0);
                cnt_hint(g_cnt + (C_A + u * 4 + wq) * 8, lane);
                TRG(u, 2);
            }
        }
    } else {
        asm volatile("setmaxnreg.dec.sync.aligned.u32 120;");
        if (b < 24) {
            const int kq = b / 6, nq = b % 6;
            const uint32_t blo = (((sb + O_WA) >> 4) & 0x3fff) | (8u << 16);
#pragma unroll 1
            for (int u = 0; u < NT; u++) {
                cnt_wait(g_cnt + (C_A + u * 4 + wq) * 8, 11 * (ep + 1));
                const uint32_t tag = ring_tag(u, ep);
                TRG(u, 0);
                const uint4* src = g_oa + (((u & (RING - 1)) * 4 + wq) * 44 + kq * 11) * 32 + lane;
                uint4 a[11];
                float d[48];
#pragma unroll
                for (int i = 0; i < 11; i++) a[i] = ldg_pkt(src + i * 32);
                validate<11>(a, src, 512, tag);
                wg_fence();
#pragma unroll
                for (int i = 0; i < 11; i++) wgmma_rs96t(d, a[i].x, a[i].y, a[i].z, a[i].w, mkdesc(blo + i * 16, 176), i > 0);
                wg_commit();
                wg_wait<0>();
                TRG(u, 1);
                uint4* dst = g_pa + (((u & (RING - 1)) * 64 + (wq >> 1) * 32 + 2 * g + (wq & 1)) * 4 + kq) * 72 + nq * 12 + c;
#pragma unroll
                for (int m = 0; m < 3; m++) {
                    stg128(dst + 4 * m, (pk(d[16 * m], d[16 * m + 1]) & ~1u) | tag, pk(d[16 * m + 4], d[16 * m + 5]), pk(d[16 * m + 8], d[16 * m + 9]), pk(d[16 * m + 12], d[16 * m + 13]));
                    stg128(dst + 4 * m + 16 * 288, (pk(d[16 * m + 2], d[16 * m + 3]) & ~1u) | tag, pk(d[16 * m + 6], d[16 * m + 7]), pk(d[16 * m + 10], d[16 * m + 11]), pk(d[16 * m + 14], d[16 * m + 15]));
                }
                cnt_hint(g_cnt + (C_WA + u * 4 + wq) * 8, lane);
                TRG(u, 3);
            }
        } else if (warp == 4) {
            int it = 0;
#pragma unroll 1
            for (int u = 0; u < NT; u++) {
                if (u < NSEG) cnt_wait(g_cnt + (C_N0 + u) * 8, 32 * (ep + 1));
                if (u >= LAG) cnt_wait(g_cnt + (C_RB + u - LAG) * 8, 64 * (ep + 1));
                TRG(u, 0);
                asm volatile("fence.proxy.async.global;" ::: "memory");
                const bool on = lane == 0 ? u < NSEG : lane == 1 && u >= LAG;
#pragma unroll 1
                for (int kb = 0; kb < 9; kb++, it++) {
                    if (it >= 4) mbar_wait(bar + 32 + (it & 3) * 8, ((it >> 2) - 1) & 1);
                    mbar_expect(bar + (it & 3) * 8, u < NSEG && u >= LAG ? 8192 : 4096, lane == 0);
                    asm volatile("{.reg .pred p; setp.ne.u32 p, %3, 0; @p cp.async.bulk.shared::cluster.global.mbarrier::complete_tx::bytes [%0], [%1], 4096, [%2];}"
                        :: "r"(sb + O_RING + (it & 3) * 8192 + (lane & 1) * 4096), "l"(g_xa + u * 4608 + (lane & 1) * 2304 + kb * 256), "r"(bar + (it & 3) * 8), "r"((uint32_t)on) : "memory");
                }
            }
        }
    }
}

extern "C" void kernel_launch(void* const* d_in, const int* in_sizes, int n_in, void* d_out, int out_size) {
    const __nv_bfloat16* x = (const __nv_bfloat16*)d_in[0];
    const __nv_bfloat16* wqkv = (const __nv_bfloat16*)d_in[1];
    const __nv_bfloat16* wo = (const __nv_bfloat16*)d_in[2];
    const __nv_bfloat16* mem0 = (const __nv_bfloat16*)d_in[4];
    const __nv_bfloat16* Wq = (const __nv_bfloat16*)d_in[5];
    const __nv_bfloat16* Wk = (const __nv_bfloat16*)d_in[6];
    const __nv_bfloat16* Wv = (const __nv_bfloat16*)d_in[7];
    const __nv_bfloat16* Wo = (const __nv_bfloat16*)d_in[8];
    cudaFuncSetAttribute(k_main, cudaFuncAttributeMaxDynamicSharedMemorySize, km::SMEM);
    cudaFuncSetAttribute(k_aux, cudaFuncAttributeMaxDynamicSharedMemorySize, ka::SMEM);
    cudaStream_t s = cudaStreamPerThread;
    k_main<<<96, 384, km::SMEM, s>>>(x, wqkv, wo, mem0, Wq, Wk, Wv, Wo);
    cudaLaunchConfig_t cfg = {};
    cudaLaunchAttribute at[1];
    at[0].id = cudaLaunchAttributeProgrammaticStreamSerialization;
    at[0].val.programmaticStreamSerializationAllowed = 1;
    cfg.stream = s; cfg.attrs = at; cfg.numAttrs = 1;
    cfg.gridDim = dim3(36); cfg.blockDim = dim3(384); cfg.dynamicSmemBytes = ka::SMEM;
    cudaLaunchKernelEx(&cfg, k_aux, x, wqkv, wo, Wo, (__nv_bfloat16*)d_out);
}
```

```cpp
#include <cuda_runtime.h>
#include <cuda_bf16.h>
#include <stdint.h>

#define LAG 7
constexpr int NSEG = 64;
constexpr int NT = NSEG + LAG;
#define AHEAD 1
constexpr int LAGA = LAG + AHEAD;
constexpr int NTA = NSEG + LAGA;
#define RING_ 8
constexpr int RING = RING_;
constexpr int DM = 576;

__device__ __align__(1024) uint4 g_xt[NT * 2 * 9 * 256];
__device__ __align__(1024) uint4 g_o[RING * 4 * 256 * 32];
__device__ __align__(1024) uint4 g_ex[2 * 131072];
__device__ unsigned g_side[96];
__device__ __align__(1024) uint4 g_pb[RING * 64 * 8 * 72];
__device__ __align__(1024) uint4 g_pa[RING * 64 * 4 * 72];
__device__ __align__(1024) uint4 g_oa[RING * 4 * 44 * 32];
__device__ __align__(1024) uint4 g_xa[NTA * 2 * 9 * 256];
__device__ __align__(1024) uint4 g_wa[11 * 9 * 21 * 64];
__device__ __align__(1024) uint4 g_x[3 * 2048 * 72];

constexpr int C_X = 0;
constexpr int C_O = C_X + NT;
constexpr int C_WB = C_O + NT * 8;
constexpr int C_RB = C_WB + NT * 4;
constexpr int C_A = C_RB + 2 * NSEG;
constexpr int C_WA = C_A + NTA * 4;
constexpr int C_N0 = C_WA + NTA * 4;
constexpr int C_W = C_N0 + NSEG;
constexpr int C_DONE = C_W + 1;
constexpr int C_TOTAL = C_DONE + 1;
__device__ __align__(1024) unsigned g_cnt[C_TOTAL * 8];
__device__ unsigned g_epoch;

#define TR(i)
#define TR1(i)
#define TR_ON(t)
#define TR_INIT(base)
#define TR_DUMP(slot)
#define TRG(t, i)
constexpr int TR_BYTES = 0;

#define DEVI __device__ __forceinline__
DEVI uint32_t smem_u32(const void* p) { return (uint32_t)__cvta_generic_to_shared(p); }
DEVI uint32_t pk(float lo, float hi) { uint32_t r; asm("cvt.rn.bf16x2.f32 %0, %1, %2;" : "=r"(r) : "f"(hi), "f"(lo)); return r; }
DEVI float bf_lo(uint32_t u) { return __uint_as_float(u << 16); }
DEVI float bf_hi(uint32_t u) { return __uint_as_float(u & 0xffff0000u); }
DEVI uint32_t add2(uint32_t a, uint32_t b) { uint32_t d; asm("add.rn.bf16x2 %0, %1, %2;" : "=r"(d) : "r"(a), "r"(b)); return d; }
DEVI uint32_t movm(uint32_t a) { uint32_t d; asm volatile("movmatrix.sync.aligned.m8n8.trans.b16 %0, %1;" : "=r"(d) : "r"(a)); return d; }
DEVI float ex2(float x) { float y; asm("ex2.approx.ftz.f32 %0, %1;" : "=f"(y) : "f"(x)); return y; }
DEVI float rcp(float x) { float y; asm("rcp.approx.ftz.f32 %0, %1;" : "=f"(y) : "f"(x)); return y; }
DEVI void mma16(float (&d)[4], uint32_t a0, uint32_t a1, uint32_t a2, uint32_t a3, uint32_t b0, uint32_t b1) {
    asm volatile("mma.sync.aligned.m16n8k16.row.col.f32.bf16.bf16.f32 {%0,%1,%2,%3}, {%4,%5,%6,%7}, {%8,%9}, {%0,%1,%2,%3};"
        : "+f"(d[0]), "+f"(d[1]), "+f"(d[2]), "+f"(d[3]) : "r"(a0), "r"(a1), "r"(a2), "r"(a3), "r"(b0), "r"(b1));
}
DEVI void mma8(float (&d)[4], uint32_t a0, uint32_t a1, uint32_t b0) {
    asm volatile("mma.sync.aligned.m16n8k8.row.col.f32.bf16.bf16.f32 {%0,%1,%2,%3}, {%4,%5}, {%6}, {%0,%1,%2,%3};"
        : "+f"(d[0]), "+f"(d[1]), "+f"(d[2]), "+f"(d[3]) : "r"(a0), "r"(a1), "r"(b0));
}
DEVI uint4 lds128(uint32_t a) { uint4 v; asm volatile("ld.shared.v4.u32 {%0,%1,%2,%3}, [%4];" : "=r"(v.x), "=r"(v.y), "=r"(v.z), "=r"(v.w) : "r"(a) : "memory"); return v; }
DEVI uint2 lds64(uint32_t a) { uint2 v; asm volatile("ld.shared.v2.u32 {%0,%1}, [%2];" : "=r"(v.x), "=r"(v.y) : "r"(a) : "memory"); return v; }
DEVI uint32_t lds32(uint32_t a) { uint32_t v; asm volatile("ld.shared.u32 %0, [%1];" : "=r"(v) : "r"(a) : "memory"); return v; }
DEVI uint32_t lds32v(uint32_t a) { uint32_t v; asm volatile("ld.volatile.shared.u32 %0, [%1];" : "=r"(v) : "r"(a) : "memory"); return v; }
DEVI uint4 lds128v(uint32_t a) { uint4 v; asm volatile("ld.volatile.shared.v4.u32 {%0,%1,%2,%3}, [%4];" : "=r"(v.x), "=r"(v.y), "=r"(v.z), "=r"(v.w) : "r"(a) : "memory"); return v; }
DEVI uint32_t lds16(uint32_t a) { uint32_t v; asm volatile("ld.shared.u16 %0, [%1];" : "=r"(v) : "r"(a) : "memory"); return v; }
DEVI uint4 ldsm4(uint32_t a) { uint4 v; asm volatile("ldmatrix.sync.aligned.m8n8.x4.shared.b16 {%0,%1,%2,%3}, [%4];" : "=r"(v.x), "=r"(v.y), "=r"(v.z), "=r"(v.w) : "r"(a) : "memory"); return v; }
DEVI uint4 ldsm4t(uint32_t a) { uint4 v; asm volatile("ldmatrix.sync.aligned.m8n8.x4.trans.shared.b16 {%0,%1,%2,%3}, [%4];" : "=r"(v.x), "=r"(v.y), "=r"(v.z), "=r"(v.w) : "r"(a) : "memory"); return v; }
DEVI uint2 ldsm2(uint32_t a) { uint2 v; asm volatile("ldmatrix.sync.aligned.m8n8.x2.shared.b16 {%0,%1}, [%2];" : "=r"(v.x), "=r"(v.y) : "r"(a) : "memory"); return v; }
DEVI void stsm4t(uint32_t a, uint32_t x, uint32_t y, uint32_t z, uint32_t w) { asm volatile("stmatrix.sync.aligned.m8n8.x4.trans.shared.b16 [%0], {%1,%2,%3,%4};" :: "r"(a), "r"(x), "r"(y), "r"(z), "r"(w) : "memory"); }
DEVI void sts128(uint32_t a, uint32_t x, uint32_t y, uint32_t z, uint32_t w) { asm volatile("st.shared.v4.u32 [%0], {%1,%2,%3,%4};" :: "r"(a), "r"(x), "r"(y), "r"(z), "r"(w) : "memory"); }
DEVI void sts64(uint32_t a, uint32_t x, uint32_t y) { asm volatile("st.shared.v2.u32 [%0], {%1,%2};" :: "r"(a), "r"(x), "r"(y) : "memory"); }
DEVI void sts32(uint32_t a, uint32_t x) { asm volatile("st.shared.u32 [%0], %1;" :: "r"(a), "r"(x) : "memory"); }
DEVI void sts32p(uint32_t a, uint32_t x, bool pred) { asm volatile("{.reg .pred p; setp.ne.u32 p, %2, 0; @p st.shared.u32 [%0], %1;}" :: "r"(a), "r"(x), "r"((uint32_t)pred) : "memory"); }
DEVI void sta128(uint32_t a, uint32_t x, uint32_t y, uint32_t z, uint32_t w, uint32_t bar) {
    asm volatile("st.async.weak.shared::cluster.mbarrier::complete_tx::bytes.v4.b32 [%0], {%1,%2,%3,%4}, [%5];" :: "r"(a), "r"(x), "r"(y), "r"(z), "r"(w), "r"(bar) : "memory");
}
DEVI void sta128p(uint32_t a, uint32_t x, uint32_t y, uint32_t z, uint32_t w, uint32_t bar, bool pred) {
    asm volatile("{.reg .pred p; setp.ne.u32 p, %6, 0; @p st.async.weak.shared::cluster.mbarrier::complete_tx::bytes.v4.b32 [%0], {%1,%2,%3,%4}, [%5];}" :: "r"(a), "r"(x), "r"(y), "r"(z), "r"(w), "r"(bar), "r"((uint32_t)pred) : "memory");
}
DEVI void sta64(uint32_t a, uint32_t x, uint32_t y, uint32_t bar) {
    asm volatile("st.async.weak.shared::cluster.mbarrier::complete_tx::bytes.v2.b32 [%0], {%1,%2}, [%3];" :: "r"(a), "r"(x), "r"(y), "r"(bar) : "memory");
}
DEVI void sta32(uint32_t a, uint32_t x, uint32_t bar) {
    asm volatile("st.async.weak.shared::cluster.mbarrier::complete_tx::bytes.b32 [%0], %1, [%2];" :: "r"(a), "r"(x), "r"(bar) : "memory");
}
DEVI uint4 ldg_pkt(const void* p) {
    uint4 v;
    asm volatile("ld.relaxed.gpu.global.v4.u32 {%0,%1,%2,%3}, [%4];" : "=r"(v.x), "=r"(v.y), "=r"(v.z), "=r"(v.w) : "l"(p) : "memory");
    return v;
}
DEVI void ldg_pkt_if(uint4& v, const void* p, bool pred) {
    asm volatile("{.reg .pred p; setp.ne.u32 p, %5, 0; @p ld.relaxed.gpu.global.v4.u32 {%0,%1,%2,%3}, [%4];}"
        : "+r"(v.x), "+r"(v.y), "+r"(v.z), "+r"(v.w) : "l"(p), "r"((uint32_t)pred) : "memory");
}
DEVI void ldg_pkt_retry(uint4& v, const void* p, uint32_t tag) {
    asm volatile("{.reg .pred p; .reg .b32 t; lop3.b32 t, %0, %5, 1, 0x28; setp.ne.u32 p, t, 0; @p ld.relaxed.gpu.global.v4.u32 {%0,%1,%2,%3}, [%4];}"
        : "+r"(v.x), "+r"(v.y), "+r"(v.z), "+r"(v.w) : "l"(p), "r"(tag) : "memory");
}
DEVI void stg_pkt(void* p, uint32_t x, uint32_t y, uint32_t z, uint32_t w) {
    asm volatile("st.relaxed.gpu.global.v4.u32 [%0], {%1,%2,%3,%4};" :: "l"(p), "r"(x), "r"(y), "r"(z), "r"(w) : "memory");
}
DEVI uint32_t ldg_word(const void* p) { uint32_t v; asm volatile("ld.relaxed.gpu.global.u32 %0, [%1];" : "=r"(v) : "l"(p) : "memory"); return v; }
DEVI void stg_word(void* p, uint32_t x, bool pred) {
    asm volatile("{.reg .pred p; setp.ne.u32 p, %2, 0; @p st.relaxed.gpu.global.u32 [%0], %1;}" :: "l"(p), "r"(x), "r"((uint32_t)pred) : "memory");
}
DEVI uint2 ldg64nc(const void* p) { uint2 v; asm volatile("ld.global.nc.L1::no_allocate.v2.u32 {%0,%1}, [%2];" : "=r"(v.x), "=r"(v.y) : "l"(p)); return v; }
DEVI void prefetch_l2(const void* p, uint32_t bytes) { asm volatile("cp.async.bulk.prefetch.L2.global [%0], %1;" :: "l"(p), "r"(bytes) : "memory"); }
DEVI uint4 ldg128(const void* p) { uint4 v; asm volatile("ld.global.cg.v4.u32 {%0,%1,%2,%3}, [%4];" : "=r"(v.x), "=r"(v.y), "=r"(v.z), "=r"(v.w) : "l"(p) : "memory"); return v; }
DEVI uint2 ldg64(const void* p) { uint2 v; asm volatile("ld.global.cg.v2.u32 {%0,%1}, [%2];" : "=r"(v.x), "=r"(v.y) : "l"(p) : "memory"); return v; }
DEVI uint32_t ldg32(const void* p) { uint32_t v; asm volatile("ld.global.cg.u32 %0, [%1];" : "=r"(v) : "l"(p) : "memory"); return v; }
DEVI void stg128(void* p, uint32_t x, uint32_t y, uint32_t z, uint32_t w) { asm volatile("st.global.cg.v4.u32 [%0], {%1,%2,%3,%4};" :: "l"(p), "r"(x), "r"(y), "r"(z), "r"(w) : "memory"); }
DEVI void stg128p(void* p, uint32_t x, uint32_t y, uint32_t z, uint32_t w, bool pred) { asm volatile("{.reg .pred p; setp.ne.u32 p, %5, 0; @p st.global.cg.v4.u32 [%0], {%1,%2,%3,%4};}" :: "l"(p), "r"(x), "r"(y), "r"(z), "r"(w), "r"((uint32_t)pred) : "memory"); }
DEVI void stg64(void* p, uint32_t x, uint32_t y) { asm volatile("st.global.cg.v2.u32 [%0], {%1,%2};" :: "l"(p), "r"(x), "r"(y) : "memory"); }
DEVI void stg32(void* p, uint32_t x) { asm volatile("st.global.cg.u32 [%0], %1;" :: "l"(p), "r"(x) : "memory"); }
DEVI void cp16(uint32_t dst, const void* src) { asm volatile("cp.async.cg.shared.global [%0], [%1], 16;" :: "r"(dst), "l"(src) : "memory"); }
DEVI void cp16_if(uint32_t dst, const void* src, bool pred) { asm volatile("{.reg .pred p; setp.ne.u32 p, %2, 0; @p cp.async.cg.shared.global [%0], [%1], 16;}" :: "r"(dst), "l"(src), "r"((uint32_t)pred) : "memory"); }
DEVI void cp_commit() { asm volatile("cp.async.commit_group;" ::: "memory"); }
DEVI void cp4(uint32_t dst, const void* src) { asm volatile("cp.async.ca.shared.global [%0], [%1], 4;" :: "r"(dst), "l"(src) : "memory"); }
template <int N> DEVI void cp_wait() { asm volatile("cp.async.wait_group %0;" :: "n"(N) : "memory"); }
DEVI void cp_wait_all() { asm volatile("cp.async.wait_all;" ::: "memory"); }
DEVI void bar_sync(int id, int n) { asm volatile("bar.sync %0, %1;" :: "r"(id), "r"(n) : "memory"); }
DEVI void bar_arrive(int id, int n) { asm volatile("bar.arrive %0, %1;" :: "r"(id), "r"(n) : "memory"); }
DEVI void fence_async_smem() { asm volatile("fence.proxy.async.shared::cta;" ::: "memory"); }
DEVI void fence_async_global() { asm volatile("fence.proxy.async.global;" ::: "memory"); }
DEVI void mbar_init(uint32_t b, int n) { asm volatile("mbarrier.init.shared.b64 [%0], %1;" :: "r"(b), "r"(n) : "memory"); }
DEVI void mbar_expect(uint32_t b, uint32_t bytes, bool pred) {
    asm volatile("{.reg .pred p; setp.ne.u32 p, %2, 0; @p mbarrier.arrive.expect_tx.shared.b64 _, [%0], %1;}" :: "r"(b), "r"(bytes), "r"((uint32_t)pred) : "memory");
}
DEVI void mbar_arrive(uint32_t b, bool pred) { asm volatile("{.reg .pred p; setp.ne.u32 p, %1, 0; @p mbarrier.arrive.shared.b64 _, [%0];}" :: "r"(b), "r"((uint32_t)pred) : "memory"); }
DEVI void mbar_arrive_all3(uint32_t b, uint32_t lane) {
    asm volatile("{.reg .pred p; .reg .u32 a; setp.lt.u32 p, %1, 3; @p mapa.shared::cluster.u32 a, %0, %1; @p mbarrier.arrive.relaxed.cluster.shared::cluster.b64 _, [a];}" :: "r"(b), "r"(lane) : "memory");
}
#define FAULT "or.b32 n, n, 1; st.volatile.shared.u32 [n], n;\n"
#define LIM1 "400000"
#define LIM2 "2000000"
DEVI void fault_if(bool p, uint32_t n) { asm volatile("{.reg .pred p; setp.ne.u32 p, %0, 0; @p st.volatile.shared.u32 [%1], %1;}" :: "r"((uint32_t)p), "r"(n | 1) : "memory"); }
DEVI void mbar_wait(uint32_t b, uint32_t parity) {
    asm volatile("{.reg .pred p; .reg .u32 n;\n"
        "mbarrier.try_wait.parity.shared::cta.b64 p, [%0], %1;\n"
        "@p bra.uni D%=;\n"
        "mov.u32 n, 0;\n"
        "W%=: mbarrier.try_wait.parity.shared::cta.b64 p, [%0], %1;\n"
        "@p bra.uni D%=;\n"
        "add.u32 n, n, 1; setp.lt.u32 p, n, " LIM1 "; @p bra.uni W%=;\n"
        FAULT
        "D%=:}" :: "r"(b), "r"(parity) : "memory");
}
constexpr int POLL_LIMIT = 2000000;
DEVI void cnt_wait(const unsigned* c, unsigned target) {
    asm volatile("{.reg .pred p; .reg .u32 n, v;\n"
        "ld.acquire.gpu.global.u32 v, [%0];\n"
        "setp.ge.u32 p, v, %1; vote.sync.all.pred p, p, 0xffffffff; @p bra.uni D%=;\n"
        "mov.u32 n, 0;\n"
        "W%=: ld.acquire.gpu.global.u32 v, [%0];\n"
        "setp.ge.u32 p, v, %1; vote.sync.all.pred p, p, 0xffffffff; @p bra.uni D%=;\n"
        "add.u32 n, n, 1; setp.lt.u32 p, n, " LIM2 "; @p bra.uni W%=;\n"
        FAULT
        "D%=:}" :: "l"(c), "r"(target) : "memory");
}
template <int N = 1> DEVI void cnt_add(unsigned* c, int lane) {
    asm volatile("{.reg .pred p; setp.eq.u32 p, %1, 0; fence.acq_rel.gpu; bar.warp.sync 0xffffffff; @p red.relaxed.gpu.global.add.u32 [%0], %2;}" :: "l"(c + lane), "r"(lane), "n"(N) : "memory");
}
DEVI void cnt_hint(unsigned* c, int lane) {
    asm volatile("{.reg .pred p; setp.eq.u32 p, %1, 0; @p red.relaxed.gpu.global.add.u32 [%0], 1;}" :: "l"(c + lane), "r"(lane) : "memory");
}
template <int N = NT> DEVI uint32_t ring_tag(unsigned u, uint32_t ep) { return (u / RING + ep * ((N - 1 - u % RING) / RING + 1) + 1) & 1; }
static_assert(RING >= LAGA && RING > LAG, "ring too short");
DEVI uint32_t lop_bad(uint32_t acc, uint32_t x, uint32_t y, uint32_t tag) {
    uint32_t d; asm("{.reg .b32 t; lop3.b32 t, %2, %3, %4, 0x7e; or.b32 %0, t, %1;}" : "=r"(d) : "r"(acc), "r"(x), "r"(y), "r"(tag)); return d;
}
template <int N> DEVI void validate(uint4* v, const void* p, int step, uint32_t tag) {
    for (int n = 0;; n++) {
        uint32_t bad = 0;
#pragma unroll
        for (int i = 0; i < N; i += 2) bad = lop_bad(bad, v[i].x, v[i + 1 < N ? i + 1 : i].x, tag);
        if (!__any_sync(~0u, bad & 1)) break;
#pragma unroll
        for (int i = 0; i < N; i++) v[i] = ldg_pkt(static_cast<const char*>(p) + i * step);
        fault_if(n > POLL_LIMIT, n);
    }
}
DEVI uint32_t page_par(uint32_t off) { return __popc((off >> 12) & 0xb2) & 1; }
DEVI uint32_t inbox_off(int b) { return (b >> 1) * 32768 + (b & 1) * 8192; }
DEVI uint32_t mem_off(int w, int i) { return 0x180000 + w * 1024 + (i & 1) * 512 + (i & 3) * 16384 + (i < 4 ? 0 : i < 8 ? 0x30000 : 0x40000); }
DEVI void sched_fence(uint32_t zero, uint32_t id) { asm volatile("{.reg .pred p; setp.ne.u32 p, %0, %1; @p bra.uni D%=; exit; D%=:}" :: "r"(zero), "r"(id) : "memory"); }
DEVI uint32_t clk() { uint32_t c; asm volatile("mov.u32 %0, %%clock;" : "=r"(c) :: "memory"); return c; }
DEVI void delay(uint32_t n) {
    if (n) asm volatile("{.reg .pred p; .reg .u32 c, e; mov.u32 e, %%clock;\n W%=: mov.u32 c, %%clock; sub.u32 c, c, e; setp.lt.u32 p, c, %0; @p bra.uni W%=;}" :: "r"(n) : "memory");
}
DEVI void delay_until(uint32_t t0, uint32_t n) {
    asm volatile("{.reg .pred p; .reg .u32 c;\n W%=: mov.u32 c, %%clock; sub.u32 c, c, %1; setp.lt.u32 p, c, %0; @p bra.uni W%=;}" :: "r"(n), "r"(t0) : "memory");
}
DEVI void wg_fence() { asm volatile("wgmma.fence.sync.aligned;" ::: "memory"); }
DEVI void wg_commit() { asm volatile("wgmma.commit_group.sync.aligned;" ::: "memory"); }
template <int N> DEVI void wg_wait() { asm volatile("wgmma.wait_group.sync.aligned %0;" :: "n"(N) : "memory"); }
DEVI uint64_t mkdesc(uint32_t lo, uint32_t hi) { uint64_t d; asm("mov.b64 %0, {%1,%2};" : "=l"(d) : "r"(lo), "r"(hi)); return d; }
DEVI void cluster_arrive() { asm volatile("barrier.cluster.arrive.relaxed.aligned;" ::: "memory"); }
DEVI void cluster_wait() { asm volatile("barrier.cluster.wait.aligned;" ::: "memory"); }
DEVI void cluster_sync() { asm volatile("barrier.cluster.arrive.aligned;\n barrier.cluster.wait.aligned;" ::: "memory"); }
DEVI void wgmma_ss16t(float (&d)[8], uint64_t da, uint64_t db, int acc) {
    asm volatile("{.reg .pred p; setp.ne.b32 p, %10, 0;\n"
        "wgmma.mma_async.sync.aligned.m64n16k16.f32.bf16.bf16 {%0,%1,%2,%3,%4,%5,%6,%7}, %8, %9, p, 1, 1, 0, 1;}"
        : "+f"(d[0]), "+f"(d[1]), "+f"(d[2]), "+f"(d[3]), "+f"(d[4]), "+f"(d[5]), "+f"(d[6]), "+f"(d[7])
        : "l"(da), "l"(db), "r"(acc));
}
DEVI void wgmma_ss16a(float (&d)[8], uint64_t da, uint64_t db, int acc) {
    asm volatile("{.reg .pred p; setp.ne.b32 p, %10, 0;\n"
        "wgmma.mma_async.sync.aligned.m64n16k16.f32.bf16.bf16 {%0,%1,%2,%3,%4,%5,%6,%7}, %8, %9, p, 1, 1, 1, 0;}"
        : "+f"(d[0]), "+f"(d[1]), "+f"(d[2]), "+f"(d[3]), "+f"(d[4]), "+f"(d[5]), "+f"(d[6]), "+f"(d[7])
        : "l"(da), "l"(db), "r"(acc));
}
DEVI void wgmma_ss64(float (&d)[32], uint64_t da, uint64_t db, int acc) {
    asm volatile("{.reg .pred p; setp.ne.b32 p, %34, 0;\n"
        "wgmma.mma_async.sync.aligned.m64n64k16.f32.bf16.bf16 {%0,%1,%2,%3,%4,%5,%6,%7,%8,%9,%10,%11,%12,%13,%14,%15,%16,%17,%18,%19,%20,%21,%22,%23,%24,%25,%26,%27,%28,%29,%30,%31}, %32, %33, p, 1, 1, 0, 0;}"
        : "+f"(d[0]), "+f"(d[1]), "+f"(d[2]), "+f"(d[3]), "+f"(d[4]), "+f"(d[5]), "+f"(d[6]), "+f"(d[7]), "+f"(d[8]), "+f"(d[9]), "+f"(d[10]), "+f"(d[11]), "+f"(d[12]), "+f"(d[13]), "+f"(d[14]), "+f"(d[15]), "+f"(d[16]), "+f"(d[17]), "+f"(d[18]), "+f"(d[19]), "+f"(d[20]), "+f"(d[21]), "+f"(d[22]), "+f"(d[23]), "+f"(d[24]), "+f"(d[25]), "+f"(d[26]), "+f"(d[27]), "+f"(d[28]), "+f"(d[29]), "+f"(d[30]), "+f"(d[31])
        : "l"(da), "l"(db), "r"(acc));
}
DEVI void wgmma_rs16t(float (&d)[8], uint32_t a0, uint32_t a1, uint32_t a2, uint32_t a3, uint64_t db, int acc) {
    asm volatile("{.reg .pred p; setp.ne.b32 p, %13, 0;\n"
        "wgmma.mma_async.sync.aligned.m64n16k16.f32.bf16.bf16 {%0,%1,%2,%3,%4,%5,%6,%7}, {%8,%9,%10,%11}, %12, p, 1, 1, 1;}"
        : "+f"(d[0]), "+f"(d[1]), "+f"(d[2]), "+f"(d[3]), "+f"(d[4]), "+f"(d[5]), "+f"(d[6]), "+f"(d[7])
        : "r"(a0), "r"(a1), "r"(a2), "r"(a3), "l"(db), "r"(acc));
}
DEVI void wgmma_rs64(float (&d)[32], uint32_t a0, uint32_t a1, uint32_t a2, uint32_t a3, uint64_t db, int acc) {
    asm volatile("{.reg .pred p; setp.ne.b32 p, %37, 0;\n"
        "wgmma.mma_async.sync.aligned.m64n64k16.f32.bf16.bf16 {%0,%1,%2,%3,%4,%5,%6,%7,%8,%9,%10,%11,%12,%13,%14,%15,%16,%17,%18,%19,%20,%21,%22,%23,%24,%25,%26,%27,%28,%29,%30,%31}, {%32,%33,%34,%35}, %36, p, 1, 1, 0;}"
        : "+f"(d[0]), "+f"(d[1]), "+f"(d[2]), "+f"(d[3]), "+f"(d[4]), "+f"(d[5]), "+f"(d[6]), "+f"(d[7]), "+f"(d[8]), "+f"(d[9]), "+f"(d[10]), "+f"(d[11]), "+f"(d[12]), "+f"(d[13]), "+f"(d[14]), "+f"(d[15]), "+f"(d[16]), "+f"(d[17]), "+f"(d[18]), "+f"(d[19]), "+f"(d[20]), "+f"(d[21]), "+f"(d[22]), "+f"(d[23]), "+f"(d[24]), "+f"(d[25]), "+f"(d[26]), "+f"(d[27]), "+f"(d[28]), "+f"(d[29]), "+f"(d[30]), "+f"(d[31])
        : "r"(a0), "r"(a1), "r"(a2), "r"(a3), "l"(db), "r"(acc));
}
DEVI void wgmma_ss168t(float (&d)[84], uint64_t da, uint64_t db, int acc) {
    asm volatile("{.reg .pred p; setp.ne.b32 p, %86, 0;\n"
        "wgmma.mma_async.sync.aligned.m64n168k16.f32.bf16.bf16 {%0,%1,%2,%3,%4,%5,%6,%7,%8,%9,%10,%11,%12,%13,%14,%15,%16,%17,%18,%19,%20,%21,%22,%23,%24,%25,%26,%27,%28,%29,%30,%31,%32,%33,%34,%35,%36,%37,%38,%39,%40,%41,%42,%43,%44,%45,%46,%47,%48,%49,%50,%51,%52,%53,%54,%55,%56,%57,%58,%59,%60,%61,%62,%63,%64,%65,%66,%67,%68,%69,%70,%71,%72,%73,%74,%75,%76,%77,%78,%79,%80,%81,%82,%83}, %84, %85, p, 1, 1, 0, 1;}"
        : "+f"(d[0]), "+f"(d[1]), "+f"(d[2]), "+f"(d[3]), "+f"(d[4]), "+f"(d[5]), "+f"(d[6]), "+f"(d[7]), "+f"(d[8]), "+f"(d[9]), "+f"(d[10]), "+f"(d[11]), "+f"(d[12]), "+f"(d[13]), "+f"(d[14]), "+f"(d[15]), "+f"(d[16]), "+f"(d[17]), "+f"(d[18]), "+f"(d[19]), "+f"(d[20]), "+f"(d[21]), "+f"(d[22]), "+f"(d[23]), "+f"(d[24]), "+f"(d[25]), "+f"(d[26]), "+f"(d[27]), "+f"(d[28]), "+f"(d[29]), "+f"(d[30]), "+f"(d[31]), "+f"(d[32]), "+f"(d[33]), "+f"(d[34]), "+f"(d[35]), "+f"(d[36]), "+f"(d[37]), "+f"(d[38]), "+f"(d[39]), "+f"(d[40]), "+f"(d[41]), "+f"(d[42]), "+f"(d[43]), "+f"(d[44]), "+f"(d[45]), "+f"(d[46]), "+f"(d[47]), "+f"(d[48]), "+f"(d[49]), "+f"(d[50]), "+f"(d[51]), "+f"(d[52]), "+f"(d[53]), "+f"(d[54]), "+f"(d[55]), "+f"(d[56]), "+f"(d[57]), "+f"(d[58]), "+f"(d[59]), "+f"(d[60]), "+f"(d[61]), "+f"(d[62]), "+f"(d[63]), "+f"(d[64]), "+f"(d[65]), "+f"(d[66]), "+f"(d[67]), "+f"(d[68]), "+f"(d[69]), "+f"(d[70]), "+f"(d[71]), "+f"(d[72]), "+f"(d[73]), "+f"(d[74]), "+f"(d[75]), "+f"(d[76]), "+f"(d[77]), "+f"(d[78]), "+f"(d[79]), "+f"(d[80]), "+f"(d[81]), "+f"(d[82]), "+f"(d[83])
        : "l"(da), "l"(db), "r"(acc));
}
DEVI void wgmma_rs96t(float (&d)[48], uint32_t a0, uint32_t a1, uint32_t a2, uint32_t a3, uint64_t db, int acc) {
    asm volatile("{.reg .pred p; setp.ne.b32 p, %53, 0;\n"
        "wgmma.mma_async.sync.aligned.m64n96k16.f32.bf16.bf16 {%0,%1,%2,%3,%4,%5,%6,%7,%8,%9,%10,%11,%12,%13,%14,%15,%16,%17,%18,%19,%20,%21,%22,%23,%24,%25,%26,%27,%28,%29,%30,%31,%32,%33,%34,%35,%36,%37,%38,%39,%40,%41,%42,%43,%44,%45,%46,%47}, {%48,%49,%50,%51}, %52, p, 1, 1, 1;}"
        : "+f"(d[0]), "+f"(d[1]), "+f"(d[2]), "+f"(d[3]), "+f"(d[4]), "+f"(d[5]), "+f"(d[6]), "+f"(d[7]), "+f"(d[8]), "+f"(d[9]), "+f"(d[10]), "+f"(d[11]), "+f"(d[12]), "+f"(d[13]), "+f"(d[14]), "+f"(d[15]), "+f"(d[16]), "+f"(d[17]), "+f"(d[18]), "+f"(d[19]), "+f"(d[20]), "+f"(d[21]), "+f"(d[22]), "+f"(d[23]), "+f"(d[24]), "+f"(d[25]), "+f"(d[26]), "+f"(d[27]), "+f"(d[28]), "+f"(d[29]), "+f"(d[30]), "+f"(d[31]), "+f"(d[32]), "+f"(d[33]), "+f"(d[34]), "+f"(d[35]), "+f"(d[36]), "+f"(d[37]), "+f"(d[38]), "+f"(d[39]), "+f"(d[40]), "+f"(d[41]), "+f"(d[42]), "+f"(d[43]), "+f"(d[44]), "+f"(d[45]), "+f"(d[46]), "+f"(d[47])
        : "r"(a0), "r"(a1), "r"(a2), "r"(a3), "l"(db), "r"(acc));
}
DEVI void wgmma_rs192t(float (&d)[96], uint32_t a0, uint32_t a1, uint32_t a2, uint32_t a3, uint64_t db, int acc) {
    asm volatile("{.reg .pred p; setp.ne.b32 p, %101, 0;\n"
        "wgmma.mma_async.sync.aligned.m64n192k16.f32.bf16.bf16 {%0,%1,%2,%3,%4,%5,%6,%7,%8,%9,%10,%11,%12,%13,%14,%15,%16,%17,%18,%19,%20,%21,%22,%23,%24,%25,%26,%27,%28,%29,%30,%31,%32,%33,%34,%35,%36,%37,%38,%39,%40,%41,%42,%43,%44,%45,%46,%47,%48,%49,%50,%51,%52,%53,%54,%55,%56,%57,%58,%59,%60,%61,%62,%63,%64,%65,%66,%67,%68,%69,%70,%71,%72,%73,%74,%75,%76,%77,%78,%79,%80,%81,%82,%83,%84,%85,%86,%87,%88,%89,%90,%91,%92,%93,%94,%95}, {%96,%97,%98,%99}, %100, p, 1, 1, 1;}"
        : "+f"(d[0]), "+f"(d[1]), "+f"(d[2]), "+f"(d[3]), "+f"(d[4]), "+f"(d[5]), "+f"(d[6]), "+f"(d[7]), "+f"(d[8]), "+f"(d[9]), "+f"(d[10]), "+f"(d[11]), "+f"(d[12]), "+f"(d[13]), "+f"(d[14]), "+f"(d[15]), "+f"(d[16]), "+f"(d[17]), "+f"(d[18]), "+f"(d[19]), "+f"(d[20]), "+f"(d[21]), "+f"(d[22]), "+f"(d[23]), "+f"(d[24]), "+f"(d[25]), "+f"(d[26]), "+f"(d[27]), "+f"(d[28]), "+f"(d[29]), "+f"(d[30]), "+f"(d[31]), "+f"(d[32]), "+f"(d[33]), "+f"(d[34]), "+f"(d[35]), "+f"(d[36]), "+f"(d[37]), "+f"(d[38]), "+f"(d[39]), "+f"(d[40]), "+f"(d[41]), "+f"(d[42]), "+f"(d[43]), "+f"(d[44]), "+f"(d[45]), "+f"(d[46]), "+f"(d[47]), "+f"(d[48]), "+f"(d[49]), "+f"(d[50]), "+f"(d[51]), "+f"(d[52]), "+f"(d[53]), "+f"(d[54]), "+f"(d[55]), "+f"(d[56]), "+f"(d[57]), "+f"(d[58]), "+f"(d[59]), "+f"(d[60]), "+f"(d[61]), "+f"(d[62]), "+f"(d[63]), "+f"(d[64]), "+f"(d[65]), "+f"(d[66]), "+f"(d[67]), "+f"(d[68]), "+f"(d[69]), "+f"(d[70]), "+f"(d[71]), "+f"(d[72]), "+f"(d[73]), "+f"(d[74]), "+f"(d[75]), "+f"(d[76]), "+f"(d[77]), "+f"(d[78]), "+f"(d[79]), "+f"(d[80]), "+f"(d[81]), "+f"(d[82]), "+f"(d[83]), "+f"(d[84]), "+f"(d[85]), "+f"(d[86]), "+f"(d[87]), "+f"(d[88]), "+f"(d[89]), "+f"(d[90]), "+f"(d[91]), "+f"(d[92]), "+f"(d[93]), "+f"(d[94]), "+f"(d[95])
        : "r"(a0), "r"(a1), "r"(a2), "r"(a3), "l"(db), "r"(acc));
}

#define TRD(t, i)
namespace km {
#define NSS 6
#define RG "184"
#define RW "136"
#define NFL 2
#define NR1 3
#define NR2 3
#define FK 5
#define NGAP 8
constexpr int O_H = 0;
constexpr int O_MB = 73728;
constexpr int O_VX = 96768;
constexpr int O_KX = 113152;
constexpr int O_QX = 119296;
constexpr int O_VM = 125440;
constexpr int O_KM = 129536;
constexpr int O_QM = 131072;
constexpr int O_SM = 132608;
constexpr int O_ST = 135168;
constexpr int O_OX = 145408;
constexpr int O_WO = 149504;
constexpr int O_OS = O_WO;
constexpr int O_WS = O_WO + 49152;
constexpr int O_RL = 110592;
constexpr int O_BAR = O_WS + NSS * 4096;
constexpr int SMEM = O_BAR + 128 + 1024 + TR_BYTES;
enum { B_X = 0, B_XFREE = 8, B_WIN = 16, B_VX = 24, B_SM = 32, B_ST = 40, B_SU = 48, B_EP = 56 };
#define DLY1 (100 * w)
#define DLY2 300
#define XON 1
#define GON 1
#define DLY0 1000
#define PFON 0
#define PLACE 1
#define XST 0
#define DLYW 12000
#define DLYB 14000
constexpr uint32_t DESC_HI = (1024 >> 4) | (1u << 30);
constexpr float SC = 0.08838834764831845f * 1.4426950408889634f;
}

__global__ void __cluster_dims__(3, 1, 1) __launch_bounds__(384, 1)
k_main(const __nv_bfloat16* __restrict__ x0, const __nv_bfloat16* __restrict__ wqkv, const __nv_bfloat16* __restrict__ wo,
       const __nv_bfloat16* __restrict__ mem0, const __nv_bfloat16* __restrict__ Wq, const __nv_bfloat16* __restrict__ Wk,
       const __nv_bfloat16* __restrict__ Wv, const __nv_bfloat16* __restrict__ Wo) {
    using namespace km;
    extern __shared__ unsigned char smem_raw[];
    const uint32_t sb = (smem_u32(smem_raw) + 1023) & ~1023u;
    const int tid = threadIdx.x, lane = tid & 31, warp = __shfl_sync(~0u, tid >> 5, 0);
    uint32_t l16 = __shfl_sync(~0u, lane * 16, lane);
#define OPQ() asm volatile("" : "+r"(l16))
    const int b = blockIdx.x, h = b / 3, r = b % 3;
    const int nq = r == 2 ? 2 : 3;
    const uint32_t bar = sb + O_BAR;
    asm volatile("griddepcontrol.launch_dependents;");
    const uint32_t t_start = clk();
    if (warp == 0 && b < 72) {
        if (lane == 0) { mbar_init(bar + 96, 1); fence_async_smem(); mbar_expect(bar + 96, 8 * 3456, true); }
        __syncwarp();
        if (lane < 8) asm volatile("cp.async.bulk.shared::cluster.global.mbarrier::complete_tx::bytes [%0], [%1], 3456, [%2];" :: "r"(sb + O_RL + lane * 3472), "l"(wqkv + (b * 8 + lane) * 1728), "r"(bar + 96) : "memory");
    }
    if (tid == 352) {
        prefetch_l2(x0 + b * (2 * DM), 2 * 1152); prefetch_l2(wo + b * (6 * DM), 6 * 1152);
    }
    if (tid == 320) sts32(bar + 64, ldg32(&g_epoch));
#define EP lds32(bar + 64)
    TR_INIT(bar + 128);
    TRG(79, 0);
    uint32_t roff0, roff1;
    {
        uint32_t y0, y1;
        asm("mapa.shared::cluster.u32 %0, %1, %2;" : "=r"(y0) : "r"(sb), "r"((r + 1) % 3));
        asm("mapa.shared::cluster.u32 %0, %1, %2;" : "=r"(y1) : "r"(sb), "r"((r + 2) % 3));
        roff0 = y0 - sb; roff1 = y1 - sb;
    }
#define LSWAP ((l16 & 0x70) | ((l16 & 0x80) << 1) | ((l16 & 0x100) >> 1))
    const uint32_t nv_remote = 8 - (8 - 2 * nq);

    if (warp < 8) {
        asm volatile("setmaxnreg.inc.sync.aligned.u32 " RG ";");
        constexpr int SSP = 36 / NSS;
#define IS_SS(kk) ((kk) % SSP == 3)
#define AI(kk) (4 * ((kk) - ((kk) + SSP - 4) / SSP))
        uint32_t a[144 - 4 * NSS];
        {
            const int ci = tid & 15, slot = ci >> 1, d0 = tid >> 4;
            const __nv_bfloat16* src = slot < nq ? Wq + (3 * r + slot) * 16 : slot < 2 * nq ? Wk + (3 * r + slot - nq) * 16 : Wv + (2 * r + slot - 2 * nq) * 16;
            src += h * 128 + (ci & 1) * 8 + d0 * 4096;
            auto issue = [&](int q) {
#pragma unroll
                for (int i = 0; i < 3; i++) if (q < 12) cp16(sb + (q * 3 + i) * 4096 + d0 * 256 + ((ci ^ (d0 & 7)) << 4), src + (size_t)(q * 3 + i) * 65536);
                asm volatile("cp.async.commit_group;" ::: "memory");
            };
            if (b < 72) {
                bar_sync(10, 256);
                mbar_wait(bar + 96, 0);
                TR1(4);
#pragma unroll 2
                for (int ag = tid >> 3; ag < 231; ag += 32) {
                    const int a = ag / 21, gr = ag % 21, tl = gr >= 18;
                    const int head = 3 * a + (tl ? 0 : (gr % 6) >> 1), nw = tl ? min(3, 32 - head) : head < 32 ? 4 : 0;
                    const uint32_t p = sb + O_RL + (tid & 7) * 3472 + (tl ? gr - 18 : gr / 6) * 1152 + head * 36 + (tl ? 32 : (gr & 1) * 16), step = tl ? 36 : 4;
                    uint32_t v[4];
#pragma unroll
                    for (int i = 0; i < 4; i++) { v[i] = lds32(p + i * step); if (i >= nw) v[i] = 0; }
                    stg128(g_wa + ((a * 9 + (b >> 3)) * 21 + gr) * 64 + (b & 7) * 8 + (tid & 7), v[0], v[1], v[2], v[3]);
                }
            }
            {
                bar_arrive(15, 288);
                TR1(5);
                delay_until(t_start, DLY0);
#pragma unroll
                for (int q = 0; q < NFL; q++) issue(q);
            }
            TR1(1);
            const int mi = lane >> 3;
            const uint32_t ad = sb + ((mi >> 1) * 8 + (lane & 7)) * 256 + (((warp * 2 + (mi & 1)) ^ (lane & 7)) << 4);
#pragma unroll
            for (int kk = 0; kk < 36; kk++) {
                if (kk % 3 == 0) { cp_wait<NFL - 1>(); issue(kk / 3 + NFL); bar_sync(10, 256); }
                const uint4 f = ldsm4t(ad + kk * 4096);
                if (IS_SS(kk)) {
                    const uint32_t o0 = sb + O_WS + (kk / SSP) * 4096 + warp * 512 + lane * 4;
                    sts32(o0, f.x); sts32(o0 + 256, f.y); sts32(o0 + 128, f.z); sts32(o0 + 384, f.w);
                } else { a[AI(kk)] = f.x; a[AI(kk) + 1] = f.y; a[AI(kk) + 2] = f.z; a[AI(kk) + 3] = f.w; }
            }
            TR1(2);
            bar_sync(9, 384);
#pragma unroll
            for (int i = 0; i < 9; i++) sts128(sb + O_H + i * 8192 + 4096 + tid * 16, 0, 0, 0, 0);
#pragma unroll
            for (int i = 0; i < 8; i++) if (i * 256 + tid < (O_OX - O_KX) / 16) sts128(sb + O_KX + i * 4096 + tid * 16, 0, 0, 0, 0);
            fence_async_smem();
            cluster_sync();
        }
        TR1(3);
        const int kind = warp < nq ? 0 : warp < 2 * nq ? 1 : 2;
        const int sl = kind == 0 ? warp : kind == 1 ? warp - nq : 2 * r + warp - 2 * nq;
        const uint32_t adX0 = sb + (kind == 0 ? O_QX : kind == 1 ? O_KX : O_VX) + sl * 2048;
        const uint32_t adM0 = sb + (kind == 0 ? O_QM : kind == 1 ? O_KM : O_VM) + sl * 512;
        const uint32_t hlo = (((sb + O_H) >> 4) & 0x3fff) | (1u << 16);
        const uint32_t mlo = (((sb + O_MB) >> 4) & 0x3fff) | (16u << 16);
        const uint32_t wlo = (((sb + O_WS + (warp >> 2) * 2048) >> 4) & 0x3fff) | (8u << 16);
        const int L = (warp >> 1) & 1, qh = warp & 1;
        const uint32_t st = sb + O_ST + warp * 1280;
        float s[5][4];

#pragma unroll 1
        for (int t = -1;; t++) {
            TR_ON(t);
            OPQ();
            const uint32_t adX = adX0 + l16, adM = adM0 + l16, l8 = l16 >> 1;
            const uint32_t lq = LSWAP;
            if (t >= 0) {
                {
                    float d0[8], d1[8];
#pragma unroll
                    for (int G = 0; G < 3; G++) {
                        if (warp < 4) bar_sync(1 + G, 160); else bar_sync(12 + G, 160);
                        if (G == 0) wg_fence();
#pragma unroll
                        for (int q = 0; q < 12; q++) {
                            const int kk = 12 * G + q;
                            const uint64_t db = mkdesc(mlo + kk * 32, 8);
                            if (IS_SS(kk)) wgmma_ss16t((kk & 1) ? d1 : d0, mkdesc(wlo + (kk / SSP) * 256, 16), db, 1);
                            else wgmma_rs16t((kk & 1) ? d1 : d0, a[AI(kk)], a[AI(kk) + 1], a[AI(kk) + 2], a[AI(kk) + 3], db, kk >= 2);
                            if (kk == 0) TR(0);
                        }
                    }
                    wg_commit(); wg_wait<0>();
                    TR(1);
                    const uint32_t p0 = pk(d0[0] + d1[0], d0[1] + d1[1]), p1 = pk(d0[2] + d1[2], d0[3] + d1[3]);
                    const uint32_t p2 = pk(d0[4] + d1[4], d0[5] + d1[5]), p3 = pk(d0[6] + d1[6], d0[7] + d1[7]);
                    if (kind == 2) {
                        sts128(adM, p0, p1, p2, p3);
                        bar_arrive(4, 384);
                        sta128(adM + roff0, p0, p1, p2, p3, bar + B_SM + roff0);
                        sta128(adM + roff1, p0, p1, p2, p3, bar + B_SM + roff1);
                    } else {
                        stsm4t(adM, p0, p1, p2, p3);
                        bar_arrive(4, 384);
                    }
                }
                if (warp < 4) {
                    {
                        uint4 q[3];
                        s[4][0] = s[4][1] = s[4][2] = s[4][3] = 0.f;
                        mbar_wait(bar + B_ST, t & 1);
                        bar_sync(5, 256);
                        const uint4 k01 = ldsm4(sb + O_KM + L * 256 + l16 + (l16 & 256));
                        const uint2 k2 = ldsm2(sb + O_KM + 1024 + L * 256 + l16);
#pragma unroll
                        for (int m = 0; m < 3; m++) q[m] = ldsm4(sb + O_QX + m * 2048 + warp * 512 + lq);
                        mma16(s[4], q[0].x, q[0].y, q[0].z, q[0].w, k01.x, k01.y);
                        mma16(s[4], q[1].x, q[1].y, q[1].z, q[1].w, k01.z, k01.w);
                        mma16(s[4], q[2].x, q[2].y, q[2].z, q[2].w, k2.x, k2.y);
                        const uint32_t w0 = pk(s[4][0], s[4][1]), w1 = pk(s[4][2], s[4][3]);
                        bar_arrive(11, 256);
                        sta64(st + l8 + 5120 + 1024 + roff0, w0, w1, bar + B_SU + roff0);
                        sta64(st + l8 + 1024 + roff1, w0, w1, bar + B_SU + roff1);
                    }
                    TR(2);
#pragma unroll
                    for (int src = 0; src < 2; src++) {
                        const uint4 u = lds128(st + src * 5120 + l16), v = lds128(st + src * 5120 + 512 + l16);
                        s[0][0] += bf_lo(u.x); s[0][1] += bf_hi(u.x); s[0][2] += bf_lo(u.y); s[0][3] += bf_hi(u.y);
                        s[1][0] += bf_lo(u.z); s[1][1] += bf_hi(u.z); s[1][2] += bf_lo(u.w); s[1][3] += bf_hi(u.w);
                        s[2][0] += bf_lo(v.x); s[2][1] += bf_hi(v.x); s[2][2] += bf_lo(v.y); s[2][3] += bf_hi(v.y);
                        s[3][0] += bf_lo(v.z); s[3][1] += bf_hi(v.z); s[3][2] += bf_lo(v.w); s[3][3] += bf_hi(v.w);
                    }
                    uint4 v0[3], v1[3];
#pragma unroll
                    for (int m = 0; m < 3; m++) {
                        v0[m] = lds128(sb + O_VX + (3 * r + m) * 2048 + L * 1024 + l16);
                    }
                    mbar_wait(bar + B_SM, t & 1);
                    mbar_wait(bar + B_SU, t & 1);
                    TR(3);
                    {
                        const uint2 x = lds64(st + 1024 + l8), y = lds64(st + 5120 + 1024 + l8);
                        s[4][0] += bf_lo(x.x) + bf_lo(y.x); s[4][1] += bf_hi(x.x) + bf_hi(y.x); s[4][2] += bf_lo(x.y) + bf_lo(y.y); s[4][3] += bf_hi(x.y) + bf_hi(y.y);
                    }
                    float mx0 = fmaxf(s[4][0], s[4][1]), mx1 = fmaxf(s[4][2], s[4][3]);
#pragma unroll
                    for (int n = 0; n < 4; n++) { mx0 = fmaxf(mx0, fmaxf(s[n][0], s[n][1])); mx1 = fmaxf(mx1, fmaxf(s[n][2], s[n][3])); }
#pragma unroll
                    for (int o = 1; o < 4; o <<= 1) { mx0 = fmaxf(mx0, __shfl_xor_sync(~0u, mx0, o)); mx1 = fmaxf(mx1, __shfl_xor_sync(~0u, mx1, o)); }
                    mx0 *= -SC; mx1 *= -SC;
                    float l0 = 0.f, l1 = 0.f;
                    uint32_t p[10];
#pragma unroll
                    for (int n = 0; n < 5; n++) {
                        const float e0 = ex2(fmaf(s[n][0], SC, mx0)), e1 = ex2(fmaf(s[n][1], SC, mx0));
                        const float e2 = ex2(fmaf(s[n][2], SC, mx1)), e3 = ex2(fmaf(s[n][3], SC, mx1));
                        l0 += e0 + e1; l1 += e2 + e3;
                        p[2 * n] = pk(e0, e1); p[2 * n + 1] = pk(e2, e3);
                    }
#pragma unroll
                    for (int o = 1; o < 4; o <<= 1) { l0 += __shfl_xor_sync(~0u, l0, o); l1 += __shfl_xor_sync(~0u, l1, o); }
                    l0 = rcp(l0); l1 = rcp(l1);
                    const uint32_t otag = ring_tag(t, EP);
#pragma unroll
                    for (int m = 0; m < 3; m++) {
                        float o0[4] = {0, 0, 0, 0}, o1[4] = {0, 0, 0, 0};
                        v1[m] = lds128(sb + O_VX + (3 * r + m) * 2048 + L * 1024 + 512 + l16);
                        const uint2 vm = lds64(sb + O_VM + (3 * r + m) * 512 + l16 + L * 8);
                        mma8(o0, p[0], p[1], v0[m].x); mma8(o1, p[0], p[1], v0[m].y); mma8(o0, p[2], p[3], v0[m].z); mma8(o1, p[2], p[3], v0[m].w);
                        mma8(o0, p[4], p[5], v1[m].x); mma8(o1, p[4], p[5], v1[m].y); mma8(o0, p[6], p[7], v1[m].z); mma8(o1, p[6], p[7], v1[m].w);
                        mma8(o0, p[8], p[9], vm.x); mma8(o1, p[8], p[9], vm.y);
                        sts128(sb + O_OS + warp * 1536 + m * 512 + l16, (pk(o0[0] * l0, o0[1] * l0) & ~1u) | otag, pk(o0[2] * l1, o0[3] * l1), pk(o1[0] * l0, o1[1] * l0), pk(o1[2] * l1, o1[3] * l1));
                    }
                    TR(4);
                }
            }
            if (t + 1 >= NT) break;
            {
                float d[32];
                mbar_wait(bar + B_X, (t + 1) & 1);
                if (warp < 4) bar_sync(7, 384); else if (t >= 0) bar_sync(11, 256);
                wg_fence();
                TR(6);
#pragma unroll
                for (int kk = 0; kk < 36; kk++) {
                    if (kk == NGAP) asm volatile("{.reg .pred p; setp.ge.u32 p, %0, 4; @p bar.sync 7, 384;}" :: "r"(warp) : "memory");
                    const uint64_t db = mkdesc(hlo + ((kk >> 2) * 8192 + (kk & 3) * 32) / 16, DESC_HI);
                    if (IS_SS(kk)) wgmma_ss64(d, mkdesc(wlo + (kk / SSP) * 256, 16), db, 1);
                    else wgmma_rs64(d, a[AI(kk)], a[AI(kk) + 1], a[AI(kk) + 2], a[AI(kk) + 3], db, kk > 0);
                }
                wg_commit();
                TR(5);
                mbar_wait(bar + B_WIN, (t + 1) & 1);
                wg_wait<0>();
                TR(7);
                mbar_arrive_all3(bar + B_XFREE, l16 >> 4);
                uint32_t p[16];
#pragma unroll
                for (int u = 0; u < 16; u++) p[u] = pk(d[2 * u], d[2 * u + 1]);
                if (kind == 2) {
#pragma unroll
                    for (int u = 0; u < 4; u++) sts128(adX + u * 512, p[4 * u], p[4 * u + 1], p[4 * u + 2], p[4 * u + 3]);
                } else {
#pragma unroll
                    for (int u = 0; u < 4; u++) stsm4t(adX + u * 512, p[4 * u], p[4 * u + 1], p[4 * u + 2], p[4 * u + 3]);
                }
                __syncwarp();
                asm volatile("{.reg .pred p; setp.eq.u32 p, %1, 0; @p mbarrier.arrive.shared.b64 _, [%0];}" :: "r"(bar + B_EP), "r"(l16) : "memory");
                if (kind == 2) {
                    fence_async_smem();
                    __syncwarp();
                    asm volatile("{.reg .pred p; setp.eq.u32 p, %5, 0;\n"
                        "@p cp.async.bulk.shared::cluster.shared::cta.mbarrier::complete_tx::bytes [%0], [%2], 2048, [%3];\n"
                        "@p cp.async.bulk.shared::cluster.shared::cta.mbarrier::complete_tx::bytes [%1], [%2], 2048, [%4];}"
                        :: "r"(adX0 + roff0), "r"(adX0 + roff1), "r"(adX0), "r"(bar + B_VX + roff0), "r"(bar + B_VX + roff1), "r"(l16) : "memory");
                }
                TR(8);
                {
                    const int lim = 16 * qh + (int)(l16 >> 6) - (int)((l16 >> 3) & 6);
#pragma unroll
                    for (int n = 0; n < 4; n++)
#pragma unroll
                        for (int j = 0; j < 4; j++) s[n][j] = (n == 0 && j >= 2) || 8 * (n - (j >> 1)) + (j & 1) <= lim ? 0.f : -1e30f;
                }
                if (warp < 4) {
                    mbar_wait(bar + B_EP, (t + 1) & 1);
#pragma unroll
                    for (int m = 0; m < 3; m++) {
                        const uint4 q = ldsm4(sb + O_QX + m * 2048 + warp * 512 + lq);
                        const uint4 k0 = ldsm4(sb + O_KX + m * 2048 + L * 1024 + l16);
                        const uint4 k1 = ldsm4(sb + O_KX + m * 2048 + L * 1024 + 512 + l16);
                        mma16(s[0], q.x, q.y, q.z, q.w, k0.x, k0.y);
                        mma16(s[1], q.x, q.y, q.z, q.w, k0.z, k0.w);
                        mma16(s[2], q.x, q.y, q.z, q.w, k1.x, k1.y);
                        mma16(s[3], q.x, q.y, q.z, q.w, k1.z, k1.w);
                    }
                    uint32_t w0 = pk(s[0][0], s[0][1]), w1 = pk(s[0][2], s[0][3]), w2 = pk(s[1][0], s[1][1]), w3 = pk(s[1][2], s[1][3]);
                    sta128(st + l16 + 5120 + roff0, w0, w1, w2, w3, bar + B_ST + roff0);
                    sta128(st + l16 + roff1, w0, w1, w2, w3, bar + B_ST + roff1);
                    w0 = pk(s[2][0], s[2][1]); w1 = pk(s[2][2], s[2][3]); w2 = pk(s[3][0], s[3][1]); w3 = pk(s[3][2], s[3][3]);
                    sta128p(st + l16 + 5120 + 512 + roff0, w0, w1, w2, w3, bar + B_ST + roff0, qh);
                    sta128p(st + l16 + 512 + roff1, w0, w1, w2, w3, bar + B_ST + roff1, qh);
                    TR(9);
                }
            }
        }
        if (warp >= 4) bar_sync(11, 256); else bar_arrive(7, 160);
        cluster_sync();
    } else {
        asm volatile("setmaxnreg.dec.sync.aligned.u32 " RW ";");
        const int w = warp - 8, t2 = tid - 256;
        if (t2 == 0) {
            mbar_init(bar + B_X, 1); mbar_init(bar + B_XFREE, 24); mbar_init(bar + B_WIN, 3);
            mbar_init(bar + B_VX, 1); mbar_init(bar + B_SM, 1); mbar_init(bar + B_ST, 1); mbar_init(bar + B_SU, 1); mbar_init(bar + B_EP, 8);
            asm volatile("fence.mbarrier_init.release.cluster;" ::: "memory");
        }
        char* const ex = reinterpret_cast<char*>((reinterpret_cast<uintptr_t>(g_ex) + 0x1fffff) & ~(uintptr_t)0x1fffff);
        char* rbase = ex; uint32_t side = 0;
        {
            uint32_t m0[5][4];
#pragma unroll
            for (int i = 0; i < 5; i++) {
                const unsigned short* m = reinterpret_cast<const unsigned short*>(mem0) + min(i * 128 + t2, DM - 1);
#pragma unroll
                for (int j = 0; j < 4; j++) m0[i][j] = m[2 * j * DM] | (m[(2 * j + 1) * DM] << 16);
            }
            if (w == 3) { bar_sync(15, 288); cnt_add(g_cnt + C_W * 8, lane); TR1(1); }
            if (t2 >= 96 && t2 < 99 && PFON) prefetch_l2((t2 == 96 ? Wq : t2 == 97 ? Wk : Wv) + b * (6 * 4096), 6 * 8192);
            delay_until(t_start, DLYW);
#pragma unroll 4
            for (int i = t2; i < 128 * 24; i += 128) {
                const int e = (i >> 3) & 127, G = i >> 10, q = i & 7;
                cp16(sb + O_WO + G * 16384 + e * 128 + ((q ^ (e & 7) ^ ((h >> 1) & 1)) << 4), Wo + (size_t)(h * 128 + e) * DM + G * 192 + r * 64 + q * 8);
            }
            bar_sync(9, 384);
#pragma unroll
            for (int i = 0; i < 5; i++) {
                const int k = min(i * 128 + t2, DM - 1);
                const uint32_t ad = sb + O_MB + (k >> 3) * 256 + (k & 7) * 16;
                sts128(ad, m0[i][0], m0[i][1], m0[i][2], m0[i][3]); sts128(ad + 128, m0[i][0], m0[i][1], m0[i][2], m0[i][3]);
            }
            fence_async_smem();
        }
        auto arm = [&]() {
            const uint32_t ln = l16 >> 4;
            mbar_expect(bar + B_VX + (ln & 3) * 8, ln == 0 ? nv_remote * 2048 : ln == 1 ? nv_remote * 512 + 2560 : ln == 2 ? 6144 : 2048, ln < 4);
        };
        if (w == 3) arm();
        cluster_sync();
        TR1(3);
        const int L = w >> 1, hf = w & 1;
        const uint32_t rd = hf ? roff1 : roff0;
        const uint32_t rzero = gridDim.y + 100;
#define WOAD (sb + O_WO + ((l16 & 0x100) << 2) + ((l16 & 0x70) << 3) + (((w * 32) | ((l16 >> 3) & 16)) ^ (l16 & 0x70)))

        auto fetch_tile = [&](int u) {
            const bool a0 = u < NSEG && (XON || u < 8), a1 = u >= LAG && (XON || u < 8);
            mbar_expect(bar + B_X, ((int)a0 + (int)a1) * 36864, l16 == 0);
            const int kb = (l16 >> 5) * 3 + r, hl = (l16 >> 4) & 1;
            asm volatile("{.reg .pred p; setp.ne.u32 p, %4, 0;\n"
                "@p cp.async.bulk.shared::cluster.global.mbarrier::complete_tx::bytes.multicast::cluster [%0], [%1], 4096, [%2], %3;}"
                :: "r"(sb + O_H + kb * 8192 + hl * 4096), "l"(g_xt + ((u * 2 + hl) * 9 + kb) * 256), "r"(bar + B_X), "h"((uint16_t)7),
                   "r"((uint32_t)(l16 < 96 && (hl ? a1 : a0))) : "memory");
        };
        auto store_o = [&](int u) {
            asm volatile("{.reg .pred p; setp.lt.u32 p, %3, 64;\n"
                "@p cp.async.bulk.global.shared::cta.bulk_group [%0], [%1], %2;\n cp.async.bulk.commit_group;}"
                :: "l"(g_o + (((u & (RING - 1)) * 4 + ((l16 >> 4) & 3)) * 256 + h * 8 + 3 * r) * 32), "r"(sb + O_OS + (l16 & 48) * 96), "r"(nq * 512), "r"(l16) : "memory");
        };
        auto hint_o = [&](int u) {
            asm volatile("cp.async.bulk.wait_group 0;" ::: "memory");
            __syncwarp();
            cnt_hint(g_cnt + (C_O + u * 8 + (h >> 2)) * 8, l16);
            TRG(u, 2);
        };
        bar_arrive(7, 384);
        if (w < 3) {
            bar_arrive(1 + w, 160); bar_arrive(12 + w, 160); if (w == 0) bar_arrive(8, 64);
            if (w < 2) {
                unsigned* pp = reinterpret_cast<unsigned*>(ex + inbox_off(b) + 16384 + w * 4096 + 2048);
                uint32_t best = ~0u, v = 0;
                if (lane == 0) {
#pragma unroll 1
                    for (int i = 0; i < 6; i++) {
                        const uint32_t c0 = clk();
                        v = atomicAdd(pp + (v >> 31), 0);
                        asm volatile("" :: "r"(v) : "memory");
                        sts32(bar + 80, v);
                        best = min(best, clk() - c0);
                    }
                    sts32(bar + 72 + w * 4, best);
                }
            }
            bar_sync(15, 96);
            const uint32_t xs = PLACE ? lds32(bar + 76) < lds32(bar + 72) : 0, ep = EP;
            side = PLACE ? xs ^ page_par(inbox_off(b)) : 0;
            rbase = ex + inbox_off(b) + xs * 4096;
            const uint32_t inv = (ep * (NT - 1)) & 1;
#pragma unroll
            for (int i = 0; i < 4; i++) stg128(rbase + (w == 2 ? 16384 : w * 2048) + i * 512 + lane * 16, inv, 0, 0, 0);
            __threadfence();
            bar_sync(15, 96);
            if (t2 == 0) stg_word(g_side + b, (ep + 1) * 2 + xs, true);
            TR1(4);
        } else {
            mbar_arrive_all3(bar + B_WIN, l16 >> 4);
            cnt_wait(g_cnt + C_X * 8, 64 * (EP + 1)); fence_async_global();
            TRG(0, 0);
            fetch_tile(0);
            TRG(0, 1);
        }
        cp_wait_all();
        bar_sync(6, 128);
        uint32_t poff;
        {
            const int rb = r * 32 + w * 8 + (lane >> 2);
            const uint32_t want = EP + 1;
            uint32_t v;
            for (int n = 0; __any_sync(~0u, ((v = ldg_word(g_side + rb)) >> 1) != want); n++) fault_if(n > POLL_LIMIT, n);
            __threadfence();
            poff = inbox_off(rb) + (v & 1) * 4096 + h * 64 + (lane & 3) * 16;
        }
        side = __shfl_sync(~0u, side, 0);
        const uint32_t roff = __shfl_sync(~0u, (uint32_t)(rbase - ex), 0) + (w == 2 ? 16384 : (w & 1) * 2048);
        uint4 a0[8];
#pragma unroll
        for (int kk = 0; kk < 8; kk++) a0[kk] = ldsm4t(WOAD + kk * 2048);
        if (w == 3) { cnt_wait(g_cnt + (C_X + 1) * 8, 64 * (EP + 1)); fence_async_global(); TRG(1, 0); }
#pragma unroll 1
        for (int t = 0;; t++) {
            TR_ON(t);
            OPQ();
            mbar_wait(bar + B_EP, t & 1);
            uint4 kx[3][2], vx[4][2];
            const uint32_t lp = LSWAP;
#pragma unroll
            for (int m = 0; m < 3; m++) {
                kx[m][0] = ldsm4(sb + O_KX + m * 2048 + L * 1024 + lp);
                kx[m][1] = ldsm4(sb + O_KX + m * 2048 + L * 1024 + 512 + lp);
            }
            mbar_wait(bar + B_VX, t & 1);
            if (w == 3) {
                mbar_wait(bar + B_XFREE, t & 1);
                bar_sync(8, 64);
                TR(6);
                if (t + 1 < NT) { fetch_tile(t + 1); TRG(t + 1, 1); }
                if (t > 0) store_o(t - 1);
                TR(7);
            }
            TR(0);
            bar_sync(4, 384);
            float s0[4] = {0, 0, 0, 0}, s1[4] = {0, 0, 0, 0}, sm[4] = {0, 0, 0, 0};
            {
                const uint4 q01 = ldsm4(sb + O_QM + L * 256 + l16 + (l16 & 256));
                const uint2 q2 = ldsm2(sb + O_QM + 1024 + L * 256 + l16);
                uint4 km_[3];
#pragma unroll
                for (int m = 0; m < 3; m++) km_[m] = ldsm4(sb + O_KM + m * 512 + (lp ^ (L << 8)));
                bar_arrive(5, 256);
                mma16(s0, kx[0][0].x, kx[0][0].y, kx[0][0].z, kx[0][0].w, q01.x, q01.y);
                mma16(s1, kx[0][1].x, kx[0][1].y, kx[0][1].z, kx[0][1].w, q01.x, q01.y);
                mma16(sm, km_[0].x, km_[0].y, km_[0].z, km_[0].w, q01.x, q01.y);
                mma16(s0, kx[1][0].x, kx[1][0].y, kx[1][0].z, kx[1][0].w, q01.z, q01.w);
                mma16(s1, kx[1][1].x, kx[1][1].y, kx[1][1].z, kx[1][1].w, q01.z, q01.w);
                mma16(sm, km_[1].x, km_[1].y, km_[1].z, km_[1].w, q01.z, q01.w);
                mma16(s0, kx[2][0].x, kx[2][0].y, kx[2][0].z, kx[2][0].w, q2.x, q2.y);
                mma16(s1, kx[2][1].x, kx[2][1].y, kx[2][1].z, kx[2][1].w, q2.x, q2.y);
                mma16(sm, km_[2].x, km_[2].y, km_[2].z, km_[2].w, q2.x, q2.y);
                const uint32_t ad = sb + O_SM + (1 - hf) * 1280 + L * 640 + rd;
                sta128(ad + l16, pk(s0[0], s0[1]), pk(s0[2], s0[3]), pk(s1[0], s1[1]), pk(s1[2], s1[3]), bar + B_SM + rd);
                sta32(ad + 512 + (l16 >> 2), pk(sm[0], sm[1]), bar + B_SM + rd);
            }
            TR(1);
            if (w == 3 && t > 0) hint_o(t - 1);
            if (t + 1 == NT) break;
#pragma unroll
            for (int m = 0; m < 8; m++) vx[m >> 1][m & 1] = lds128(sb + O_VX + (hf * 4 + (m >> 1)) * 2048 + L * 1024 + (m & 1) * 512 + l16);
            const uint32_t tag = (t + EP * (NT - 1) + 1) & 1;
            mbar_wait(bar + B_SM, t & 1);
            TR(2);
            {
                const uint32_t ad = sb + O_SM + L * 640;
                const uint4 u = lds128(ad + l16), v = lds128(ad + 1280 + l16);
                const uint32_t x = lds32(ad + 512 + (l16 >> 2)), y = lds32(ad + 1280 + 512 + (l16 >> 2));
                s0[0] += bf_lo(u.x) + bf_lo(v.x); s0[1] += bf_hi(u.x) + bf_hi(v.x); s0[2] += bf_lo(u.y) + bf_lo(v.y); s0[3] += bf_hi(u.y) + bf_hi(v.y);
                s1[0] += bf_lo(u.z) + bf_lo(v.z); s1[1] += bf_hi(u.z) + bf_hi(v.z); s1[2] += bf_lo(u.w) + bf_lo(v.w); s1[3] += bf_hi(u.w) + bf_hi(v.w);
                sm[0] += bf_lo(x) + bf_lo(y); sm[1] += bf_hi(x) + bf_hi(y);
            }
            uint2 vm[4];
#pragma unroll
            for (int m = 0; m < 4; m++) vm[m] = lds64(sb + O_VM + (hf * 4 + m) * 512 + l16 + L * 8);
            float mx0 = fmaxf(fmaxf(fmaxf(s0[0], s0[2]), fmaxf(s1[0], s1[2])), sm[0]);
            float mx1 = fmaxf(fmaxf(fmaxf(s0[1], s0[3]), fmaxf(s1[1], s1[3])), sm[1]);
#pragma unroll
            for (int o = 4; o < 32; o <<= 1) { mx0 = fmaxf(mx0, __shfl_xor_sync(~0u, mx0, o)); mx1 = fmaxf(mx1, __shfl_xor_sync(~0u, mx1, o)); }
            mx0 *= -SC; mx1 *= -SC;
            s0[0] = ex2(fmaf(s0[0], SC, mx0)); s0[1] = ex2(fmaf(s0[1], SC, mx1));
            s0[2] = ex2(fmaf(s0[2], SC, mx0)); s0[3] = ex2(fmaf(s0[3], SC, mx1));
            const uint32_t pb0 = movm(pk(s0[0], s0[1])), pb1 = movm(pk(s0[2], s0[3]));
            s1[0] = ex2(fmaf(s1[0], SC, mx0)); s1[1] = ex2(fmaf(s1[1], SC, mx1));
            s1[2] = ex2(fmaf(s1[2], SC, mx0)); s1[3] = ex2(fmaf(s1[3], SC, mx1));
            const uint32_t pb2 = movm(pk(s1[0], s1[1])), pb3 = movm(pk(s1[2], s1[3]));
            sm[0] = ex2(fmaf(sm[0], SC, mx0)); sm[1] = ex2(fmaf(sm[1], SC, mx1));
            const uint32_t pm = movm(pk(sm[0], sm[1]));
            float l0 = (s0[0] + s0[2]) + (s1[0] + s1[2]) + sm[0], l1 = (s0[1] + s0[3]) + (s1[1] + s1[3]) + sm[1];
            float o[4][4];
#pragma unroll
            for (int m = 0; m < 4; m++) { o[m][0] = o[m][1] = o[m][2] = o[m][3] = 0.f; mma16(o[m], vx[m][0].x, vx[m][0].y, vx[m][0].z, vx[m][0].w, pb0, pb1); }
            l0 += __shfl_xor_sync(~0u, l0, 4); l1 += __shfl_xor_sync(~0u, l1, 4);
#pragma unroll
            for (int m = 0; m < 4; m++) mma16(o[m], vx[m][1].x, vx[m][1].y, vx[m][1].z, vx[m][1].w, pb2, pb3);
            l0 += __shfl_xor_sync(~0u, l0, 8); l1 += __shfl_xor_sync(~0u, l1, 8);
#pragma unroll
            for (int m = 0; m < 4; m++) mma8(o[m], vm[m].x, vm[m].y, pm);
            l0 += __shfl_xor_sync(~0u, l0, 16); l1 += __shfl_xor_sync(~0u, l1, 16);
            l0 = rcp(l0); l1 = rcp(l1);
#pragma unroll
            for (int m = 0; m < 4; m += 2)
                stsm4t(sb + O_OX + (hf * 4 + m) * 512 + (L ^ ((h >> 2) & 1)) * 256   + ((l16 & 0x100) << 1) + (l16 & 0xf0),
                       pk(o[m][0] * l0, o[m][1] * l1), pk(o[m][2] * l0, o[m][3] * l1), pk(o[m + 1][0] * l0, o[m + 1][1] * l1), pk(o[m + 1][2] * l0, o[m + 1][3] * l1));
            TR(3);
            char* const pdst = ex + poff;
            bar_sync(6, 128);
            {
                uint4 bo[8], a1[8];
                const uint32_t wad = WOAD;
#pragma unroll
                for (int kk = 0; kk < 8; kk++) bo[kk] = ldsm4(sb + O_OX + kk * 512 + l16);
#pragma unroll
                for (int G = 0; G < 3; G++) {
                    float e[4][4];
#pragma unroll
                    for (int q = 0; q < 4; q++) e[q][0] = e[q][1] = e[q][2] = e[q][3] = 0.f;
#pragma unroll
                    for (int kk = 0; kk < 8; kk++) {
                        const uint4 f = G == 0 ? a0[kk] : a1[kk];
                        mma16(e[(kk & 1) * 2], f.x, f.y, f.z, f.w, bo[kk].x, bo[kk].y);
                        mma16(e[(kk & 1) * 2 + 1], f.x, f.y, f.z, f.w, bo[kk].z, bo[kk].w);
                        if (G == 1) a1[kk] = ldsm4t(wad + 32768 + kk * 2048);
                        if (G == 0 && kk == FK) {
                            sched_fence(rzero, 2);
#pragma unroll
                            for (int j = 0; j < 8; j++) a1[j] = ldsm4t(wad + 16384 + j * 2048);
                        }
                    }
                    stg_pkt(pdst + (G == 2 ? 16384 : G * 2048), (pk(e[0][0] + e[2][0], e[0][1] + e[2][1]) & ~1u) | tag, pk(e[0][2] + e[2][2], e[0][3] + e[2][3]),
                            pk(e[1][0] + e[3][0], e[1][1] + e[3][1]), pk(e[1][2] + e[3][2], e[1][3] + e[3][3]));
                    if (G == 0) { TR(9); TRD(t, 0); }
                    if (G < 2) sched_fence(rzero, 3 + G);
                }
            }
            TR(4);
            if (w < 3) {
                bar_arrive(7, 384);
                OPQ();
                const uint32_t tagm = tag;
                uint32_t m0v = 0;
                if (t + 1 <= LAG) {
                    const unsigned short* m = reinterpret_cast<const unsigned short*>(mem0) + ((l16 >> 3) & 6) * DM + 192 * w + 16 * (b >> 3) + (b & 7) + ((l16 >> 4) & 8);
                    m0v = m[0] | (m[DM] << 16);
                }
                const char* const rsrc = ex + roff + l16;
                uint4 v[4];
                delay(DLY1);
#pragma unroll
                for (int i = 0; i < 4; i++) v[i] = ldg_pkt(rsrc + i * 512);
                for (int n = 0; __any_sync(~0u, lop_bad(lop_bad(0, v[0].x, v[1].x, tagm), v[2].x, v[3].x, tagm) & 1); n++) {
#pragma unroll
                    for (int i = 0; i < 4; i++) v[i] = ldg_pkt(rsrc + i * 512);
                    fault_if(n > POLL_LIMIT, n);
                }
                TR(5); TRD(t, 1);
                float s[8];
                s[4] = (bf_lo(v[0].z) + bf_lo(v[1].z)) + (bf_lo(v[2].z) + bf_lo(v[3].z)); s[5] = (bf_hi(v[0].z) + bf_hi(v[1].z)) + (bf_hi(v[2].z) + bf_hi(v[3].z));
                s[6] = (bf_lo(v[0].w) + bf_lo(v[1].w)) + (bf_lo(v[2].w) + bf_lo(v[3].w)); s[7] = (bf_hi(v[0].w) + bf_hi(v[1].w)) + (bf_hi(v[2].w) + bf_hi(v[3].w));
                s[2] = (bf_lo(v[0].y) + bf_lo(v[1].y)) + (bf_lo(v[2].y) + bf_lo(v[3].y)); s[3] = (bf_hi(v[0].y) + bf_hi(v[1].y)) + (bf_hi(v[2].y) + bf_hi(v[3].y));
                s[0] = (bf_lo(v[0].x) + bf_lo(v[1].x)) + (bf_lo(v[2].x) + bf_lo(v[3].x)); s[1] = (bf_hi(v[0].x) + bf_hi(v[1].x)) + (bf_hi(v[2].x) + bf_hi(v[3].x));
#pragma unroll
                for (int j = 0; j < 4; j++) s[j] += __shfl_xor_sync(~0u, s[j + 4], 16);
#pragma unroll
                for (int j = 0; j < 2; j++) s[j] += __shfl_xor_sync(~0u, s[j + 2], 8);
#pragma unroll
                for (int j = 0; j < 2; j++) s[j] += __shfl_xor_sync(~0u, s[j], 4);
                char* const mem_w = ex + mem_off(w, 0);
                uint32_t res = t + 1 <= LAG && l16 >= 256 ? m0v : pk(s[0], s[1]);
                if ((l16 & 48) == 0) res = (res & ~1u) | tag;
                stg_word(mem_w + (mem_off(0, b >> 3) - mem_off(0, 0)) + (b & 7) * 16 + (((l16 & 64) << 6) + ((l16 & 128) << 1) + ((l16 & 256) >> 1) + ((l16 >> 2) & 12)), res, true);
                TR(6); TRD(t, 2);
                delay(DLY2);
                const char* src = mem_w + (side ^ page_par(0x180000)) * 4096 + l16;
                const uint32_t gdst = sb + O_MB + w * 6144 + l16;
                uint4 x[12];
#pragma unroll
                for (int i = 0; i < 12; i++) x[i] = ldg_pkt(src + (mem_off(0, i) - mem_off(0, 0)));
                for (int n = 0;; n++) {
                    uint32_t bad = 0;
#pragma unroll
                    for (int i = 0; i < 12; i += 2) bad = lop_bad(bad, x[i].x, x[i + 1].x, tagm);
                    if (!__any_sync(~0u, bad & 1)) break;
#pragma unroll
                    for (int i = 0; i < 12; i++) ldg_pkt_retry(x[i], src + (mem_off(0, i) - mem_off(0, 0)), tagm);
                    fault_if(n > POLL_LIMIT, n);
                }
#pragma unroll
                for (int i = 0; i < 12; i++) sts128(gdst + i * 512, x[i].x, x[i].y, x[i].z, x[i].w);
                TR(7); TRD(t, 3);
                fence_async_smem();
                bar_arrive(12 + w, 160);
                bar_arrive(1 + w, 160);
                if (w == XST) bar_arrive(8, 64);
                TR(8);
            } else {
                bar_sync(7, 384);
                fence_async_smem();
                arm();
                __syncwarp();
                mbar_arrive_all3(bar + B_WIN, l16 >> 4);
                if (t + 2 < NT) { cnt_wait(g_cnt + (C_X + t + 2) * 8, 64 * (EP + 1)); fence_async_global(); TRG(t + 2, 0); }
                TR(5);
            }
        }
        if (w == 3) { bar_sync(7, 160); fence_async_smem(); store_o(NT - 1); hint_o(NT - 1); }
        cluster_sync();
    }
    TR_DUMP(b);
}

#define VG 12
namespace ka {
constexpr int O_WA = 196608;
constexpr int A_KB = 21504;
constexpr int O_RING = 194560;
constexpr int O_BAR = 230400;
constexpr int SMEM = O_BAR + 256 + 1024;
constexpr float SC = 0.23570226039551584f * 1.4426950408889634f;
}

template <int NP>
DEVI void row_task(const uint4* res, const uint4* part, uint4* xout, char* img, int pos, int lane, uint32_t tag) {
    const bool on = lane < 24;
    const int ln = on ? lane : 0;
    uint4 rv[3], pv[NP > 0 ? NP * 3 : 1];
#pragma unroll
    for (int i = 0; i < 3; i++) rv[i] = ldg128(res + i * 24 + ln);
#pragma unroll
    for (int i = 0; i < NP * 3; i++) pv[i] = ldg_pkt(part + i * 24 + ln);
    if (NP > 0) validate<NP * 3>(pv, part + ln, 384, tag);
#pragma unroll
    for (int q = 0; q < NP * 3 / 2; q++) {
        const uint4 y = pv[q + NP * 3 / 2];
        pv[q] = make_uint4(add2(pv[q].x, y.x), add2(pv[q].y, y.y), add2(pv[q].z, y.z), add2(pv[q].w, y.w));
    }
    float x[24];
#pragma unroll
    for (int i = 0; i < 3; i++) {
        x[8 * i] = bf_lo(rv[i].x); x[8 * i + 1] = bf_hi(rv[i].x); x[8 * i + 2] = bf_lo(rv[i].y); x[8 * i + 3] = bf_hi(rv[i].y);
        x[8 * i + 4] = bf_lo(rv[i].z); x[8 * i + 5] = bf_hi(rv[i].z); x[8 * i + 6] = bf_lo(rv[i].w); x[8 * i + 7] = bf_hi(rv[i].w);
    }
    if (NP > 0) {
#pragma unroll
        for (int q = 0; q < NP * 3 / 2; q++) {
            const int i = q % 3;
            x[8 * i] += bf_lo(pv[q].x); x[8 * i + 1] += bf_hi(pv[q].x); x[8 * i + 2] += bf_lo(pv[q].y); x[8 * i + 3] += bf_hi(pv[q].y);
            x[8 * i + 4] += bf_lo(pv[q].z); x[8 * i + 5] += bf_hi(pv[q].z); x[8 * i + 6] += bf_lo(pv[q].w); x[8 * i + 7] += bf_hi(pv[q].w);
        }
#pragma unroll
        for (int i = 0; i < 3; i++) {
            uint32_t w[4];
#pragma unroll
            for (int j = 0; j < 4; j++) { w[j] = pk(x[8 * i + 2 * j], x[8 * i + 2 * j + 1]); x[8 * i + 2 * j] = bf_lo(w[j]); x[8 * i + 2 * j + 1] = bf_hi(w[j]); }
            stg128p(xout + i * 24 + ln, w[0], w[1], w[2], w[3], on);
        }
    }
    if (img) {
        float s = 0.f;
#pragma unroll
        for (int j = 0; j < 24; j++) s += x[j];
        if (!on) s = 0.f;
#pragma unroll
        for (int o = 1; o < 32; o <<= 1) s += __shfl_xor_sync(~0u, s, o);
        const float mean = s * (1.f / DM);
        float v = 0.f;
#pragma unroll
        for (int j = 0; j < 24; j++) { x[j] -= mean; v = fmaf(x[j], x[j], v); }
        if (!on) v = 0.f;
#pragma unroll
        for (int o = 1; o < 32; o <<= 1) v += __shfl_xor_sync(~0u, v, o);
        const float rs = rsqrtf(v * (1.f / DM) + 1e-5f);
        char* dst = img + (ln >> 3) * 4096 + pos * 128 + (((ln ^ pos) & 7) << 4);
#pragma unroll
        for (int i = 0; i < 3; i++)
            stg128p(dst + i * 12288, pk(x[8 * i] * rs, x[8 * i + 1] * rs), pk(x[8 * i + 2] * rs, x[8 * i + 3] * rs),
                    pk(x[8 * i + 4] * rs, x[8 * i + 5] * rs), pk(x[8 * i + 6] * rs, x[8 * i + 7] * rs), on);
    }
}

DEVI void rows_a(const uint4* xin, int f, int i, int lane, uint32_t ep, int warp) {
    for (int u = 0; u < LAG; u++) cnt_hint(g_cnt + (C_X + u + (f ? 0 : NSEG)) * 8, lane);
#pragma unroll 1
    for (int seg = 0; seg < NSEG; seg++) {
        const int j = seg + f * LAGA, u = seg + f * LAG, row = seg * 32 + i;
        cnt_wait(g_cnt + (C_WA + j * 4 + f * 2 + (i & 1)) * 8, 24 * (ep + 1));
        TRG(u, 0);
        row_task<4>((f ? g_x + 2048 * 72 : xin) + row * 72, g_pa + ((j & (RING - 1)) * 64 + f * 32 + i) * 288,
                    g_x + (f * 4096 + row) * 72, reinterpret_cast<char*>(g_xt + u * 4608 + f * 2304), i, lane, ring_tag<NTA>(j, ep));
        TRG(u, 1);
        cnt_add(g_cnt + (C_X + u) * 8, lane);
        TRG(u, 2);
    }
}

__global__ void __launch_bounds__(384, 1)
k_aux(const __nv_bfloat16* __restrict__ x0, const __nv_bfloat16* __restrict__ wqkv, const __nv_bfloat16* __restrict__ wo,
      const __nv_bfloat16* __restrict__ Wo, __nv_bfloat16* __restrict__ out) {
    using namespace ka;
    extern __shared__ unsigned char smem_raw[];
    const uint32_t sb = (smem_u32(smem_raw) + 1023) & ~1023u;
    const int tid = threadIdx.x, lane = tid & 31, warp = __shfl_sync(~0u, tid >> 5, 0), g = lane >> 2, c = lane & 3;
    const int b = blockIdx.x;
    const uint32_t bar = sb + O_BAR;
    const uint32_t ep = __shfl_sync(~0u, ldg32(&g_epoch), 0);

    TRG(79, 0);
    const uint4* xin = reinterpret_cast<const uint4*>(x0);
    if (warp >= 8 || b == 35) {
        asm volatile("setmaxnreg.dec.sync.aligned.u32 128;");
        const int rw = b < 24 ? (warp - 8) * 24 + b : b < 35 ? (warp - 8) * 11 + b - 24 : 96 + 2 * warp;
        if (b < 24 || b == 35) {
#pragma unroll 1
            for (int row = rw; row < 2048; row += (row & 1) ? 23 : 1) {
                if (lane == 0 && b == 35 && row < 2024) prefetch_l2(xin + (row + 24) * 72, 1152);
                row_task<0>(xin + row * 72, nullptr, nullptr, reinterpret_cast<char*>(g_xa + (row >> 5) * 4608), (row & 1) * 16 + ((row & 31) >> 1), lane, 0);
                if (b < 24) { cnt_add(g_cnt + (C_N0 + (row >> 5)) * 8, lane); break; }
                if (row & 1) cnt_add<2>(g_cnt + (C_N0 + (row >> 5)) * 8, lane);
            }
        }
        if (rw < 32) {
            const int f = b < 24, i = rw;
#pragma unroll 1
            for (int seg = 0; seg < NSEG; seg++) {
                const int u = seg + f * LAG, row = seg * 32 + i;
                cnt_wait(g_cnt + (C_WB + u * 4 + f * 2 + (i >> 4)) * 8, 24 * (ep + 1));
                TRG(u, 0);
                row_task<8>(g_x + (f * 4096 + row) * 72, g_pb + ((u & (RING - 1)) * 64 + f * 32 + i) * 576,
                            f ? reinterpret_cast<uint4*>(out) + row * 72 : g_x + (2048 + row) * 72,
                            f ? nullptr : reinterpret_cast<char*>(g_xa + (seg + LAGA) * 4608 + 2304), (i & 1) * 16 + (i >> 1), lane, ring_tag(u, ep));
                TRG(u, 1);
                cnt_add(g_cnt + (C_RB + f * NSEG + seg) * 8, lane);
                TRG(u, 2);
            }
            if (f && rw == 31) {
                asm volatile("griddepcontrol.wait;" ::: "memory");
                if (lane == 0) g_epoch = ep + 1;
            }
        } else if (rw < 64 && b < 24) rows_a(xin, 0, rw - 32, lane, ep, warp);
        return;
    }

    if (b < 24) {
        if (warp >= 4) {
            const int kq = b / 6, nq = b % 6;
            uint4 v[17];
#pragma unroll
            for (int q = 0; q < 17; q++) {
                const int it = q * 4 + warp - 4, kr = (it / 3) * 8 + g, s = kq * 11 + (kr >> 4), a = s >> 2, j = s & 3, e = kr & 15;
                const int head = 3 * a + (j < 3 ? j : e >> 1), row = head * 18 + (j < 3 ? e : 16 + (e & 1));
                v[q] = make_uint4(0, 0, 0, 0);
                if (it < 66 && head < 32 && (j < 3 || e < 6)) v[q] = *reinterpret_cast<const uint4*>(wo + row * DM + nq * 96 + (it % 3) * 32 + c * 8);
            }
#pragma unroll
            for (int q = 0; q < 17; q++) {
                const int it = q * 4 + warp - 4;
                const uint32_t ad = sb + O_WA + (it % 3) * 4 * 2816 + (it / 3) * 128 + lane * 4;
                if (it < 66) { sts32(ad, v[q].x); sts32(ad + 2816, v[q].y); sts32(ad + 2 * 2816, v[q].z); sts32(ad + 3 * 2816, v[q].w); }
            }
        } else {
            const int kg = b / 3, ng = b % 3;
            delay(DLYB);
#pragma unroll 1
            for (int bt = 0; bt < 4; bt++) {
                uint4 v[24];
#pragma unroll
                for (int q = 0; q < 24; q++)
                    v[q] = *reinterpret_cast<const uint4*>(Wo + (size_t)(kg * 512 + (bt * 4 + q / 6) * 32 + warp * 8 + g) * DM + ng * 192 + (q % 6) * 32 + c * 8);
#pragma unroll
                for (int q = 0; q < 24; q++) {
                    const uint32_t ad = sb + (q % 6) * 4 * 8192 + ((bt * 4 + q / 6) * 4 + warp) * 128 + lane * 4;
                    sts32(ad, v[q].x); sts32(ad + 8192, v[q].y); sts32(ad + 2 * 8192, v[q].z); sts32(ad + 3 * 8192, v[q].w);
                }
            }
        }
        fence_async_smem();
        bar_sync(2 + (warp >> 2), 128);
    } else {
        for (int i = tid; i < 2048; i += 256) sts128(sb + O_RING + i * 16, 0, 0, 0, 0);
        if (tid < 17) mbar_init(bar + tid * 8, tid >= 4 && tid < 8 ? 4 : 1);
        fence_async_smem();
        bar_sync(1, 256);
    }
    TRG(79, 1);
    const int wq = warp & 3;

    if (warp < 4) {
        asm volatile("setmaxnreg.inc.sync.aligned.u32 256;");
        if (b < 24) {
            const int kg = b / 3, ng = b % 3;
            const uint32_t blo = ((sb >> 4) & 0x3fff) | (8u << 16);
            uint4 a[32];
            bool pre = false;
#pragma unroll 1
            for (int u = 0; u < NT; u++) {
                const uint32_t tag = ring_tag(u, ep);
                const uint4* src = g_o + (((u & (RING - 1)) * 4 + wq) * 256 + kg * 32) * 32 + lane;
                if (!pre) {
                    cnt_wait(g_cnt + (C_O + u * 8 + kg) * 8, 12 * (ep + 1));
#pragma unroll
                    for (int i = 0; i < VG; i++) a[i] = ldg_pkt(src + i * 32);
                }
                TRG(u, 0);
                float d[96];
                validate<VG>(a, src, 512, tag);
#pragma unroll
                for (int i = VG; i < 32; i++) a[i] = ldg_pkt(src + i * 32);
                wg_fence();
#pragma unroll
                for (int i = 0; i < 32; i++) {
                    if (i == VG) { validate<32 - VG>(a + VG, src + VG * 32, 512, tag); wg_fence(); }
                    wgmma_rs192t(d, a[i].x, a[i].y, a[i].z, a[i].w, mkdesc(blo + i * 16, 512), i > 0);
                    if (i == 23 || i == 31) wg_commit();
                }
                wg_wait<1>();
                pre = u + 1 < NT && __all_sync(~0u, ldg_word(g_cnt + (C_O + (u + 1) * 8 + kg) * 8) >= 12 * (ep + 1));
                if (pre) {
                    const uint4* nx = g_o + ((((u + 1) & (RING - 1)) * 4 + wq) * 256 + kg * 32) * 32 + lane;
#pragma unroll
                    for (int i = 0; i < VG; i++) a[i] = ldg_pkt(nx + i * 32);
                }
                wg_wait<0>();
                TRG(u, 1);
                uint4* dst = g_pb + (((u & (RING - 1)) * 64 + wq * 16 + g) * 8 + kg) * 72 + ng * 24 + c;
#pragma unroll
                for (int m = 0; m < 6; m++) {
                    stg128(dst + 4 * m, (pk(d[16 * m], d[16 * m + 1]) & ~1u) | tag, pk(d[16 * m + 4], d[16 * m + 5]), pk(d[16 * m + 8], d[16 * m + 9]), pk(d[16 * m + 12], d[16 * m + 13]));
                    stg128(dst + 4 * m + 8 * 576, (pk(d[16 * m + 2], d[16 * m + 3]) & ~1u) | tag, pk(d[16 * m + 6], d[16 * m + 7]), pk(d[16 * m + 10], d[16 * m + 11]), pk(d[16 * m + 14], d[16 * m + 15]));
                }
                cnt_hint(g_cnt + (C_WB + u * 4 + wq) * 8, lane);
                TRG(u, 3);
            }
        } else {
            const int a = b - 24, f = wq >> 1;
            const uint32_t blo = ((sb >> 4) & 0x3fff) | (8u << 16), alo = (((sb + O_RING) >> 4) & 0x3fff) | (1u << 16);
            const bool m0 = 2 * c <= g, m1 = 2 * c + 1 <= g;
            const uint32_t M = (m0 ? 0xffffu : 0u) | (m1 ? 0xffff0000u : 0u);
            uint32_t kh[7], vh[7];
#pragma unroll
            for (int i = 0; i < 7; i++) kh[i] = vh[i] = 0;
            int it = 0;
#pragma unroll 1
            for (int u = 0; u < NTA; u++) {
                float d[84];
#pragma unroll 1
                for (int kb = 0; kb < 9; kb++, it++) {
                    mbar_wait(bar + (it & 3) * 8, (it >> 2) & 1);
                    if (u == 0) mbar_wait(bar + 64 + kb * 8, 0);
                    if (kb == 0) TRG(u, 0);
                    wg_fence();
#pragma unroll
                    for (int q = 0; q < 4; q++)
                        wgmma_ss168t(d, mkdesc(alo + (it & 3) * 512 + q * 2, km::DESC_HI), mkdesc(blo + kb * (A_KB >> 4) + q * 16, 64), kb + q > 0);
                    wg_commit();
                    wg_wait<1>();
                    mbar_arrive(bar + 32 + ((it - 1) & 3) * 8, lane == 0 && kb > 0);
                }
                wg_wait<0>();
                mbar_arrive(bar + 32 + ((it - 1) & 3) * 8, lane == 0);
                TRG(u, 1);
                const bool first = u == f * LAGA;
                const uint32_t tag = ring_tag<NTA>(u, ep);
                const uint32_t qt0 = pk(d[72], d[73]), qt1 = pk(d[74], d[75]), kt0 = pk(d[76], d[77]), kt1 = pk(d[78], d[79]);
                const uint32_t vt0 = movm(pk(d[80], d[81])), vt1 = movm(pk(d[82], d[83]));
                float ot[4] = {0, 0, 0, 0};
                uint4* dst = g_oa + (((u & (RING - 1)) * 4 + wq) * 44 + a * 4) * 32 + lane;
#pragma unroll
                for (int h = 0; h < 3; h++) {
                    const float* q = d + 8 * h; const float* k = d + 24 + 8 * h; const float* v = d + 48 + 8 * h;
                    const uint32_t q0 = pk(q[0], q[1]), q1 = pk(q[2], q[3]), q2 = pk(q[4], q[5]), q3 = pk(q[6], q[7]);
                    const uint32_t k0 = pk(k[0], k[1]), k1 = pk(k[4], k[5]), k2 = pk(k[2], k[3]), k3 = pk(k[6], k[7]);
                    const uint32_t v0 = movm(pk(v[0], v[1])), v1 = movm(pk(v[2], v[3])), v2 = movm(pk(v[4], v[5])), v3 = movm(pk(v[6], v[7]));
                    const uint32_t t0 = c == h ? qt0 : 0, t1 = c == h ? qt1 : 0;
                    float sp[4] = {0, 0, 0, 0}, sl[4] = {0, 0, 0, 0}, sh[4] = {0, 0, 0, 0};
                    mma16(sp, q0, q1, q2, q3, kh[2 * h], kh[2 * h + 1]); mma16(sl, q0, q1, q2, q3, k0, k1); mma16(sh, q0, q1, q2, q3, k2, k3);
                    mma8(sp, t0, t1, kh[6]); mma8(sl, t0, t1, kt0); mma8(sh, t0, t1, kt1);
                    float x0_ = m0 ? sl[0] : first ? -INFINITY : sp[0], x1_ = m1 ? sl[1] : first ? -INFINITY : sp[1];
                    float y0_ = m0 ? sh[2] : sl[2], y1_ = m1 ? sh[3] : sl[3];
                    float mx = fmaxf(x0_, x1_), my = fmaxf(y0_, y1_);
#pragma unroll
                    for (int o = 1; o < 4; o <<= 1) { mx = fmaxf(mx, __shfl_xor_sync(~0u, mx, o)); my = fmaxf(my, __shfl_xor_sync(~0u, my, o)); }
                    mx *= -SC; my *= -SC;
                    x0_ = ex2(fmaf(x0_, SC, mx)); x1_ = ex2(fmaf(x1_, SC, mx)); y0_ = ex2(fmaf(y0_, SC, my)); y1_ = ex2(fmaf(y1_, SC, my));
                    float lx = x0_ + x1_, ly = y0_ + y1_;
#pragma unroll
                    for (int o = 1; o < 4; o <<= 1) { lx += __shfl_xor_sync(~0u, lx, o); ly += __shfl_xor_sync(~0u, ly, o); }
                    lx = rcp(lx); ly = rcp(ly);
                    const uint32_t px = pk(x0_ * lx, x1_ * lx), py = pk(y0_ * ly, y1_ * ly);
                    const uint32_t hm = (g >> 1) == h ? ~0u : 0u;
                    float o0[4] = {0, 0, 0, 0}, o1[4] = {0, 0, 0, 0};
                    mma16(o0, px & M, py & ~M, 0, py & M, v0, v1); mma16(o1, px & M, py & ~M, 0, py & M, v2, v3);
                    mma16(ot, px & M, py & ~M, 0, py & M, vt0 & hm, vt1 & hm);
                    mma8(o0, px & ~M, 0, vh[2 * h]); mma8(o1, px & ~M, 0, vh[2 * h + 1]); mma8(ot, px & ~M, 0, vh[6] & hm);
                    stg128(dst + h * 32, (pk(o0[0], o0[1]) & ~1u) | tag, pk(o0[2], o0[3]), pk(o1[0], o1[1]), pk(o1[2], o1[3]));
                    kh[2 * h] = k2; kh[2 * h + 1] = k3; vh[2 * h] = v1; vh[2 * h + 1] = v3;
                }
                kh[6] = kt1; vh[6] = vt1;
                stg128(dst + 96, (pk(ot[0], ot[1]) & ~1u) | tag, pk(ot[2], ot[3]), 0, 0);
                cnt_hint(g_cnt + (C_A + u * 4 + wq) * 8, lane);
                TRG(u, 2);
            }
        }
    } else {
        asm volatile("setmaxnreg.dec.sync.aligned.u32 120;");
        if (b < 24) {
            const int kq = b / 6, nq = b % 6;
            const uint32_t blo = (((sb + O_WA) >> 4) & 0x3fff) | (8u << 16);
#pragma unroll 1
            for (int u = 0; u < NTA; u++) {
                cnt_wait(g_cnt + (C_A + u * 4 + wq) * 8, 11 * (ep + 1));
                const uint32_t tag = ring_tag<NTA>(u, ep);
                TRG(u, 0);
                const uint4* src = g_oa + (((u & (RING - 1)) * 4 + wq) * 44 + kq * 11) * 32 + lane;
                uint4 a[11];
                float d[48];
#pragma unroll
                for (int i = 0; i < 11; i++) a[i] = ldg_pkt(src + i * 32);
                validate<11>(a, src, 512, tag);
                wg_fence();
#pragma unroll
                for (int i = 0; i < 11; i++) wgmma_rs96t(d, a[i].x, a[i].y, a[i].z, a[i].w, mkdesc(blo + i * 16, 176), i > 0);
                wg_commit();
                wg_wait<0>();
                TRG(u, 1);
                uint4* dst = g_pa + (((u & (RING - 1)) * 64 + (wq >> 1) * 32 + 2 * g + (wq & 1)) * 4 + kq) * 72 + nq * 12 + c;
#pragma unroll
                for (int m = 0; m < 3; m++) {
                    stg128(dst + 4 * m, (pk(d[16 * m], d[16 * m + 1]) & ~1u) | tag, pk(d[16 * m + 4], d[16 * m + 5]), pk(d[16 * m + 8], d[16 * m + 9]), pk(d[16 * m + 12], d[16 * m + 13]));
                    stg128(dst + 4 * m + 16 * 288, (pk(d[16 * m + 2], d[16 * m + 3]) & ~1u) | tag, pk(d[16 * m + 6], d[16 * m + 7]), pk(d[16 * m + 10], d[16 * m + 11]), pk(d[16 * m + 14], d[16 * m + 15]));
                }
                cnt_hint(g_cnt + (C_WA + u * 4 + wq) * 8, lane);
                TRG(u, 3);
            }
        } else if (warp == 4) {
            mbar_expect(bar + 64 + lane * 8, A_KB, lane < 9);
            int it = 0;
#pragma unroll 1
            for (int u = 0; u < NTA; u++) {
                if (u == 0) { cnt_wait(g_cnt + C_W * 8, 96 * (ep + 1)); TRG(78, 0); }
                if (u < NSEG) cnt_wait(g_cnt + (C_N0 + u) * 8, 32 * (ep + 1));
                if (u > LAGA + LAG) cnt_wait(g_cnt + (C_RB + NSEG + u - LAGA - LAG - 1) * 8, 32 * (ep + 1));
                if (u >= LAGA) cnt_wait(g_cnt + (C_RB + u - LAGA) * 8, 32 * (ep + 1));
                TRG(u, 0);
                asm volatile("fence.proxy.async.global;" ::: "memory");
                const bool on = lane == 0 ? u < NSEG : lane == 1 && u >= LAGA;
#pragma unroll 1
                for (int kb = 0; kb < 9; kb++, it++) {
                    if (it >= 4) mbar_wait(bar + 32 + (it & 3) * 8, ((it >> 2) - 1) & 1);
                    mbar_expect(bar + (it & 3) * 8, u < NSEG && u >= LAGA ? 8192 : 4096, lane == 0);
                    asm volatile("{.reg .pred p; setp.ne.u32 p, %3, 0; @p cp.async.bulk.shared::cluster.global.mbarrier::complete_tx::bytes [%0], [%1], 4096, [%2];}"
                        :: "r"(sb + O_RING + (it & 3) * 8192 + (lane & 1) * 4096), "l"(g_xa + u * 4608 + (lane & 1) * 2304 + kb * 256), "r"(bar + (it & 3) * 8), "r"((uint32_t)on) : "memory");
                    if (u == 0) asm volatile("{.reg .pred p; setp.ne.u32 p, %4, 0; @p cp.async.bulk.shared::cluster.global.mbarrier::complete_tx::bytes [%0], [%1], %3, [%2];}"
                        :: "r"(sb + lane * A_KB), "l"(g_wa + ((b - 24) * 9 + lane) * (A_KB / 16)), "r"(bar + 64 + lane * 8), "n"(A_KB),
                           "r"((uint32_t)(lane < 9 && kb == (lane < 4 ? lane : lane < 6 ? 3 : lane - 2))) : "memory");
                }
            }
        } else if ((warp - 5) * 11 + b - 24 < 32) rows_a(xin, 1, (warp - 5) * 11 + b - 24, lane, ep, warp);
    }
}

extern "C" void kernel_launch(void* const* d_in, const int* in_sizes, int n_in, void* d_out, int out_size) {
    const __nv_bfloat16* x = (const __nv_bfloat16*)d_in[0];
    const __nv_bfloat16* wqkv = (const __nv_bfloat16*)d_in[1];
    const __nv_bfloat16* wo = (const __nv_bfloat16*)d_in[2];
    const __nv_bfloat16* mem0 = (const __nv_bfloat16*)d_in[4];
    const __nv_bfloat16* Wq = (const __nv_bfloat16*)d_in[5];
    const __nv_bfloat16* Wk = (const __nv_bfloat16*)d_in[6];
    const __nv_bfloat16* Wv = (const __nv_bfloat16*)d_in[7];
    const __nv_bfloat16* Wo = (const __nv_bfloat16*)d_in[8];
    cudaFuncSetAttribute(k_main, cudaFuncAttributeMaxDynamicSharedMemorySize, km::SMEM);
    cudaFuncSetAttribute(k_aux, cudaFuncAttributeMaxDynamicSharedMemorySize, ka::SMEM);
    cudaStream_t s = cudaStreamPerThread;
    k_main<<<96, 384, km::SMEM, s>>>(x, wqkv, wo, mem0, Wq, Wk, Wv, Wo);
    cudaLaunchConfig_t cfg = {};
    cudaLaunchAttribute at[1];
    at[0].id = cudaLaunchAttributeProgrammaticStreamSerialization;
    at[0].val.programmaticStreamSerializationAllowed = 1;
    cfg.stream = s; cfg.attrs = at; cfg.numAttrs = 1;
    cfg.gridDim = dim3(36); cfg.blockDim = dim3(384); cfg.dynamicSmemBytes = ka::SMEM;
    cudaLaunchKernelEx(&cfg, k_aux, x, wqkv, wo, Wo, (__nv_bfloat16*)d_out);
}
```

```cpp
#include <cuda_runtime.h>
#include <cuda_bf16.h>
#include <stdint.h>

#define LAG 7
constexpr int NSEG = 64;
constexpr int NT = NSEG + LAG;
#define AHEAD 1
constexpr int LAGA = LAG + AHEAD;
constexpr int NTA = NSEG + LAGA;
#define RING_ 8
constexpr int RING = RING_;
constexpr int DM = 576;

__device__ __align__(1024) uint4 g_xt[NT * 2 * 9 * 256];
__device__ __align__(1024) uint4 g_o[RING * 4 * 256 * 32];
__device__ __align__(1024) uint4 g_ex[2 * 131072];
__device__ unsigned g_side[96];
__device__ __align__(1024) uint4 g_pb[RING * 64 * 8 * 72];
__device__ __align__(1024) uint4 g_pa[RING * 64 * 4 * 72];
__device__ __align__(1024) uint4 g_oa[RING * 4 * 44 * 32];
__device__ __align__(1024) uint4 g_xa[NTA * 2 * 9 * 256];
__device__ __align__(1024) uint4 g_wa[11 * 9 * 21 * 64];
__device__ __align__(1024) uint4 g_x[3 * 2048 * 72];

constexpr int C_X = 0;
constexpr int C_O = C_X + NT;
constexpr int C_WB = C_O + NT * 8;
constexpr int C_RB = C_WB + NT * 4;
constexpr int C_A = C_RB + 2 * NSEG;
constexpr int C_WA = C_A + NTA * 4;
constexpr int C_N0 = C_WA + NTA * 4;
constexpr int C_W = C_N0 + NSEG;
constexpr int C_DONE = C_W + 1;
constexpr int C_TOTAL = C_DONE + 1;
__device__ __align__(1024) unsigned g_cnt[C_TOTAL * 8];
__device__ unsigned g_epoch;

#define TR(i)
#define TR1(i)
#define TR_ON(t)
#define TR_INIT(base)
#define TR_DUMP(slot)
#define TRG(t, i)
constexpr int TR_BYTES = 0;

#define DEVI __device__ __forceinline__
DEVI uint32_t smem_u32(const void* p) { return (uint32_t)__cvta_generic_to_shared(p); }
DEVI uint32_t pk(float lo, float hi) { uint32_t r; asm("cvt.rn.bf16x2.f32 %0, %1, %2;" : "=r"(r) : "f"(hi), "f"(lo)); return r; }
DEVI float bf_lo(uint32_t u) { return __uint_as_float(u << 16); }
DEVI float bf_hi(uint32_t u) { return __uint_as_float(u & 0xffff0000u); }
DEVI uint32_t add2(uint32_t a, uint32_t b) { uint32_t d; asm("add.rn.bf16x2 %0, %1, %2;" : "=r"(d) : "r"(a), "r"(b)); return d; }
DEVI uint32_t movm(uint32_t a) { uint32_t d; asm volatile("movmatrix.sync.aligned.m8n8.trans.b16 %0, %1;" : "=r"(d) : "r"(a)); return d; }
DEVI float ex2(float x) { float y; asm("ex2.approx.ftz.f32 %0, %1;" : "=f"(y) : "f"(x)); return y; }
DEVI float rcp(float x) { float y; asm("rcp.approx.ftz.f32 %0, %1;" : "=f"(y) : "f"(x)); return y; }
DEVI void mma16(float (&d)[4], uint32_t a0, uint32_t a1, uint32_t a2, uint32_t a3, uint32_t b0, uint32_t b1) {
    asm volatile("mma.sync.aligned.m16n8k16.row.col.f32.bf16.bf16.f32 {%0,%1,%2,%3}, {%4,%5,%6,%7}, {%8,%9}, {%0,%1,%2,%3};"
        : "+f"(d[0]), "+f"(d[1]), "+f"(d[2]), "+f"(d[3]) : "r"(a0), "r"(a1), "r"(a2), "r"(a3), "r"(b0), "r"(b1));
}
DEVI void mma8(float (&d)[4], uint32_t a0, uint32_t a1, uint32_t b0) {
    asm volatile("mma.sync.aligned.m16n8k8.row.col.f32.bf16.bf16.f32 {%0,%1,%2,%3}, {%4,%5}, {%6}, {%0,%1,%2,%3};"
        : "+f"(d[0]), "+f"(d[1]), "+f"(d[2]), "+f"(d[3]) : "r"(a0), "r"(a1), "r"(b0));
}
DEVI uint4 lds128(uint32_t a) { uint4 v; asm volatile("ld.shared.v4.u32 {%0,%1,%2,%3}, [%4];" : "=r"(v.x), "=r"(v.y), "=r"(v.z), "=r"(v.w) : "r"(a) : "memory"); return v; }
DEVI uint2 lds64(uint32_t a) { uint2 v; asm volatile("ld.shared.v2.u32 {%0,%1}, [%2];" : "=r"(v.x), "=r"(v.y) : "r"(a) : "memory"); return v; }
DEVI uint32_t lds32(uint32_t a) { uint32_t v; asm volatile("ld.shared.u32 %0, [%1];" : "=r"(v) : "r"(a) : "memory"); return v; }
DEVI uint32_t lds32v(uint32_t a) { uint32_t v; asm volatile("ld.volatile.shared.u32 %0, [%1];" : "=r"(v) : "r"(a) : "memory"); return v; }
DEVI uint4 lds128v(uint32_t a) { uint4 v; asm volatile("ld.volatile.shared.v4.u32 {%0,%1,%2,%3}, [%4];" : "=r"(v.x), "=r"(v.y), "=r"(v.z), "=r"(v.w) : "r"(a) : "memory"); return v; }
DEVI uint32_t lds16(uint32_t a) { uint32_t v; asm volatile("ld.shared.u16 %0, [%1];" : "=r"(v) : "r"(a) : "memory"); return v; }
DEVI uint4 ldsm4(uint32_t a) { uint4 v; asm volatile("ldmatrix.sync.aligned.m8n8.x4.shared.b16 {%0,%1,%2,%3}, [%4];" : "=r"(v.x), "=r"(v.y), "=r"(v.z), "=r"(v.w) : "r"(a) : "memory"); return v; }
DEVI uint4 ldsm4t(uint32_t a) { uint4 v; asm volatile("ldmatrix.sync.aligned.m8n8.x4.trans.shared.b16 {%0,%1,%2,%3}, [%4];" : "=r"(v.x), "=r"(v.y), "=r"(v.z), "=r"(v.w) : "r"(a) : "memory"); return v; }
DEVI uint2 ldsm2(uint32_t a) { uint2 v; asm volatile("ldmatrix.sync.aligned.m8n8.x2.shared.b16 {%0,%1}, [%2];" : "=r"(v.x), "=r"(v.y) : "r"(a) : "memory"); return v; }
DEVI void stsm4t(uint32_t a, uint32_t x, uint32_t y, uint32_t z, uint32_t w) { asm volatile("stmatrix.sync.aligned.m8n8.x4.trans.shared.b16 [%0], {%1,%2,%3,%4};" :: "r"(a), "r"(x), "r"(y), "r"(z), "r"(w) : "memory"); }
DEVI void sts128(uint32_t a, uint32_t x, uint32_t y, uint32_t z, uint32_t w) { asm volatile("st.shared.v4.u32 [%0], {%1,%2,%3,%4};" :: "r"(a), "r"(x), "r"(y), "r"(z), "r"(w) : "memory"); }
DEVI void sts64(uint32_t a, uint32_t x, uint32_t y) { asm volatile("st.shared.v2.u32 [%0], {%1,%2};" :: "r"(a), "r"(x), "r"(y) : "memory"); }
DEVI void sts32(uint32_t a, uint32_t x) { asm volatile("st.shared.u32 [%0], %1;" :: "r"(a), "r"(x) : "memory"); }
DEVI void sts32p(uint32_t a, uint32_t x, bool pred) { asm volatile("{.reg .pred p; setp.ne.u32 p, %2, 0; @p st.shared.u32 [%0], %1;}" :: "r"(a), "r"(x), "r"((uint32_t)pred) : "memory"); }
DEVI void sta128(uint32_t a, uint32_t x, uint32_t y, uint32_t z, uint32_t w, uint32_t bar) {
    asm volatile("st.async.weak.shared::cluster.mbarrier::complete_tx::bytes.v4.b32 [%0], {%1,%2,%3,%4}, [%5];" :: "r"(a), "r"(x), "r"(y), "r"(z), "r"(w), "r"(bar) : "memory");
}
DEVI void sta128p(uint32_t a, uint32_t x, uint32_t y, uint32_t z, uint32_t w, uint32_t bar, bool pred) {
    asm volatile("{.reg .pred p; setp.ne.u32 p, %6, 0; @p st.async.weak.shared::cluster.mbarrier::complete_tx::bytes.v4.b32 [%0], {%1,%2,%3,%4}, [%5];}" :: "r"(a), "r"(x), "r"(y), "r"(z), "r"(w), "r"(bar), "r"((uint32_t)pred) : "memory");
}
DEVI void sta64(uint32_t a, uint32_t x, uint32_t y, uint32_t bar) {
    asm volatile("st.async.weak.shared::cluster.mbarrier::complete_tx::bytes.v2.b32 [%0], {%1,%2}, [%3];" :: "r"(a), "r"(x), "r"(y), "r"(bar) : "memory");
}
DEVI void sta32(uint32_t a, uint32_t x, uint32_t bar) {
    asm volatile("st.async.weak.shared::cluster.mbarrier::complete_tx::bytes.b32 [%0], %1, [%2];" :: "r"(a), "r"(x), "r"(bar) : "memory");
}
DEVI uint4 ldg_pkt(const void* p) {
    uint4 v;
    asm volatile("ld.relaxed.gpu.global.v4.u32 {%0,%1,%2,%3}, [%4];" : "=r"(v.x), "=r"(v.y), "=r"(v.z), "=r"(v.w) : "l"(p) : "memory");
    return v;
}
DEVI void ldg_pkt_if(uint4& v, const void* p, bool pred) {
    asm volatile("{.reg .pred p; setp.ne.u32 p, %5, 0; @p ld.relaxed.gpu.global.v4.u32 {%0,%1,%2,%3}, [%4];}"
        : "+r"(v.x), "+r"(v.y), "+r"(v.z), "+r"(v.w) : "l"(p), "r"((uint32_t)pred) : "memory");
}
DEVI void ldg_pkt_retry(uint4& v, const void* p, uint32_t tag) {
    asm volatile("{.reg .pred p; .reg .b32 t; lop3.b32 t, %0, %5, 1, 0x28; setp.ne.u32 p, t, 0; @p ld.relaxed.gpu.global.v4.u32 {%0,%1,%2,%3}, [%4];}"
        : "+r"(v.x), "+r"(v.y), "+r"(v.z), "+r"(v.w) : "l"(p), "r"(tag) : "memory");
}
DEVI void stg_pkt(void* p, uint32_t x, uint32_t y, uint32_t z, uint32_t w) {
    asm volatile("st.relaxed.gpu.global.v4.u32 [%0], {%1,%2,%3,%4};" :: "l"(p), "r"(x), "r"(y), "r"(z), "r"(w) : "memory");
}
DEVI uint32_t ldg_word(const void* p) { uint32_t v; asm volatile("ld.relaxed.gpu.global.u32 %0, [%1];" : "=r"(v) : "l"(p) : "memory"); return v; }
DEVI void stg_word(void* p, uint32_t x, bool pred) {
    asm volatile("{.reg .pred p; setp.ne.u32 p, %2, 0; @p st.relaxed.gpu.global.u32 [%0], %1;}" :: "l"(p), "r"(x), "r"((uint32_t)pred) : "memory");
}
DEVI uint2 ldg64nc(const void* p) { uint2 v; asm volatile("ld.global.nc.L1::no_allocate.v2.u32 {%0,%1}, [%2];" : "=r"(v.x), "=r"(v.y) : "l"(p)); return v; }
DEVI void prefetch_l2(const void* p, uint32_t bytes) { asm volatile("cp.async.bulk.prefetch.L2.global [%0], %1;" :: "l"(p), "r"(bytes) : "memory"); }
DEVI uint4 ldg128(const void* p) { uint4 v; asm volatile("ld.global.cg.v4.u32 {%0,%1,%2,%3}, [%4];" : "=r"(v.x), "=r"(v.y), "=r"(v.z), "=r"(v.w) : "l"(p) : "memory"); return v; }
DEVI uint2 ldg64(const void* p) { uint2 v; asm volatile("ld.global.cg.v2.u32 {%0,%1}, [%2];" : "=r"(v.x), "=r"(v.y) : "l"(p) : "memory"); return v; }
DEVI uint32_t ldg32(const void* p) { uint32_t v; asm volatile("ld.global.cg.u32 %0, [%1];" : "=r"(v) : "l"(p) : "memory"); return v; }
DEVI void stg128(void* p, uint32_t x, uint32_t y, uint32_t z, uint32_t w) { asm volatile("st.global.cg.v4.u32 [%0], {%1,%2,%3,%4};" :: "l"(p), "r"(x), "r"(y), "r"(z), "r"(w) : "memory"); }
DEVI void stg128p(void* p, uint32_t x, uint32_t y, uint32_t z, uint32_t w, bool pred) { asm volatile("{.reg .pred p; setp.ne.u32 p, %5, 0; @p st.global.cg.v4.u32 [%0], {%1,%2,%3,%4};}" :: "l"(p), "r"(x), "r"(y), "r"(z), "r"(w), "r"((uint32_t)pred) : "memory"); }
DEVI void stg64(void* p, uint32_t x, uint32_t y) { asm volatile("st.global.cg.v2.u32 [%0], {%1,%2};" :: "l"(p), "r"(x), "r"(y) : "memory"); }
DEVI void stg32(void* p, uint32_t x) { asm volatile("st.global.cg.u32 [%0], %1;" :: "l"(p), "r"(x) : "memory"); }
DEVI void cp16(uint32_t dst, const void* src) { asm volatile("cp.async.cg.shared.global [%0], [%1], 16;" :: "r"(dst), "l"(src) : "memory"); }
DEVI void cp16_if(uint32_t dst, const void* src, bool pred) { asm volatile("{.reg .pred p; setp.ne.u32 p, %2, 0; @p cp.async.cg.shared.global [%0], [%1], 16;}" :: "r"(dst), "l"(src), "r"((uint32_t)pred) : "memory"); }
DEVI void cp_commit() { asm volatile("cp.async.commit_group;" ::: "memory"); }
DEVI void cp4(uint32_t dst, const void* src) { asm volatile("cp.async.ca.shared.global [%0], [%1], 4;" :: "r"(dst), "l"(src) : "memory"); }
template <int N> DEVI void cp_wait() { asm volatile("cp.async.wait_group %0;" :: "n"(N) : "memory"); }
DEVI void cp_wait_all() { asm volatile("cp.async.wait_all;" ::: "memory"); }
DEVI void bar_sync(int id, int n) { asm volatile("bar.sync %0, %1;" :: "r"(id), "r"(n) : "memory"); }
DEVI void bar_arrive(int id, int n) { asm volatile("bar.arrive %0, %1;" :: "r"(id), "r"(n) : "memory"); }
DEVI void fence_async_smem() { asm volatile("fence.proxy.async.shared::cta;" ::: "memory"); }
DEVI void fence_async_global() { asm volatile("fence.proxy.async.global;" ::: "memory"); }
DEVI void mbar_init(uint32_t b, int n) { asm volatile("mbarrier.init.shared.b64 [%0], %1;" :: "r"(b), "r"(n) : "memory"); }
DEVI void mbar_expect(uint32_t b, uint32_t bytes, bool pred) {
    asm volatile("{.reg .pred p; setp.ne.u32 p, %2, 0; @p mbarrier.arrive.expect_tx.shared.b64 _, [%0], %1;}" :: "r"(b), "r"(bytes), "r"((uint32_t)pred) : "memory");
}
DEVI void mbar_arrive(uint32_t b, bool pred) { asm volatile("{.reg .pred p; setp.ne.u32 p, %1, 0; @p mbarrier.arrive.shared.b64 _, [%0];}" :: "r"(b), "r"((uint32_t)pred) : "memory"); }
DEVI void mbar_arrive_all3(uint32_t b, uint32_t lane) {
    asm volatile("{.reg .pred p; .reg .u32 a; setp.lt.u32 p, %1, 3; @p mapa.shared::cluster.u32 a, %0, %1; @p mbarrier.arrive.relaxed.cluster.shared::cluster.b64 _, [a];}" :: "r"(b), "r"(lane) : "memory");
}
#define FAULT "or.b32 n, n, 1; st.volatile.shared.u32 [n], n;\n"
#define LIM1 "400000"
#define LIM2 "2000000"
DEVI void fault_if(bool p, uint32_t n) { asm volatile("{.reg .pred p; setp.ne.u32 p, %0, 0; @p st.volatile.shared.u32 [%1], %1;}" :: "r"((uint32_t)p), "r"(n | 1) : "memory"); }
DEVI void mbar_wait(uint32_t b, uint32_t parity) {
    asm volatile("{.reg .pred p; .reg .u32 n;\n"
        "mbarrier.try_wait.parity.shared::cta.b64 p, [%0], %1;\n"
        "@p bra.uni D%=;\n"
        "mov.u32 n, 0;\n"
        "W%=: mbarrier.try_wait.parity.shared::cta.b64 p, [%0], %1;\n"
        "@p bra.uni D%=;\n"
        "add.u32 n, n, 1; setp.lt.u32 p, n, " LIM1 "; @p bra.uni W%=;\n"
        FAULT
        "D%=:}" :: "r"(b), "r"(parity) : "memory");
}
constexpr int POLL_LIMIT = 2000000;
DEVI void cnt_wait(const unsigned* c, unsigned target) {
    asm volatile("{.reg .pred p; .reg .u32 n, v;\n"
        "ld.acquire.gpu.global.u32 v, [%0];\n"
        "setp.ge.u32 p, v, %1; vote.sync.all.pred p, p, 0xffffffff; @p bra.uni D%=;\n"
        "mov.u32 n, 0;\n"
        "W%=: ld.acquire.gpu.global.u32 v, [%0];\n"
        "setp.ge.u32 p, v, %1; vote.sync.all.pred p, p, 0xffffffff; @p bra.uni D%=;\n"
        "add.u32 n, n, 1; setp.lt.u32 p, n, " LIM2 "; @p bra.uni W%=;\n"
        FAULT
        "D%=:}" :: "l"(c), "r"(target) : "memory");
}
DEVI void hint_wait(const unsigned* c, unsigned target) {
    asm volatile("{.reg .pred p; .reg .u32 n, v;\n"
        "ld.relaxed.gpu.global.u32 v, [%0];\n"
        "setp.ge.u32 p, v, %1; vote.sync.all.pred p, p, 0xffffffff; @p bra.uni D%=;\n"
        "mov.u32 n, 0;\n"
        "W%=: ld.relaxed.gpu.global.u32 v, [%0];\n"
        "setp.ge.u32 p, v, %1; vote.sync.all.pred p, p, 0xffffffff; @p bra.uni D%=;\n"
        "add.u32 n, n, 1; setp.lt.u32 p, n, " LIM2 "; @p bra.uni W%=;\n"
        FAULT
        "D%=:}" :: "l"(c), "r"(target) : "memory");
}
DEVI bool cnt_poll(const unsigned* c, unsigned target, uint32_t b, uint32_t parity) {
    uint32_t r;
    asm volatile("{.reg .pred p; .reg .u32 n, v;\n"
        "mov.u32 n, 0; mov.u32 %0, 0;\n"
        "W%=: ld.acquire.gpu.global.u32 v, [%1];\n"
        "setp.ge.u32 p, v, %2; vote.sync.all.pred p, p, 0xffffffff; @p bra.uni D%=;\n"
        "mbarrier.test_wait.parity.shared::cta.b64 p, [%3], %4;\n"
        "add.u32 n, n, 1; setp.gt.or.u32 p, n, 1000, p; vote.sync.any.pred p, p, 0xffffffff; @!p bra.uni W%=;\n"
        "mov.u32 %0, 1;\n"
        "D%=:}" : "=r"(r) : "l"(c), "r"(target), "r"(b), "r"(parity) : "memory");
    return r;
}
template <int N = 1> DEVI void cnt_add(unsigned* c, int lane) {
    asm volatile("{.reg .pred p; setp.eq.u32 p, %1, 0; fence.acq_rel.gpu; bar.warp.sync 0xffffffff; @p red.relaxed.gpu.global.add.u32 [%0], %2;}" :: "l"(c + lane), "r"(lane), "n"(N) : "memory");
}
DEVI void cnt_hint(unsigned* c, int lane) {
    asm volatile("{.reg .pred p; setp.eq.u32 p, %1, 0; @p red.relaxed.gpu.global.add.u32 [%0], 1;}" :: "l"(c + lane), "r"(lane) : "memory");
}
template <int N = NT> DEVI uint32_t ring_tag(unsigned u, uint32_t ep) { return (u / RING + ep * ((N - 1 - u % RING) / RING + 1) + 1) & 1; }
static_assert(RING >= LAGA && RING > LAG, "ring too short");
DEVI uint32_t lop_bad(uint32_t acc, uint32_t x, uint32_t y, uint32_t tag) {
    uint32_t d; asm("{.reg .b32 t; lop3.b32 t, %2, %3, %4, 0x7e; or.b32 %0, t, %1;}" : "=r"(d) : "r"(acc), "r"(x), "r"(y), "r"(tag)); return d;
}
template <int N> DEVI void validate(uint4* v, const void* p, int step, uint32_t tag) {
    for (int n = 0;; n++) {
        uint32_t bad = 0;
#pragma unroll
        for (int i = 0; i < N; i += 2) bad = lop_bad(bad, v[i].x, v[i + 1 < N ? i + 1 : i].x, tag);
        if (!__any_sync(~0u, bad & 1)) break;
#pragma unroll
        for (int i = 0; i < N; i++) ldg_pkt_retry(v[i], static_cast<const char*>(p) + i * step, tag);
        fault_if(n > POLL_LIMIT, n);
    }
}
DEVI uint32_t page_par(uint32_t off) { return __popc((off >> 12) & 0xb2) & 1; }
DEVI uint32_t inbox_off(int b) { return (b >> 1) * 32768 + (b & 1) * 8192; }
DEVI uint32_t mem_off(int w, int i) { return 0x180000 + w * 1024 + (i & 1) * 512 + (i & 3) * 16384 + (i < 4 ? 0 : i < 8 ? 0x30000 : 0x40000); }
DEVI void sched_fence(uint32_t zero, uint32_t id) { asm volatile("{.reg .pred p; setp.ne.u32 p, %0, %1; @p bra.uni D%=; exit; D%=:}" :: "r"(zero), "r"(id) : "memory"); }
DEVI uint32_t clk() { uint32_t c; asm volatile("mov.u32 %0, %%clock;" : "=r"(c) :: "memory"); return c; }
DEVI void delay(uint32_t n) {
    if (n) asm volatile("{.reg .pred p; .reg .u32 c, e; mov.u32 e, %%clock;\n W%=: mov.u32 c, %%clock; sub.u32 c, c, e; setp.lt.u32 p, c, %0; @p bra.uni W%=;}" :: "r"(n) : "memory");
}
DEVI void delay_until(uint32_t t0, uint32_t n) {
    asm volatile("{.reg .pred p; .reg .u32 c;\n W%=: mov.u32 c, %%clock; sub.u32 c, c, %1; setp.lt.u32 p, c, %0; @p bra.uni W%=;}" :: "r"(n), "r"(t0) : "memory");
}
DEVI void wg_fence() { asm volatile("wgmma.fence.sync.aligned;" ::: "memory"); }
DEVI void wg_commit() { asm volatile("wgmma.commit_group.sync.aligned;" ::: "memory"); }
template <int N> DEVI void wg_wait() { asm volatile("wgmma.wait_group.sync.aligned %0;" :: "n"(N) : "memory"); }
DEVI uint64_t mkdesc(uint32_t lo, uint32_t hi) { uint64_t d; asm("mov.b64 %0, {%1,%2};" : "=l"(d) : "r"(lo), "r"(hi)); return d; }
DEVI void cluster_arrive() { asm volatile("barrier.cluster.arrive.relaxed.aligned;" ::: "memory"); }
DEVI void cluster_wait() { asm volatile("barrier.cluster.wait.aligned;" ::: "memory"); }
DEVI void cluster_sync() { asm volatile("barrier.cluster.arrive.aligned;\n barrier.cluster.wait.aligned;" ::: "memory"); }
DEVI void wgmma_ss16t(float (&d)[8], uint64_t da, uint64_t db, int acc) {
    asm volatile("{.reg .pred p; setp.ne.b32 p, %10, 0;\n"
        "wgmma.mma_async.sync.aligned.m64n16k16.f32.bf16.bf16 {%0,%1,%2,%3,%4,%5,%6,%7}, %8, %9, p, 1, 1, 0, 1;}"
        : "+f"(d[0]), "+f"(d[1]), "+f"(d[2]), "+f"(d[3]), "+f"(d[4]), "+f"(d[5]), "+f"(d[6]), "+f"(d[7])
        : "l"(da), "l"(db), "r"(acc));
}
DEVI void wgmma_ss16a(float (&d)[8], uint64_t da, uint64_t db, int acc) {
    asm volatile("{.reg .pred p; setp.ne.b32 p, %10, 0;\n"
        "wgmma.mma_async.sync.aligned.m64n16k16.f32.bf16.bf16 {%0,%1,%2,%3,%4,%5,%6,%7}, %8, %9, p, 1, 1, 1, 0;}"
        : "+f"(d[0]), "+f"(d[1]), "+f"(d[2]), "+f"(d[3]), "+f"(d[4]), "+f"(d[5]), "+f"(d[6]), "+f"(d[7])
        : "l"(da), "l"(db), "r"(acc));
}
DEVI void wgmma_ss64(float (&d)[32], uint64_t da, uint64_t db, int acc) {
    asm volatile("{.reg .pred p; setp.ne.b32 p, %34, 0;\n"
        "wgmma.mma_async.sync.aligned.m64n64k16.f32.bf16.bf16 {%0,%1,%2,%3,%4,%5,%6,%7,%8,%9,%10,%11,%12,%13,%14,%15,%16,%17,%18,%19,%20,%21,%22,%23,%24,%25,%26,%27,%28,%29,%30,%31}, %32, %33, p, 1, 1, 0, 0;}"
        : "+f"(d[0]), "+f"(d[1]), "+f"(d[2]), "+f"(d[3]), "+f"(d[4]), "+f"(d[5]), "+f"(d[6]), "+f"(d[7]), "+f"(d[8]), "+f"(d[9]), "+f"(d[10]), "+f"(d[11]), "+f"(d[12]), "+f"(d[13]), "+f"(d[14]), "+f"(d[15]), "+f"(d[16]), "+f"(d[17]), "+f"(d[18]), "+f"(d[19]), "+f"(d[20]), "+f"(d[21]), "+f"(d[22]), "+f"(d[23]), "+f"(d[24]), "+f"(d[25]), "+f"(d[26]), "+f"(d[27]), "+f"(d[28]), "+f"(d[29]), "+f"(d[30]), "+f"(d[31])
        : "l"(da), "l"(db), "r"(acc));
}
DEVI void wgmma_rs16t(float (&d)[8], uint32_t a0, uint32_t a1, uint32_t a2, uint32_t a3, uint64_t db, int acc) {
    asm volatile("{.reg .pred p; setp.ne.b32 p, %13, 0;\n"
        "wgmma.mma_async.sync.aligned.m64n16k16.f32.bf16.bf16 {%0,%1,%2,%3,%4,%5,%6,%7}, {%8,%9,%10,%11}, %12, p, 1, 1, 1;}"
        : "+f"(d[0]), "+f"(d[1]), "+f"(d[2]), "+f"(d[3]), "+f"(d[4]), "+f"(d[5]), "+f"(d[6]), "+f"(d[7])
        : "r"(a0), "r"(a1), "r"(a2), "r"(a3), "l"(db), "r"(acc));
}
DEVI void wgmma_rs64(float (&d)[32], uint32_t a0, uint32_t a1, uint32_t a2, uint32_t a3, uint64_t db, int acc) {
    asm volatile("{.reg .pred p; setp.ne.b32 p, %37, 0;\n"
        "wgmma.mma_async.sync.aligned.m64n64k16.f32.bf16.bf16 {%0,%1,%2,%3,%4,%5,%6,%7,%8,%9,%10,%11,%12,%13,%14,%15,%16,%17,%18,%19,%20,%21,%22,%23,%24,%25,%26,%27,%28,%29,%30,%31}, {%32,%33,%34,%35}, %36, p, 1, 1, 0;}"
        : "+f"(d[0]), "+f"(d[1]), "+f"(d[2]), "+f"(d[3]), "+f"(d[4]), "+f"(d[5]), "+f"(d[6]), "+f"(d[7]), "+f"(d[8]), "+f"(d[9]), "+f"(d[10]), "+f"(d[11]), "+f"(d[12]), "+f"(d[13]), "+f"(d[14]), "+f"(d[15]), "+f"(d[16]), "+f"(d[17]), "+f"(d[18]), "+f"(d[19]), "+f"(d[20]), "+f"(d[21]), "+f"(d[22]), "+f"(d[23]), "+f"(d[24]), "+f"(d[25]), "+f"(d[26]), "+f"(d[27]), "+f"(d[28]), "+f"(d[29]), "+f"(d[30]), "+f"(d[31])
        : "r"(a0), "r"(a1), "r"(a2), "r"(a3), "l"(db), "r"(acc));
}
DEVI void wgmma_ss168t(float (&d)[84], uint64_t da, uint64_t db, int acc) {
    asm volatile("{.reg .pred p; setp.ne.b32 p, %86, 0;\n"
        "wgmma.mma_async.sync.aligned.m64n168k16.f32.bf16.bf16 {%0,%1,%2,%3,%4,%5,%6,%7,%8,%9,%10,%11,%12,%13,%14,%15,%16,%17,%18,%19,%20,%21,%22,%23,%24,%25,%26,%27,%28,%29,%30,%31,%32,%33,%34,%35,%36,%37,%38,%39,%40,%41,%42,%43,%44,%45,%46,%47,%48,%49,%50,%51,%52,%53,%54,%55,%56,%57,%58,%59,%60,%61,%62,%63,%64,%65,%66,%67,%68,%69,%70,%71,%72,%73,%74,%75,%76,%77,%78,%79,%80,%81,%82,%83}, %84, %85, p, 1, 1, 0, 1;}"
        : "+f"(d[0]), "+f"(d[1]), "+f"(d[2]), "+f"(d[3]), "+f"(d[4]), "+f"(d[5]), "+f"(d[6]), "+f"(d[7]), "+f"(d[8]), "+f"(d[9]), "+f"(d[10]), "+f"(d[11]), "+f"(d[12]), "+f"(d[13]), "+f"(d[14]), "+f"(d[15]), "+f"(d[16]), "+f"(d[17]), "+f"(d[18]), "+f"(d[19]), "+f"(d[20]), "+f"(d[21]), "+f"(d[22]), "+f"(d[23]), "+f"(d[24]), "+f"(d[25]), "+f"(d[26]), "+f"(d[27]), "+f"(d[28]), "+f"(d[29]), "+f"(d[30]), "+f"(d[31]), "+f"(d[32]), "+f"(d[33]), "+f"(d[34]), "+f"(d[35]), "+f"(d[36]), "+f"(d[37]), "+f"(d[38]), "+f"(d[39]), "+f"(d[40]), "+f"(d[41]), "+f"(d[42]), "+f"(d[43]), "+f"(d[44]), "+f"(d[45]), "+f"(d[46]), "+f"(d[47]), "+f"(d[48]), "+f"(d[49]), "+f"(d[50]), "+f"(d[51]), "+f"(d[52]), "+f"(d[53]), "+f"(d[54]), "+f"(d[55]), "+f"(d[56]), "+f"(d[57]), "+f"(d[58]), "+f"(d[59]), "+f"(d[60]), "+f"(d[61]), "+f"(d[62]), "+f"(d[63]), "+f"(d[64]), "+f"(d[65]), "+f"(d[66]), "+f"(d[67]), "+f"(d[68]), "+f"(d[69]), "+f"(d[70]), "+f"(d[71]), "+f"(d[72]), "+f"(d[73]), "+f"(d[74]), "+f"(d[75]), "+f"(d[76]), "+f"(d[77]), "+f"(d[78]), "+f"(d[79]), "+f"(d[80]), "+f"(d[81]), "+f"(d[82]), "+f"(d[83])
        : "l"(da), "l"(db), "r"(acc));
}
DEVI void wgmma_rs96t(float (&d)[48], uint32_t a0, uint32_t a1, uint32_t a2, uint32_t a3, uint64_t db, int acc) {
    asm volatile("{.reg .pred p; setp.ne.b32 p, %53, 0;\n"
        "wgmma.mma_async.sync.aligned.m64n96k16.f32.bf16.bf16 {%0,%1,%2,%3,%4,%5,%6,%7,%8,%9,%10,%11,%12,%13,%14,%15,%16,%17,%18,%19,%20,%21,%22,%23,%24,%25,%26,%27,%28,%29,%30,%31,%32,%33,%34,%35,%36,%37,%38,%39,%40,%41,%42,%43,%44,%45,%46,%47}, {%48,%49,%50,%51}, %52, p, 1, 1, 1;}"
        : "+f"(d[0]), "+f"(d[1]), "+f"(d[2]), "+f"(d[3]), "+f"(d[4]), "+f"(d[5]), "+f"(d[6]), "+f"(d[7]), "+f"(d[8]), "+f"(d[9]), "+f"(d[10]), "+f"(d[11]), "+f"(d[12]), "+f"(d[13]), "+f"(d[14]), "+f"(d[15]), "+f"(d[16]), "+f"(d[17]), "+f"(d[18]), "+f"(d[19]), "+f"(d[20]), "+f"(d[21]), "+f"(d[22]), "+f"(d[23]), "+f"(d[24]), "+f"(d[25]), "+f"(d[26]), "+f"(d[27]), "+f"(d[28]), "+f"(d[29]), "+f"(d[30]), "+f"(d[31]), "+f"(d[32]), "+f"(d[33]), "+f"(d[34]), "+f"(d[35]), "+f"(d[36]), "+f"(d[37]), "+f"(d[38]), "+f"(d[39]), "+f"(d[40]), "+f"(d[41]), "+f"(d[42]), "+f"(d[43]), "+f"(d[44]), "+f"(d[45]), "+f"(d[46]), "+f"(d[47])
        : "r"(a0), "r"(a1), "r"(a2), "r"(a3), "l"(db), "r"(acc));
}
DEVI void wgmma_rs192t(float (&d)[96], uint32_t a0, uint32_t a1, uint32_t a2, uint32_t a3, uint64_t db, int acc) {
    asm volatile("{.reg .pred p; setp.ne.b32 p, %101, 0;\n"
        "wgmma.mma_async.sync.aligned.m64n192k16.f32.bf16.bf16 {%0,%1,%2,%3,%4,%5,%6,%7,%8,%9,%10,%11,%12,%13,%14,%15,%16,%17,%18,%19,%20,%21,%22,%23,%24,%25,%26,%27,%28,%29,%30,%31,%32,%33,%34,%35,%36,%37,%38,%39,%40,%41,%42,%43,%44,%45,%46,%47,%48,%49,%50,%51,%52,%53,%54,%55,%56,%57,%58,%59,%60,%61,%62,%63,%64,%65,%66,%67,%68,%69,%70,%71,%72,%73,%74,%75,%76,%77,%78,%79,%80,%81,%82,%83,%84,%85,%86,%87,%88,%89,%90,%91,%92,%93,%94,%95}, {%96,%97,%98,%99}, %100, p, 1, 1, 1;}"
        : "+f"(d[0]), "+f"(d[1]), "+f"(d[2]), "+f"(d[3]), "+f"(d[4]), "+f"(d[5]), "+f"(d[6]), "+f"(d[7]), "+f"(d[8]), "+f"(d[9]), "+f"(d[10]), "+f"(d[11]), "+f"(d[12]), "+f"(d[13]), "+f"(d[14]), "+f"(d[15]), "+f"(d[16]), "+f"(d[17]), "+f"(d[18]), "+f"(d[19]), "+f"(d[20]), "+f"(d[21]), "+f"(d[22]), "+f"(d[23]), "+f"(d[24]), "+f"(d[25]), "+f"(d[26]), "+f"(d[27]), "+f"(d[28]), "+f"(d[29]), "+f"(d[30]), "+f"(d[31]), "+f"(d[32]), "+f"(d[33]), "+f"(d[34]), "+f"(d[35]), "+f"(d[36]), "+f"(d[37]), "+f"(d[38]), "+f"(d[39]), "+f"(d[40]), "+f"(d[41]), "+f"(d[42]), "+f"(d[43]), "+f"(d[44]), "+f"(d[45]), "+f"(d[46]), "+f"(d[47]), "+f"(d[48]), "+f"(d[49]), "+f"(d[50]), "+f"(d[51]), "+f"(d[52]), "+f"(d[53]), "+f"(d[54]), "+f"(d[55]), "+f"(d[56]), "+f"(d[57]), "+f"(d[58]), "+f"(d[59]), "+f"(d[60]), "+f"(d[61]), "+f"(d[62]), "+f"(d[63]), "+f"(d[64]), "+f"(d[65]), "+f"(d[66]), "+f"(d[67]), "+f"(d[68]), "+f"(d[69]), "+f"(d[70]), "+f"(d[71]), "+f"(d[72]), "+f"(d[73]), "+f"(d[74]), "+f"(d[75]), "+f"(d[76]), "+f"(d[77]), "+f"(d[78]), "+f"(d[79]), "+f"(d[80]), "+f"(d[81]), "+f"(d[82]), "+f"(d[83]), "+f"(d[84]), "+f"(d[85]), "+f"(d[86]), "+f"(d[87]), "+f"(d[88]), "+f"(d[89]), "+f"(d[90]), "+f"(d[91]), "+f"(d[92]), "+f"(d[93]), "+f"(d[94]), "+f"(d[95])
        : "r"(a0), "r"(a1), "r"(a2), "r"(a3), "l"(db), "r"(acc));
}

#define TRD(t, i)
namespace km {
#define NSS 6
#define RG "184"
#define RW "136"
#define NFL 2
#define NR1 3
#define NR2 3
#define FK 5
#define NGAP 8
constexpr int O_H = 0;
constexpr int O_MB = 73728;
constexpr int O_VX = 96768;
constexpr int O_KX = 113152;
constexpr int O_QX = 119296;
constexpr int O_VM = 125440;
constexpr int O_KM = 129536;
constexpr int O_QM = 131072;
constexpr int O_SM = 132608;
constexpr int O_ST = 135168;
constexpr int O_OX = 145408;
constexpr int O_WO = 149504;
constexpr int O_OS = O_WO;
constexpr int O_WS = O_WO + 49152;
constexpr int O_RL = 110592;
constexpr int O_BAR = O_WS + NSS * 4096;
constexpr int SMEM = O_BAR + 128 + 1024 + TR_BYTES;
enum { B_X = 0, B_XFREE = 8, B_WIN = 16, B_VX = 24, B_SM = 32, B_ST = 40, B_SU = 48, B_EP = 56 };
#define DLY1 (100 * w)
#define DLY2 300
#define XON 1
#define GON 1
#define DLY0 1000
#define PFON 0
#define PLACE 1
#define XST 0
#define DLYW 12000
#define DLYB 14000
constexpr uint32_t DESC_HI = (1024 >> 4) | (1u << 30);
constexpr float SC = 0.08838834764831845f * 1.4426950408889634f;
}

__global__ void __cluster_dims__(3, 1, 1) __launch_bounds__(384, 1)
k_main(const __nv_bfloat16* __restrict__ x0, const __nv_bfloat16* __restrict__ wqkv, const __nv_bfloat16* __restrict__ wo,
       const __nv_bfloat16* __restrict__ mem0, const __nv_bfloat16* __restrict__ Wq, const __nv_bfloat16* __restrict__ Wk,
       const __nv_bfloat16* __restrict__ Wv, const __nv_bfloat16* __restrict__ Wo) {
    using namespace km;
    extern __shared__ unsigned char smem_raw[];
    const uint32_t sb = (smem_u32(smem_raw) + 1023) & ~1023u;
    const int tid = threadIdx.x, lane = tid & 31, warp = __shfl_sync(~0u, tid >> 5, 0);
    uint32_t l16 = __shfl_sync(~0u, lane * 16, lane);
#define OPQ() asm volatile("" : "+r"(l16))
    const int b = blockIdx.x, h = b / 3, r = b % 3;
    const int nq = r == 2 ? 2 : 3;
    const uint32_t bar = sb + O_BAR;
    asm volatile("griddepcontrol.launch_dependents;");
    const uint32_t t_start = clk();
    if (warp == 0 && b < 72) {
        if (lane == 0) { mbar_init(bar + 96, 1); fence_async_smem(); mbar_expect(bar + 96, 8 * 3456, true); }
        __syncwarp();
        if (lane < 8) asm volatile("cp.async.bulk.shared::cluster.global.mbarrier::complete_tx::bytes [%0], [%1], 3456, [%2];" :: "r"(sb + O_RL + lane * 3472), "l"(wqkv + (b * 8 + lane) * 1728), "r"(bar + 96) : "memory");
    }
    if (tid == 352) {
        prefetch_l2(x0 + b * (2 * DM), 2 * 1152); prefetch_l2(wo + b * (6 * DM), 6 * 1152);
    }
    if (tid == 320) sts32(bar + 64, ldg32(&g_epoch));
#define EP lds32(bar + 64)
    TR_INIT(bar + 128);
    TRG(79, 0);
    uint32_t roff0, roff1;
    {
        uint32_t y0, y1;
        asm("mapa.shared::cluster.u32 %0, %1, %2;" : "=r"(y0) : "r"(sb), "r"((r + 1) % 3));
        asm("mapa.shared::cluster.u32 %0, %1, %2;" : "=r"(y1) : "r"(sb), "r"((r + 2) % 3));
        roff0 = y0 - sb; roff1 = y1 - sb;
    }
#define LSWAP ((l16 & 0x70) | ((l16 & 0x80) << 1) | ((l16 & 0x100) >> 1))
    const uint32_t nv_remote = 8 - (8 - 2 * nq);

    if (warp < 8) {
        asm volatile("setmaxnreg.inc.sync.aligned.u32 " RG ";");
        constexpr int SSP = 36 / NSS;
#define IS_SS(kk) ((kk) % SSP == 3)
#define AI(kk) (4 * ((kk) - ((kk) + SSP - 4) / SSP))
        uint32_t a[144 - 4 * NSS];
        {
            const int ci = tid & 15, slot = ci >> 1, d0 = tid >> 4;
            const __nv_bfloat16* src = slot < nq ? Wq + (3 * r + slot) * 16 : slot < 2 * nq ? Wk + (3 * r + slot - nq) * 16 : Wv + (2 * r + slot - 2 * nq) * 16;
            src += h * 128 + (ci & 1) * 8 + d0 * 4096;
            auto issue = [&](int q) {
#pragma unroll
                for (int i = 0; i < 3; i++) if (q < 12) cp16(sb + (q * 3 + i) * 4096 + d0 * 256 + ((ci ^ (d0 & 7)) << 4), src + (size_t)(q * 3 + i) * 65536);
                asm volatile("cp.async.commit_group;" ::: "memory");
            };
            if (b < 72) {
                bar_sync(10, 256);
                mbar_wait(bar + 96, 0);
                TR1(4);
#pragma unroll 2
                for (int ag = tid >> 3; ag < 231; ag += 32) {
                    const int a = ag / 21, gr = ag % 21, tl = gr >= 18;
                    const int head = 3 * a + (tl ? 0 : (gr % 6) >> 1), nw = tl ? min(3, 32 - head) : head < 32 ? 4 : 0;
                    const uint32_t p = sb + O_RL + (tid & 7) * 3472 + (tl ? gr - 18 : gr / 6) * 1152 + head * 36 + (tl ? 32 : (gr & 1) * 16), step = tl ? 36 : 4;
                    uint32_t v[4];
#pragma unroll
                    for (int i = 0; i < 4; i++) { v[i] = lds32(p + i * step); if (i >= nw) v[i] = 0; }
                    stg128(g_wa + ((a * 9 + (b >> 3)) * 21 + gr) * 64 + (b & 7) * 8 + (tid & 7), v[0], v[1], v[2], v[3]);
                }
            }
            {
                bar_arrive(15, 288);
                TR1(5);
                delay_until(t_start, DLY0);
#pragma unroll
                for (int q = 0; q < NFL; q++) issue(q);
            }
            TR1(1);
            const int mi = lane >> 3;
            const uint32_t ad = sb + ((mi >> 1) * 8 + (lane & 7)) * 256 + (((warp * 2 + (mi & 1)) ^ (lane & 7)) << 4);
#pragma unroll
            for (int kk = 0; kk < 36; kk++) {
                if (kk % 3 == 0) { cp_wait<NFL - 1>(); issue(kk / 3 + NFL); bar_sync(10, 256); }
                const uint4 f = ldsm4t(ad + kk * 4096);
                if (IS_SS(kk)) {
                    const uint32_t o0 = sb + O_WS + (kk / SSP) * 4096 + warp * 512 + lane * 4;
                    sts32(o0, f.x); sts32(o0 + 256, f.y); sts32(o0 + 128, f.z); sts32(o0 + 384, f.w);
                } else { a[AI(kk)] = f.x; a[AI(kk) + 1] = f.y; a[AI(kk) + 2] = f.z; a[AI(kk) + 3] = f.w; }
            }
            TR1(2);
            bar_sync(9, 384);
#pragma unroll
            for (int i = 0; i < 9; i++) sts128(sb + O_H + i * 8192 + 4096 + tid * 16, 0, 0, 0, 0);
#pragma unroll
            for (int i = 0; i < 8; i++) if (i * 256 + tid < (O_OX - O_KX) / 16) sts128(sb + O_KX + i * 4096 + tid * 16, 0, 0, 0, 0);
            fence_async_smem();
            cluster_sync();
        }
        TR1(3);
        const int kind = warp < nq ? 0 : warp < 2 * nq ? 1 : 2;
        const int sl = kind == 0 ? warp : kind == 1 ? warp - nq : 2 * r + warp - 2 * nq;
        const uint32_t adX0 = sb + (kind == 0 ? O_QX : kind == 1 ? O_KX : O_VX) + sl * 2048;
        const uint32_t adM0 = sb + (kind == 0 ? O_QM : kind == 1 ? O_KM : O_VM) + sl * 512;
        const uint32_t hlo = (((sb + O_H) >> 4) & 0x3fff) | (1u << 16);
        const uint32_t mlo = (((sb + O_MB) >> 4) & 0x3fff) | (16u << 16);
        const uint32_t wlo = (((sb + O_WS + (warp >> 2) * 2048) >> 4) & 0x3fff) | (8u << 16);
        const int L = (warp >> 1) & 1, qh = warp & 1;
        const uint32_t st = sb + O_ST + warp * 1280;
        float s[5][4];

#pragma unroll 1
        for (int t = -1;; t++) {
            TR_ON(t);
            OPQ();
            const uint32_t adX = adX0 + l16, adM = adM0 + l16, l8 = l16 >> 1;
            const uint32_t lq = LSWAP;
            if (t >= 0) {
                {
                    float d0[8], d1[8];
#pragma unroll
                    for (int G = 0; G < 3; G++) {
                        if (warp < 4) bar_sync(1 + G, 160); else bar_sync(12 + G, 160);
                        if (G == 0) wg_fence();
#pragma unroll
                        for (int q = 0; q < 12; q++) {
                            const int kk = 12 * G + q;
                            const uint64_t db = mkdesc(mlo + kk * 32, 8);
                            if (IS_SS(kk)) wgmma_ss16t((kk & 1) ? d1 : d0, mkdesc(wlo + (kk / SSP) * 256, 16), db, 1);
                            else wgmma_rs16t((kk & 1) ? d1 : d0, a[AI(kk)], a[AI(kk) + 1], a[AI(kk) + 2], a[AI(kk) + 3], db, kk >= 2);
                            if (kk == 0) TR(0);
                        }
                    }
                    wg_commit(); wg_wait<0>();
                    TR(1);
                    const uint32_t p0 = pk(d0[0] + d1[0], d0[1] + d1[1]), p1 = pk(d0[2] + d1[2], d0[3] + d1[3]);
                    const uint32_t p2 = pk(d0[4] + d1[4], d0[5] + d1[5]), p3 = pk(d0[6] + d1[6], d0[7] + d1[7]);
                    if (kind == 2) {
                        sts128(adM, p0, p1, p2, p3);
                        bar_arrive(4, 384);
                        sta128(adM + roff0, p0, p1, p2, p3, bar + B_SM + roff0);
                        sta128(adM + roff1, p0, p1, p2, p3, bar + B_SM + roff1);
                    } else {
                        stsm4t(adM, p0, p1, p2, p3);
                        bar_arrive(4, 384);
                    }
                }
                if (warp < 4) {
                    {
                        uint4 q[3];
                        s[4][0] = s[4][1] = s[4][2] = s[4][3] = 0.f;
                        mbar_wait(bar + B_ST, t & 1);
                        bar_sync(5, 256);
                        const uint4 k01 = ldsm4(sb + O_KM + L * 256 + l16 + (l16 & 256));
                        const uint2 k2 = ldsm2(sb + O_KM + 1024 + L * 256 + l16);
#pragma unroll
                        for (int m = 0; m < 3; m++) q[m] = ldsm4(sb + O_QX + m * 2048 + warp * 512 + lq);
                        mma16(s[4], q[0].x, q[0].y, q[0].z, q[0].w, k01.x, k01.y);
                        mma16(s[4], q[1].x, q[1].y, q[1].z, q[1].w, k01.z, k01.w);
                        mma16(s[4], q[2].x, q[2].y, q[2].z, q[2].w, k2.x, k2.y);
                        const uint32_t w0 = pk(s[4][0], s[4][1]), w1 = pk(s[4][2], s[4][3]);
                        bar_arrive(11, 256);
                        sta64(st + l8 + 5120 + 1024 + roff0, w0, w1, bar + B_SU + roff0);
                        sta64(st + l8 + 1024 + roff1, w0, w1, bar + B_SU + roff1);
                    }
                    TR(2);
#pragma unroll
                    for (int src = 0; src < 2; src++) {
                        const uint4 u = lds128(st + src * 5120 + l16), v = lds128(st + src * 5120 + 512 + l16);
                        s[0][0] += bf_lo(u.x); s[0][1] += bf_hi(u.x); s[0][2] += bf_lo(u.y); s[0][3] += bf_hi(u.y);
                        s[1][0] += bf_lo(u.z); s[1][1] += bf_hi(u.z); s[1][2] += bf_lo(u.w); s[1][3] += bf_hi(u.w);
                        s[2][0] += bf_lo(v.x); s[2][1] += bf_hi(v.x); s[2][2] += bf_lo(v.y); s[2][3] += bf_hi(v.y);
                        s[3][0] += bf_lo(v.z); s[3][1] += bf_hi(v.z); s[3][2] += bf_lo(v.w); s[3][3] += bf_hi(v.w);
                    }
                    uint4 v0[3], v1[3];
#pragma unroll
                    for (int m = 0; m < 3; m++) {
                        v0[m] = lds128(sb + O_VX + (3 * r + m) * 2048 + L * 1024 + l16);
                    }
                    mbar_wait(bar + B_SM, t & 1);
                    mbar_wait(bar + B_SU, t & 1);
                    TR(3);
                    {
                        const uint2 x = lds64(st + 1024 + l8), y = lds64(st + 5120 + 1024 + l8);
                        s[4][0] += bf_lo(x.x) + bf_lo(y.x); s[4][1] += bf_hi(x.x) + bf_hi(y.x); s[4][2] += bf_lo(x.y) + bf_lo(y.y); s[4][3] += bf_hi(x.y) + bf_hi(y.y);
                    }
                    float mx0 = fmaxf(s[4][0], s[4][1]), mx1 = fmaxf(s[4][2], s[4][3]);
#pragma unroll
                    for (int n = 0; n < 4; n++) { mx0 = fmaxf(mx0, fmaxf(s[n][0], s[n][1])); mx1 = fmaxf(mx1, fmaxf(s[n][2], s[n][3])); }
#pragma unroll
                    for (int o = 1; o < 4; o <<= 1) { mx0 = fmaxf(mx0, __shfl_xor_sync(~0u, mx0, o)); mx1 = fmaxf(mx1, __shfl_xor_sync(~0u, mx1, o)); }
                    mx0 *= -SC; mx1 *= -SC;
                    float l0 = 0.f, l1 = 0.f;
                    uint32_t p[10];
#pragma unroll
                    for (int n = 0; n < 5; n++) {
                        const float e0 = ex2(fmaf(s[n][0], SC, mx0)), e1 = ex2(fmaf(s[n][1], SC, mx0));
                        const float e2 = ex2(fmaf(s[n][2], SC, mx1)), e3 = ex2(fmaf(s[n][3], SC, mx1));
                        l0 += e0 + e1; l1 += e2 + e3;
                        p[2 * n] = pk(e0, e1); p[2 * n + 1] = pk(e2, e3);
                    }
#pragma unroll
                    for (int o = 1; o < 4; o <<= 1) { l0 += __shfl_xor_sync(~0u, l0, o); l1 += __shfl_xor_sync(~0u, l1, o); }
                    l0 = rcp(l0); l1 = rcp(l1);
                    const uint32_t otag = ring_tag(t, EP);
#pragma unroll
                    for (int m = 0; m < 3; m++) {
                        float o0[4] = {0, 0, 0, 0}, o1[4] = {0, 0, 0, 0};
                        v1[m] = lds128(sb + O_VX + (3 * r + m) * 2048 + L * 1024 + 512 + l16);
                        const uint2 vm = lds64(sb + O_VM + (3 * r + m) * 512 + l16 + L * 8);
                        mma8(o0, p[0], p[1], v0[m].x); mma8(o1, p[0], p[1], v0[m].y); mma8(o0, p[2], p[3], v0[m].z); mma8(o1, p[2], p[3], v0[m].w);
                        mma8(o0, p[4], p[5], v1[m].x); mma8(o1, p[4], p[5], v1[m].y); mma8(o0, p[6], p[7], v1[m].z); mma8(o1, p[6], p[7], v1[m].w);
                        mma8(o0, p[8], p[9], vm.x); mma8(o1, p[8], p[9], vm.y);
                        sts128(sb + O_OS + warp * 512 + m * 2048 + l16, (pk(o0[0] * l0, o0[1] * l0) & ~1u) | otag, pk(o0[2] * l1, o0[3] * l1), pk(o1[0] * l0, o1[1] * l0), pk(o1[2] * l1, o1[3] * l1));
                    }
                    TR(4);
                }
            }
            if (t + 1 >= NT) break;
            {
                float d[32];
                mbar_wait(bar + B_X, (t + 1) & 1);
                if (warp < 4) bar_sync(7, 384); else if (t >= 0) bar_sync(11, 256);
                wg_fence();
                TR(6);
#pragma unroll
                for (int kk = 0; kk < 36; kk++) {
                    if (kk == NGAP) asm volatile("{.reg .pred p; setp.ge.u32 p, %0, 4; @p bar.sync 7, 384;}" :: "r"(warp) : "memory");
                    const uint64_t db = mkdesc(hlo + ((kk >> 2) * 8192 + (kk & 3) * 32) / 16, DESC_HI);
                    if (IS_SS(kk)) wgmma_ss64(d, mkdesc(wlo + (kk / SSP) * 256, 16), db, 1);
                    else wgmma_rs64(d, a[AI(kk)], a[AI(kk) + 1], a[AI(kk) + 2], a[AI(kk) + 3], db, kk > 0);
                }
                wg_commit();
                TR(5);
                mbar_wait(bar + B_WIN, (t + 1) & 1);
                wg_wait<0>();
                TR(7);
                mbar_arrive_all3(bar + B_XFREE, l16 >> 4);
                uint32_t p[16];
#pragma unroll
                for (int u = 0; u < 16; u++) p[u] = pk(d[2 * u], d[2 * u + 1]);
                if (kind == 2) {
#pragma unroll
                    for (int u = 0; u < 4; u++) sts128(adX + u * 512, p[4 * u], p[4 * u + 1], p[4 * u + 2], p[4 * u + 3]);
                } else {
#pragma unroll
                    for (int u = 0; u < 4; u++) stsm4t(adX + u * 512, p[4 * u], p[4 * u + 1], p[4 * u + 2], p[4 * u + 3]);
                }
                __syncwarp();
                asm volatile("{.reg .pred p; setp.eq.u32 p, %1, 0; @p mbarrier.arrive.shared.b64 _, [%0];}" :: "r"(bar + B_EP), "r"(l16) : "memory");
                if (kind == 2) {
                    fence_async_smem();
                    __syncwarp();
                    asm volatile("{.reg .pred p; setp.eq.u32 p, %5, 0;\n"
                        "@p cp.async.bulk.shared::cluster.shared::cta.mbarrier::complete_tx::bytes [%0], [%2], 2048, [%3];\n"
                        "@p cp.async.bulk.shared::cluster.shared::cta.mbarrier::complete_tx::bytes [%1], [%2], 2048, [%4];}"
                        :: "r"(adX0 + roff0), "r"(adX0 + roff1), "r"(adX0), "r"(bar + B_VX + roff0), "r"(bar + B_VX + roff1), "r"(l16) : "memory");
                }
                TR(8);
                {
                    const int lim = 16 * qh + (int)(l16 >> 6) - (int)((l16 >> 3) & 6);
#pragma unroll
                    for (int n = 0; n < 4; n++)
#pragma unroll
                        for (int j = 0; j < 4; j++) s[n][j] = (n == 0 && j >= 2) || 8 * (n - (j >> 1)) + (j & 1) <= lim ? 0.f : -1e30f;
                }
                if (warp < 4) {
                    mbar_wait(bar + B_EP, (t + 1) & 1);
#pragma unroll
                    for (int m = 0; m < 3; m++) {
                        const uint4 q = ldsm4(sb + O_QX + m * 2048 + warp * 512 + lq);
                        const uint4 k0 = ldsm4(sb + O_KX + m * 2048 + L * 1024 + l16);
                        const uint4 k1 = ldsm4(sb + O_KX + m * 2048 + L * 1024 + 512 + l16);
                        mma16(s[0], q.x, q.y, q.z, q.w, k0.x, k0.y);
                        mma16(s[1], q.x, q.y, q.z, q.w, k0.z, k0.w);
                        mma16(s[2], q.x, q.y, q.z, q.w, k1.x, k1.y);
                        mma16(s[3], q.x, q.y, q.z, q.w, k1.z, k1.w);
                    }
                    uint32_t w0 = pk(s[0][0], s[0][1]), w1 = pk(s[0][2], s[0][3]), w2 = pk(s[1][0], s[1][1]), w3 = pk(s[1][2], s[1][3]);
                    sta128(st + l16 + 5120 + roff0, w0, w1, w2, w3, bar + B_ST + roff0);
                    sta128(st + l16 + roff1, w0, w1, w2, w3, bar + B_ST + roff1);
                    w0 = pk(s[2][0], s[2][1]); w1 = pk(s[2][2], s[2][3]); w2 = pk(s[3][0], s[3][1]); w3 = pk(s[3][2], s[3][3]);
                    sta128p(st + l16 + 5120 + 512 + roff0, w0, w1, w2, w3, bar + B_ST + roff0, qh);
                    sta128p(st + l16 + 512 + roff1, w0, w1, w2, w3, bar + B_ST + roff1, qh);
                    TR(9);
                }
            }
        }
        if (warp >= 4) bar_sync(11, 256); else bar_arrive(7, 160);
        cluster_sync();
    } else {
        asm volatile("setmaxnreg.dec.sync.aligned.u32 " RW ";");
        const int w = warp - 8, t2 = tid - 256;
        if (t2 == 0) {
            mbar_init(bar + B_X, 1); mbar_init(bar + B_XFREE, 24); mbar_init(bar + B_WIN, 3);
            mbar_init(bar + B_VX, 1); mbar_init(bar + B_SM, 1); mbar_init(bar + B_ST, 1); mbar_init(bar + B_SU, 1); mbar_init(bar + B_EP, 8);
            asm volatile("fence.mbarrier_init.release.cluster;" ::: "memory");
        }
        char* const ex = reinterpret_cast<char*>((reinterpret_cast<uintptr_t>(g_ex) + 0x1fffff) & ~(uintptr_t)0x1fffff);
        char* rbase = ex; uint32_t side = 0;
        {
            uint32_t m0[5][4];
#pragma unroll
            for (int i = 0; i < 5; i++) {
                const unsigned short* m = reinterpret_cast<const unsigned short*>(mem0) + min(i * 128 + t2, DM - 1);
#pragma unroll
                for (int j = 0; j < 4; j++) m0[i][j] = m[2 * j * DM] | (m[(2 * j + 1) * DM] << 16);
            }
            if (w == 3) { bar_sync(15, 288); cnt_add(g_cnt + C_W * 8, lane); TR1(1); }
            if (t2 >= 96 && t2 < 99 && PFON) prefetch_l2((t2 == 96 ? Wq : t2 == 97 ? Wk : Wv) + b * (6 * 4096), 6 * 8192);
            delay_until(t_start, DLYW);
#pragma unroll 4
            for (int i = t2; i < 128 * 24; i += 128) {
                const int e = (i >> 3) & 127, G = i >> 10, q = i & 7;
                cp16(sb + O_WO + G * 16384 + e * 128 + ((q ^ (e & 7) ^ ((h >> 1) & 1)) << 4), Wo + (size_t)(h * 128 + e) * DM + G * 192 + r * 64 + q * 8);
            }
            bar_sync(9, 384);
#pragma unroll
            for (int i = 0; i < 5; i++) {
                const int k = min(i * 128 + t2, DM - 1);
                const uint32_t ad = sb + O_MB + (k >> 3) * 256 + (k & 7) * 16;
                sts128(ad, m0[i][0], m0[i][1], m0[i][2], m0[i][3]); sts128(ad + 128, m0[i][0], m0[i][1], m0[i][2], m0[i][3]);
            }
            fence_async_smem();
        }
        auto arm = [&]() {
            const uint32_t ln = l16 >> 4;
            mbar_expect(bar + B_VX + (ln & 3) * 8, ln == 0 ? nv_remote * 2048 : ln == 1 ? nv_remote * 512 + 2560 : ln == 2 ? 6144 : 2048, ln < 4);
        };
        if (w == 3) arm();
        cluster_sync();
        TR1(3);
        const int L = w >> 1, hf = w & 1;
        const uint32_t rd = hf ? roff1 : roff0;
        const uint32_t rzero = gridDim.y + 100;
#define WOAD (sb + O_WO + ((l16 & 0x100) << 2) + ((l16 & 0x70) << 3) + (((w * 32) | ((l16 >> 3) & 16)) ^ (l16 & 0x70)))

        auto fetch_tile = [&](int u) {
            const bool a0 = u < NSEG, a1 = u >= LAG;
            mbar_expect(bar + B_X, ((int)a0 + (int)a1) * 36864, l16 == 0);
            const uint32_t off = r * 24576 + (l16 << 9) + (a0 ? 0 : 4096);
            asm volatile("{.reg .pred p; setp.lt.u32 p, %5, %6;\n"
                "@p cp.async.bulk.shared::cluster.global.mbarrier::complete_tx::bytes.multicast::cluster [%0], [%1], %4, [%2], %3;}"
                :: "r"(sb + O_H + off), "l"(reinterpret_cast<const char*>(g_xt + u * 4608) + off), "r"(bar + B_X), "h"((uint16_t)7),
                   "r"(a0 && a1 ? 24576 : 4096), "r"(l16), "r"(a0 && a1 ? 16 : 48) : "memory");
        };
        auto store_o = [&](int u) {
            asm volatile("{.reg .pred p; setp.eq.u32 p, %3, 0;\n"
                "@p cp.async.bulk.global.shared::cta.bulk_group [%0], [%1], %2;\n cp.async.bulk.commit_group;}"
                :: "l"(g_o + ((u & (RING - 1)) * 256 + h * 8 + 3 * r) * 128), "r"(sb + O_OS), "r"(nq * 2048), "r"(l16) : "memory");
            cnt_hint(g_cnt + (C_O + u * 8 + (h >> 2)) * 8, l16);
            TRG(u, 2);
        };
        bar_arrive(7, 384);
        if (w < 3) {
            bar_arrive(1 + w, 160); bar_arrive(12 + w, 160); if (w == 0) bar_arrive(8, 64);
            if (w < 2) {
                unsigned* pp = reinterpret_cast<unsigned*>(ex + inbox_off(b) + 16384 + w * 4096 + 2048);
                uint32_t best = ~0u, v = 0;
                if (lane == 0) {
#pragma unroll 1
                    for (int i = 0; i < 6; i++) {
                        const uint32_t c0 = clk();
                        v = atomicAdd(pp + (v >> 31), 0);
                        asm volatile("" :: "r"(v) : "memory");
                        sts32(bar + 80, v);
                        best = min(best, clk() - c0);
                    }
                    sts32(bar + 72 + w * 4, best);
                }
            }
            bar_sync(15, 96);
            const uint32_t xs = PLACE ? lds32(bar + 76) < lds32(bar + 72) : 0, ep = EP;
            side = PLACE ? xs ^ page_par(inbox_off(b)) : 0;
            rbase = ex + inbox_off(b) + xs * 4096;
            const uint32_t inv = (ep * (NT - 1)) & 1;
#pragma unroll
            for (int i = 0; i < 4; i++) stg128(rbase + (w == 2 ? 16384 : w * 2048) + i * 512 + lane * 16, inv, 0, 0, 0);
            __threadfence();
            bar_sync(15, 96);
            if (t2 == 0) stg_word(g_side + b, (ep + 1) * 2 + xs, true);
            TR1(4);
        } else {
            mbar_arrive_all3(bar + B_WIN, l16 >> 4);
            cnt_wait(g_cnt + C_X * 8, 64 * (EP + 1)); fence_async_global();
            TRG(0, 0);
            fetch_tile(0);
            TRG(0, 1);
        }
        cp_wait_all();
        bar_sync(6, 128);
        uint32_t poff;
        {
            const int rb = r * 32 + w * 8 + (lane >> 2);
            const uint32_t want = EP + 1;
            uint32_t v;
            for (int n = 0; __any_sync(~0u, ((v = ldg_word(g_side + rb)) >> 1) != want); n++) fault_if(n > POLL_LIMIT, n);
            __threadfence();
            poff = inbox_off(rb) + (v & 1) * 4096 + h * 64 + (lane & 3) * 16;
        }
        side = __shfl_sync(~0u, side, 0);
        const uint32_t roff = __shfl_sync(~0u, (uint32_t)(rbase - ex), 0) + (w == 2 ? 16384 : (w & 1) * 2048);
        bool late = true;
        uint4 a0[8];
#pragma unroll
        for (int kk = 0; kk < 8; kk++) a0[kk] = ldsm4t(WOAD + kk * 2048);
#pragma unroll 1
        for (int t = 0;; t++) {
            TR_ON(t);
            OPQ();
            mbar_wait(bar + B_EP, t & 1);
            uint4 kx[3][2], vx[4][2];
            const uint32_t lp = LSWAP;
#pragma unroll
            for (int m = 0; m < 3; m++) {
                kx[m][0] = ldsm4(sb + O_KX + m * 2048 + L * 1024 + lp);
                kx[m][1] = ldsm4(sb + O_KX + m * 2048 + L * 1024 + 512 + lp);
            }
            mbar_wait(bar + B_VX, t & 1);
            if (w == 3) {
                mbar_wait(bar + B_XFREE, t & 1);
                bar_sync(8, 64);
                TR(6);
                if (t > 0) store_o(t - 1);
                if (late) { cnt_wait(g_cnt + (C_X + t + 1) * 8, 64 * (EP + 1)); fence_async_global(); }
                TRG(t + 1, 0);
                if (t + 1 < NT) { fetch_tile(t + 1); TRG(t + 1, 1); }
                asm volatile("cp.async.bulk.wait_group.read 0;" ::: "memory");
                TR(7);
            }
            TR(0);
            bar_sync(4, 384);
            float s0[4] = {0, 0, 0, 0}, s1[4] = {0, 0, 0, 0}, sm[4] = {0, 0, 0, 0};
            {
                const uint4 q01 = ldsm4(sb + O_QM + L * 256 + l16 + (l16 & 256));
                const uint2 q2 = ldsm2(sb + O_QM + 1024 + L * 256 + l16);
                uint4 km_[3];
#pragma unroll
                for (int m = 0; m < 3; m++) km_[m] = ldsm4(sb + O_KM + m * 512 + (lp ^ (L << 8)));
                bar_arrive(5, 256);
                mma16(s0, kx[0][0].x, kx[0][0].y, kx[0][0].z, kx[0][0].w, q01.x, q01.y);
                mma16(s1, kx[0][1].x, kx[0][1].y, kx[0][1].z, kx[0][1].w, q01.x, q01.y);
                mma16(sm, km_[0].x, km_[0].y, km_[0].z, km_[0].w, q01.x, q01.y);
                mma16(s0, kx[1][0].x, kx[1][0].y, kx[1][0].z, kx[1][0].w, q01.z, q01.w);
                mma16(s1, kx[1][1].x, kx[1][1].y, kx[1][1].z, kx[1][1].w, q01.z, q01.w);
                mma16(sm, km_[1].x, km_[1].y, km_[1].z, km_[1].w, q01.z, q01.w);
                mma16(s0, kx[2][0].x, kx[2][0].y, kx[2][0].z, kx[2][0].w, q2.x, q2.y);
                mma16(s1, kx[2][1].x, kx[2][1].y, kx[2][1].z, kx[2][1].w, q2.x, q2.y);
                mma16(sm, km_[2].x, km_[2].y, km_[2].z, km_[2].w, q2.x, q2.y);
                const uint32_t ad = sb + O_SM + (1 - hf) * 1280 + L * 640 + rd;
                sta128(ad + l16, pk(s0[0], s0[1]), pk(s0[2], s0[3]), pk(s1[0], s1[1]), pk(s1[2], s1[3]), bar + B_SM + rd);
                sta32(ad + 512 + (l16 >> 2), pk(sm[0], sm[1]), bar + B_SM + rd);
            }
            TR(1);
            if (t + 1 == NT) break;
#pragma unroll
            for (int m = 0; m < 8; m++) vx[m >> 1][m & 1] = lds128(sb + O_VX + (hf * 4 + (m >> 1)) * 2048 + L * 1024 + (m & 1) * 512 + l16);
            const uint32_t tag = (t + EP * (NT - 1) + 1) & 1;
            mbar_wait(bar + B_SM, t & 1);
            TR(2);
            {
                const uint32_t ad = sb + O_SM + L * 640;
                const uint4 u = lds128(ad + l16), v = lds128(ad + 1280 + l16);
                const uint32_t x = lds32(ad + 512 + (l16 >> 2)), y = lds32(ad + 1280 + 512 + (l16 >> 2));
                s0[0] += bf_lo(u.x) + bf_lo(v.x); s0[1] += bf_hi(u.x) + bf_hi(v.x); s0[2] += bf_lo(u.y) + bf_lo(v.y); s0[3] += bf_hi(u.y) + bf_hi(v.y);
                s1[0] += bf_lo(u.z) + bf_lo(v.z); s1[1] += bf_hi(u.z) + bf_hi(v.z); s1[2] += bf_lo(u.w) + bf_lo(v.w); s1[3] += bf_hi(u.w) + bf_hi(v.w);
                sm[0] += bf_lo(x) + bf_lo(y); sm[1] += bf_hi(x) + bf_hi(y);
            }
            uint2 vm[4];
#pragma unroll
            for (int m = 0; m < 4; m++) vm[m] = lds64(sb + O_VM + (hf * 4 + m) * 512 + l16 + L * 8);
            float mx0 = fmaxf(fmaxf(fmaxf(s0[0], s0[2]), fmaxf(s1[0], s1[2])), sm[0]);
            float mx1 = fmaxf(fmaxf(fmaxf(s0[1], s0[3]), fmaxf(s1[1], s1[3])), sm[1]);
#pragma unroll
            for (int o = 4; o < 32; o <<= 1) { mx0 = fmaxf(mx0, __shfl_xor_sync(~0u, mx0, o)); mx1 = fmaxf(mx1, __shfl_xor_sync(~0u, mx1, o)); }
            mx0 *= -SC; mx1 *= -SC;
            s0[0] = ex2(fmaf(s0[0], SC, mx0)); s0[1] = ex2(fmaf(s0[1], SC, mx1));
            s0[2] = ex2(fmaf(s0[2], SC, mx0)); s0[3] = ex2(fmaf(s0[3], SC, mx1));
            const uint32_t pb0 = movm(pk(s0[0], s0[1])), pb1 = movm(pk(s0[2], s0[3]));
            s1[0] = ex2(fmaf(s1[0], SC, mx0)); s1[1] = ex2(fmaf(s1[1], SC, mx1));
            s1[2] = ex2(fmaf(s1[2], SC, mx0)); s1[3] = ex2(fmaf(s1[3], SC, mx1));
            const uint32_t pb2 = movm(pk(s1[0], s1[1])), pb3 = movm(pk(s1[2], s1[3]));
            sm[0] = ex2(fmaf(sm[0], SC, mx0)); sm[1] = ex2(fmaf(sm[1], SC, mx1));
            const uint32_t pm = movm(pk(sm[0], sm[1]));
            float l0 = (s0[0] + s0[2]) + (s1[0] + s1[2]) + sm[0], l1 = (s0[1] + s0[3]) + (s1[1] + s1[3]) + sm[1];
            float o[4][4];
#pragma unroll
            for (int m = 0; m < 4; m++) { o[m][0] = o[m][1] = o[m][2] = o[m][3] = 0.f; mma16(o[m], vx[m][0].x, vx[m][0].y, vx[m][0].z, vx[m][0].w, pb0, pb1); }
            l0 += __shfl_xor_sync(~0u, l0, 4); l1 += __shfl_xor_sync(~0u, l1, 4);
#pragma unroll
            for (int m = 0; m < 4; m++) mma16(o[m], vx[m][1].x, vx[m][1].y, vx[m][1].z, vx[m][1].w, pb2, pb3);
            l0 += __shfl_xor_sync(~0u, l0, 8); l1 += __shfl_xor_sync(~0u, l1, 8);
#pragma unroll
            for (int m = 0; m < 4; m++) mma8(o[m], vm[m].x, vm[m].y, pm);
            l0 += __shfl_xor_sync(~0u, l0, 16); l1 += __shfl_xor_sync(~0u, l1, 16);
            l0 = rcp(l0); l1 = rcp(l1);
#pragma unroll
            for (int m = 0; m < 4; m += 2)
                stsm4t(sb + O_OX + (hf * 4 + m) * 512 + (L ^ ((h >> 2) & 1)) * 256   + ((l16 & 0x100) << 1) + (l16 & 0xf0),
                       pk(o[m][0] * l0, o[m][1] * l1), pk(o[m][2] * l0, o[m][3] * l1), pk(o[m + 1][0] * l0, o[m + 1][1] * l1), pk(o[m + 1][2] * l0, o[m + 1][3] * l1));
            TR(3);
            char* const pdst = ex + poff;
            bar_sync(6, 128);
            {
                uint4 bo[8], a1[8];
                const uint32_t wad = WOAD;
#pragma unroll
                for (int kk = 0; kk < 8; kk++) bo[kk] = ldsm4(sb + O_OX + kk * 512 + l16);
#pragma unroll
                for (int G = 0; G < 3; G++) {
                    float e[4][4];
#pragma unroll
                    for (int q = 0; q < 4; q++) e[q][0] = e[q][1] = e[q][2] = e[q][3] = 0.f;
#pragma unroll
                    for (int kk = 0; kk < 8; kk++) {
                        const uint4 f = G == 0 ? a0[kk] : a1[kk];
                        mma16(e[(kk & 1) * 2], f.x, f.y, f.z, f.w, bo[kk].x, bo[kk].y);
                        mma16(e[(kk & 1) * 2 + 1], f.x, f.y, f.z, f.w, bo[kk].z, bo[kk].w);
                        if (G == 1) a1[kk] = ldsm4t(wad + 32768 + kk * 2048);
                        if (G == 0 && kk == FK) {
                            sched_fence(rzero, 2);
#pragma unroll
                            for (int j = 0; j < 8; j++) a1[j] = ldsm4t(wad + 16384 + j * 2048);
                        }
                    }
                    stg_pkt(pdst + (G == 2 ? 16384 : G * 2048), (pk(e[0][0] + e[2][0], e[0][1] + e[2][1]) & ~1u) | tag, pk(e[0][2] + e[2][2], e[0][3] + e[2][3]),
                            pk(e[1][0] + e[3][0], e[1][1] + e[3][1]), pk(e[1][2] + e[3][2], e[1][3] + e[3][3]));
                    if (G == 0) { TR(9); TRD(t, 0); }
                    if (G < 2) sched_fence(rzero, 3 + G);
                }
            }
            TR(4);
            if (w < 3) {
                bar_arrive(7, 384);
                OPQ();
                const uint32_t tagm = tag;
                uint32_t m0v = 0;
                if (t + 1 <= LAG) {
                    const unsigned short* m = reinterpret_cast<const unsigned short*>(mem0) + ((l16 >> 3) & 6) * DM + 192 * w + 16 * (b >> 3) + (b & 7) + ((l16 >> 4) & 8);
                    m0v = m[0] | (m[DM] << 16);
                }
                const char* const rsrc = ex + roff + l16;
                uint4 v[4];
                delay(DLY1);
#pragma unroll
                for (int i = 0; i < 4; i++) v[i] = ldg_pkt(rsrc + i * 512);
                for (int n = 0; __any_sync(~0u, lop_bad(lop_bad(0, v[0].x, v[1].x, tagm), v[2].x, v[3].x, tagm) & 1); n++) {
#pragma unroll
                    for (int i = 0; i < 4; i++) v[i] = ldg_pkt(rsrc + i * 512);
                    fault_if(n > POLL_LIMIT, n);
                }
                TR(5); TRD(t, 1);
                float s[8];
                s[4] = (bf_lo(v[0].z) + bf_lo(v[1].z)) + (bf_lo(v[2].z) + bf_lo(v[3].z)); s[5] = (bf_hi(v[0].z) + bf_hi(v[1].z)) + (bf_hi(v[2].z) + bf_hi(v[3].z));
                s[6] = (bf_lo(v[0].w) + bf_lo(v[1].w)) + (bf_lo(v[2].w) + bf_lo(v[3].w)); s[7] = (bf_hi(v[0].w) + bf_hi(v[1].w)) + (bf_hi(v[2].w) + bf_hi(v[3].w));
                s[2] = (bf_lo(v[0].y) + bf_lo(v[1].y)) + (bf_lo(v[2].y) + bf_lo(v[3].y)); s[3] = (bf_hi(v[0].y) + bf_hi(v[1].y)) + (bf_hi(v[2].y) + bf_hi(v[3].y));
                s[0] = (bf_lo(v[0].x) + bf_lo(v[1].x)) + (bf_lo(v[2].x) + bf_lo(v[3].x)); s[1] = (bf_hi(v[0].x) + bf_hi(v[1].x)) + (bf_hi(v[2].x) + bf_hi(v[3].x));
#pragma unroll
                for (int j = 0; j < 4; j++) s[j] += __shfl_xor_sync(~0u, s[j + 4], 16);
#pragma unroll
                for (int j = 0; j < 2; j++) s[j] += __shfl_xor_sync(~0u, s[j + 2], 8);
#pragma unroll
                for (int j = 0; j < 2; j++) s[j] += __shfl_xor_sync(~0u, s[j], 4);
                char* const mem_w = ex + mem_off(w, 0);
                uint32_t res = t + 1 <= LAG && l16 >= 256 ? m0v : pk(s[0], s[1]);
                if ((l16 & 48) == 0) res = (res & ~1u) | tag;
                stg_word(mem_w + (mem_off(0, b >> 3) - mem_off(0, 0)) + (b & 7) * 16 + (((l16 & 64) << 6) + ((l16 & 128) << 1) + ((l16 & 256) >> 1) + ((l16 >> 2) & 12)), res, true);
                TR(6); TRD(t, 2);
                delay(DLY2);
                const char* src = mem_w + (side ^ page_par(0x180000)) * 4096 + l16;
                const uint32_t gdst = sb + O_MB + w * 6144 + l16;
                uint4 x[12];
#pragma unroll
                for (int i = 0; i < 12; i++) x[i] = ldg_pkt(src + (mem_off(0, i) - mem_off(0, 0)));
                for (int n = 0;; n++) {
                    uint32_t bad = 0;
#pragma unroll
                    for (int i = 0; i < 12; i += 2) bad = lop_bad(bad, x[i].x, x[i + 1].x, tagm);
                    if (!__any_sync(~0u, bad & 1)) break;
#pragma unroll
                    for (int i = 0; i < 12; i++) ldg_pkt_retry(x[i], src + (mem_off(0, i) - mem_off(0, 0)), tagm);
                    fault_if(n > POLL_LIMIT, n);
                }
#pragma unroll
                for (int i = 0; i < 12; i++) sts128(gdst + i * 512, x[i].x, x[i].y, x[i].z, x[i].w);
                TR(7); TRD(t, 3);
                fence_async_smem();
                bar_arrive(12 + w, 160);
                bar_arrive(1 + w, 160);
                if (w == XST) bar_arrive(8, 64);
                TR(8);
            } else {
                bar_sync(7, 384);
                fence_async_smem();
                arm();
                __syncwarp();
                mbar_arrive_all3(bar + B_WIN, l16 >> 4);
                late = t + 2 < NT && cnt_poll(g_cnt + (C_X + t + 2) * 8, 64 * (EP + 1), bar + B_EP, (t + 1) & 1);
                fence_async_global();
                TR(5);
            }
        }
        if (w == 3) { bar_sync(7, 160); fence_async_smem(); store_o(NT - 1); asm volatile("cp.async.bulk.wait_group 0;" ::: "memory"); }
        cluster_sync();
    }
    TR_DUMP(b);
}

#define VG 12
#define HB 3
#define HA 2
#define HW 0
namespace ka {
constexpr int O_WA = 196608;
constexpr int A_KB = 21504;
constexpr int O_RING = 194560;
constexpr int O_BAR = 230400;
constexpr int SMEM = O_BAR + 256 + 1024;
constexpr float SC = 0.23570226039551584f * 1.4426950408889634f;
}

template <int NP, int KB = 4096>
DEVI void row_task(const uint4* res, const uint4* part, uint4* xout, char* img, int pos, int lane, uint32_t tag) {
    const bool on = lane < 24;
    const int ln = on ? lane : 0;
    uint4 rv[3], pv[NP > 0 ? NP * 3 : 1];
#pragma unroll
    for (int i = 0; i < 3; i++) rv[i] = ldg128(res + i * 24 + ln);
#pragma unroll
    for (int i = 0; i < NP * 3; i++) pv[i] = ldg_pkt(part + i * 24 + ln);
    if (NP > 0) validate<NP * 3>(pv, part + ln, 384, tag);
#pragma unroll
    for (int q = 0; q < NP * 3 / 2; q++) {
        const uint4 y = pv[q + NP * 3 / 2];
        pv[q] = make_uint4(add2(pv[q].x, y.x), add2(pv[q].y, y.y), add2(pv[q].z, y.z), add2(pv[q].w, y.w));
    }
    float x[24];
#pragma unroll
    for (int i = 0; i < 3; i++) {
        x[8 * i] = bf_lo(rv[i].x); x[8 * i + 1] = bf_hi(rv[i].x); x[8 * i + 2] = bf_lo(rv[i].y); x[8 * i + 3] = bf_hi(rv[i].y);
        x[8 * i + 4] = bf_lo(rv[i].z); x[8 * i + 5] = bf_hi(rv[i].z); x[8 * i + 6] = bf_lo(rv[i].w); x[8 * i + 7] = bf_hi(rv[i].w);
    }
    if (NP > 0) {
#pragma unroll
        for (int q = 0; q < NP * 3 / 2; q++) {
            const int i = q % 3;
            x[8 * i] += bf_lo(pv[q].x); x[8 * i + 1] += bf_hi(pv[q].x); x[8 * i + 2] += bf_lo(pv[q].y); x[8 * i + 3] += bf_hi(pv[q].y);
            x[8 * i + 4] += bf_lo(pv[q].z); x[8 * i + 5] += bf_hi(pv[q].z); x[8 * i + 6] += bf_lo(pv[q].w); x[8 * i + 7] += bf_hi(pv[q].w);
        }
#pragma unroll
        for (int i = 0; i < 3; i++) {
            uint32_t w[4];
#pragma unroll
            for (int j = 0; j < 4; j++) { w[j] = pk(x[8 * i + 2 * j], x[8 * i + 2 * j + 1]); x[8 * i + 2 * j] = bf_lo(w[j]); x[8 * i + 2 * j + 1] = bf_hi(w[j]); }
            stg128p(xout + i * 24 + ln, w[0], w[1], w[2], w[3], on);
        }
    }
    if (img) {
        float s = 0.f;
#pragma unroll
        for (int j = 0; j < 24; j++) s += x[j];
        if (!on) s = 0.f;
#pragma unroll
        for (int o = 1; o < 32; o <<= 1) s += __shfl_xor_sync(~0u, s, o);
        const float mean = s * (1.f / DM);
        float v = 0.f;
#pragma unroll
        for (int j = 0; j < 24; j++) { x[j] -= mean; v = fmaf(x[j], x[j], v); }
        if (!on) v = 0.f;
#pragma unroll
        for (int o = 1; o < 32; o <<= 1) v += __shfl_xor_sync(~0u, v, o);
        const float rs = rsqrtf(v * (1.f / DM) + 1e-5f);
        char* dst = img + (ln >> 3) * KB + pos * 128 + (((ln ^ pos) & 7) << 4);
#pragma unroll
        for (int i = 0; i < 3; i++)
            stg128p(dst + i * (3 * KB), pk(x[8 * i] * rs, x[8 * i + 1] * rs), pk(x[8 * i + 2] * rs, x[8 * i + 3] * rs),
                    pk(x[8 * i + 4] * rs, x[8 * i + 5] * rs), pk(x[8 * i + 6] * rs, x[8 * i + 7] * rs), on);
    }
}

DEVI void rows_a(const uint4* xin, int f, int i, int lane, uint32_t ep, int warp) {
    for (int u = 0; u < LAG; u++) cnt_hint(g_cnt + (C_X + u + (f ? 0 : NSEG)) * 8, lane);
#pragma unroll 1
    for (int seg = 0; seg < NSEG; seg++) {
        const int j = seg + f * LAGA, u = seg + f * LAG, row = seg * 32 + i;
        hint_wait(g_cnt + (C_WA + j * 4 + f * 2 + (i & 1)) * 8, 24 * (ep + 1));
        TRG(u, 0);
        row_task<4, 8192>((f ? g_x + 2048 * 72 : xin) + row * 72, g_pa + ((j & (RING - 1)) * 64 + f * 32 + i) * 288,
                    g_x + (f * 4096 + row) * 72, reinterpret_cast<char*>(g_xt + u * 4608 + f * 256), i, lane, ring_tag<NTA>(j, ep));
        TRG(u, 1);
        cnt_add(g_cnt + (C_X + u) * 8, lane);
        TRG(u, 2);
    }
}

__global__ void __launch_bounds__(384, 1)
k_aux(const __nv_bfloat16* __restrict__ x0, const __nv_bfloat16* __restrict__ wqkv, const __nv_bfloat16* __restrict__ wo,
      const __nv_bfloat16* __restrict__ Wo, __nv_bfloat16* __restrict__ out) {
    using namespace ka;
    extern __shared__ unsigned char smem_raw[];
    const uint32_t sb = (smem_u32(smem_raw) + 1023) & ~1023u;
    const int tid = threadIdx.x, lane = tid & 31, warp = __shfl_sync(~0u, tid >> 5, 0), g = lane >> 2, c = lane & 3;
    const int b = blockIdx.x;
    const uint32_t bar = sb + O_BAR;
    const uint32_t ep = __shfl_sync(~0u, ldg32(&g_epoch), 0);

    TRG(79, 0);
    const uint4* xin = reinterpret_cast<const uint4*>(x0);
    if (warp >= 8 || b == 35) {
        asm volatile("setmaxnreg.dec.sync.aligned.u32 128;");
        const int rw = b < 24 ? (warp - 8) * 24 + b : b < 35 ? (warp - 8) * 11 + b - 24 : 96 + 2 * warp;
        if (b < 24 || b == 35) {
#pragma unroll 1
            for (int row = rw; row < 2048; row += (row & 1) ? 23 : 1) {
                if (lane == 0 && b == 35 && row < 2024) prefetch_l2(xin + (row + 24) * 72, 1152);
                row_task<0>(xin + row * 72, nullptr, nullptr, reinterpret_cast<char*>(g_xa + (row >> 5) * 4608), (row & 1) * 16 + ((row & 31) >> 1), lane, 0);
                if (b < 24) { cnt_add(g_cnt + (C_N0 + (row >> 5)) * 8, lane); break; }
                if (row & 1) cnt_add<2>(g_cnt + (C_N0 + (row >> 5)) * 8, lane);
            }
        }
        if (rw < 32) {
            const int f = b < 24, i = rw;
#pragma unroll 1
            for (int seg = 0; seg < NSEG; seg++) {
                const int u = seg + f * LAG, row = seg * 32 + i;
                hint_wait(g_cnt + (C_WB + u * 4 + f * 2 + (i >> 4)) * 8, 24 * (ep + 1));
                TRG(u, 0);
                row_task<8>(g_x + (f * 4096 + row) * 72, g_pb + ((u & (RING - 1)) * 64 + f * 32 + i) * 576,
                            f ? reinterpret_cast<uint4*>(out) + row * 72 : g_x + (2048 + row) * 72,
                            f ? nullptr : reinterpret_cast<char*>(g_xa + (seg + LAGA) * 4608 + 2304), (i & 1) * 16 + (i >> 1), lane, ring_tag(u, ep));
                TRG(u, 1);
                cnt_add(g_cnt + (C_RB + f * NSEG + seg) * 8, lane);
                TRG(u, 2);
            }
            if (f && rw == 31) {
                asm volatile("griddepcontrol.wait;" ::: "memory");
                if (lane == 0) g_epoch = ep + 1;
            }
        } else if (rw < 64 && b < 24) rows_a(xin, 0, rw - 32, lane, ep, warp);
        return;
    }

    if (b < 24) {
        if (warp >= 4) {
            const int kq = b / 6, nq = b % 6;
            uint4 v[17];
#pragma unroll
            for (int q = 0; q < 17; q++) {
                const int it = q * 4 + warp - 4, kr = (it / 3) * 8 + g, s = kq * 11 + (kr >> 4), a = s >> 2, j = s & 3, e = kr & 15;
                const int head = 3 * a + (j < 3 ? j : e >> 1), row = head * 18 + (j < 3 ? e : 16 + (e & 1));
                v[q] = make_uint4(0, 0, 0, 0);
                if (it < 66 && head < 32 && (j < 3 || e < 6)) v[q] = *reinterpret_cast<const uint4*>(wo + row * DM + nq * 96 + (it % 3) * 32 + c * 8);
            }
#pragma unroll
            for (int q = 0; q < 17; q++) {
                const int it = q * 4 + warp - 4;
                const uint32_t ad = sb + O_WA + (it % 3) * 4 * 2816 + (it / 3) * 128 + lane * 4;
                if (it < 66) { sts32(ad, v[q].x); sts32(ad + 2816, v[q].y); sts32(ad + 2 * 2816, v[q].z); sts32(ad + 3 * 2816, v[q].w); }
            }
        } else {
            const int kg = b / 3, ng = b % 3;
            delay(DLYB);
#pragma unroll 1
            for (int bt = 0; bt < 4; bt++) {
                uint4 v[24];
#pragma unroll
                for (int q = 0; q < 24; q++)
                    v[q] = *reinterpret_cast<const uint4*>(Wo + (size_t)(kg * 512 + (bt * 4 + q / 6) * 32 + warp * 8 + g) * DM + ng * 192 + (q % 6) * 32 + c * 8);
#pragma unroll
                for (int q = 0; q < 24; q++) {
                    const uint32_t ad = sb + (q % 6) * 4 * 8192 + ((bt * 4 + q / 6) * 4 + warp) * 128 + lane * 4;
                    sts32(ad, v[q].x); sts32(ad + 8192, v[q].y); sts32(ad + 2 * 8192, v[q].z); sts32(ad + 3 * 8192, v[q].w);
                }
            }
        }
        fence_async_smem();
        bar_sync(2 + (warp >> 2), 128);
    } else {
        for (int i = tid; i < 2048; i += 256) sts128(sb + O_RING + i * 16, 0, 0, 0, 0);
        if (tid < 17) mbar_init(bar + tid * 8, tid >= 4 && tid < 8 ? 4 : 1);
        fence_async_smem();
        bar_sync(1, 256);
    }
    TRG(79, 1);
    const int wq = warp & 3;

    if (warp < 4) {
        asm volatile("setmaxnreg.inc.sync.aligned.u32 256;");
        if (b < 24) {
            const int kg = b / 3, ng = b % 3;
            const uint32_t blo = ((sb >> 4) & 0x3fff) | (8u << 16);
            uint4 a[32];
            bool pre = false;
#pragma unroll 1
            for (int u = 0; u < NT; u++) {
                const uint32_t tag = ring_tag(u, ep);
                const uint4* src = g_o + (((u & (RING - 1)) * 256 + kg * 32) * 4 + wq) * 32 + lane;
                if (!pre) {
                    hint_wait(g_cnt + (C_O + u * 8 + kg) * 8, 12 * (ep + 1));
#pragma unroll
                    for (int i = 0; i < VG; i++) a[i] = ldg_pkt(src + i * 128);
                }
                TRG(u, 0);
                float d[96];
                validate<VG>(a, src, 2048, tag);
#pragma unroll
                for (int i = VG; i < 32; i++) a[i] = ldg_pkt(src + i * 128);
                wg_fence();
#pragma unroll
                for (int i = 0; i < 32; i++) {
                    if (i == VG) { validate<32 - VG>(a + VG, src + VG * 128, 2048, tag); wg_fence(); }
                    wgmma_rs192t(d, a[i].x, a[i].y, a[i].z, a[i].w, mkdesc(blo + i * 16, 512), i > 0);
                    if (i == 23 || i == 31) wg_commit();
                }
                wg_wait<1>();
                pre = u + 1 < NT && __all_sync(~0u, ldg_word(g_cnt + (C_O + (u + 1) * 8 + kg) * 8) >= 12 * (ep + 1));
                if (pre) {
                    const uint4* nx = g_o + ((((u + 1) & (RING - 1)) * 256 + kg * 32) * 4 + wq) * 32 + lane;
#pragma unroll
                    for (int i = 0; i < VG; i++) a[i] = ldg_pkt(nx + i * 128);
                }
                wg_wait<0>();
                TRG(u, 1);
                uint4* dst = g_pb + (((u & (RING - 1)) * 64 + wq * 16 + g) * 8 + kg) * 72 + ng * 24 + c;
#pragma unroll
                for (int m = 0; m < 6; m++) {
                    if (m == HB) cnt_hint(g_cnt + (C_WB + u * 4 + wq) * 8, lane);
                    stg128(dst + 4 * m, (pk(d[16 * m], d[16 * m + 1]) & ~1u) | tag, pk(d[16 * m + 4], d[16 * m + 5]), pk(d[16 * m + 8], d[16 * m + 9]), pk(d[16 * m + 12], d[16 * m + 13]));
                    stg128(dst + 4 * m + 8 * 576, (pk(d[16 * m + 2], d[16 * m + 3]) & ~1u) | tag, pk(d[16 * m + 6], d[16 * m + 7]), pk(d[16 * m + 10], d[16 * m + 11]), pk(d[16 * m + 14], d[16 * m + 15]));
                }
                TRG(u, 3);
            }
        } else {
            const int a = b - 24, f = wq >> 1;
            const uint32_t blo = ((sb >> 4) & 0x3fff) | (8u << 16), alo = (((sb + O_RING) >> 4) & 0x3fff) | (1u << 16);
            const bool m0 = 2 * c <= g, m1 = 2 * c + 1 <= g;
            const uint32_t M = (m0 ? 0xffffu : 0u) | (m1 ? 0xffff0000u : 0u);
            uint32_t kh[7], vh[7];
#pragma unroll
            for (int i = 0; i < 7; i++) kh[i] = vh[i] = 0;
            int it = 0;
#pragma unroll 1
            for (int u = 0; u < NTA; u++) {
                float d[84];
#pragma unroll 1
                for (int kb = 0; kb < 9; kb++, it++) {
                    mbar_wait(bar + (it & 3) * 8, (it >> 2) & 1);
                    if (u == 0) mbar_wait(bar + 64 + kb * 8, 0);
                    if (kb == 0) TRG(u, 0);
                    wg_fence();
#pragma unroll
                    for (int q = 0; q < 4; q++)
                        wgmma_ss168t(d, mkdesc(alo + (it & 3) * 512 + q * 2, km::DESC_HI), mkdesc(blo + kb * (A_KB >> 4) + q * 16, 64), kb + q > 0);
                    wg_commit();
                    wg_wait<1>();
                    mbar_arrive(bar + 32 + ((it - 1) & 3) * 8, lane == 0 && kb > 0);
                }
                wg_wait<0>();
                mbar_arrive(bar + 32 + ((it - 1) & 3) * 8, lane == 0);
                TRG(u, 1);
                const bool first = u == f * LAGA;
                const uint32_t tag = ring_tag<NTA>(u, ep);
                const uint32_t qt0 = pk(d[72], d[73]), qt1 = pk(d[74], d[75]), kt0 = pk(d[76], d[77]), kt1 = pk(d[78], d[79]);
                const uint32_t vt0 = movm(pk(d[80], d[81])), vt1 = movm(pk(d[82], d[83]));
                float ot[4] = {0, 0, 0, 0};
                uint4* dst = g_oa + (((u & (RING - 1)) * 4 + wq) * 44 + a * 4) * 32 + lane;
#pragma unroll
                for (int h = 0; h < 3; h++) {
                    const float* q = d + 8 * h; const float* k = d + 24 + 8 * h; const float* v = d + 48 + 8 * h;
                    const uint32_t q0 = pk(q[0], q[1]), q1 = pk(q[2], q[3]), q2 = pk(q[4], q[5]), q3 = pk(q[6], q[7]);
                    const uint32_t k0 = pk(k[0], k[1]), k1 = pk(k[4], k[5]), k2 = pk(k[2], k[3]), k3 = pk(k[6], k[7]);
                    const uint32_t v0 = movm(pk(v[0], v[1])), v1 = movm(pk(v[2], v[3])), v2 = movm(pk(v[4], v[5])), v3 = movm(pk(v[6], v[7]));
                    const uint32_t t0 = c == h ? qt0 : 0, t1 = c == h ? qt1 : 0;
                    float sp[4] = {0, 0, 0, 0}, sl[4] = {0, 0, 0, 0}, sh[4] = {0, 0, 0, 0};
                    mma16(sp, q0, q1, q2, q3, kh[2 * h], kh[2 * h + 1]); mma16(sl, q0, q1, q2, q3, k0, k1); mma16(sh, q0, q1, q2, q3, k2, k3);
                    mma8(sp, t0, t1, kh[6]); mma8(sl, t0, t1, kt0); mma8(sh, t0, t1, kt1);
                    float x0_ = m0 ? sl[0] : first ? -INFINITY : sp[0], x1_ = m1 ? sl[1] : first ? -INFINITY : sp[1];
                    float y0_ = m0 ? sh[2] : sl[2], y1_ = m1 ? sh[3] : sl[3];
                    float mx = fmaxf(x0_, x1_), my = fmaxf(y0_, y1_);
#pragma unroll
                    for (int o = 1; o < 4; o <<= 1) { mx = fmaxf(mx, __shfl_xor_sync(~0u, mx, o)); my = fmaxf(my, __shfl_xor_sync(~0u, my, o)); }
                    mx *= -SC; my *= -SC;
                    x0_ = ex2(fmaf(x0_, SC, mx)); x1_ = ex2(fmaf(x1_, SC, mx)); y0_ = ex2(fmaf(y0_, SC, my)); y1_ = ex2(fmaf(y1_, SC, my));
                    float lx = x0_ + x1_, ly = y0_ + y1_;
#pragma unroll
                    for (int o = 1; o < 4; o <<= 1) { lx += __shfl_xor_sync(~0u, lx, o); ly += __shfl_xor_sync(~0u, ly, o); }
                    lx = rcp(lx); ly = rcp(ly);
                    const uint32_t px = pk(x0_ * lx, x1_ * lx), py = pk(y0_ * ly, y1_ * ly);
                    const uint32_t hm = (g >> 1) == h ? ~0u : 0u;
                    float o0[4] = {0, 0, 0, 0}, o1[4] = {0, 0, 0, 0};
                    mma16(o0, px & M, py & ~M, 0, py & M, v0, v1); mma16(o1, px & M, py & ~M, 0, py & M, v2, v3);
                    mma16(ot, px & M, py & ~M, 0, py & M, vt0 & hm, vt1 & hm);
                    mma8(o0, px & ~M, 0, vh[2 * h]); mma8(o1, px & ~M, 0, vh[2 * h + 1]); mma8(ot, px & ~M, 0, vh[6] & hm);
                    if (h == HA) cnt_hint(g_cnt + (C_A + u * 4 + wq) * 8, lane);
                    stg128(dst + h * 32, (pk(o0[0], o0[1]) & ~1u) | tag, pk(o0[2], o0[3]), pk(o1[0], o1[1]), pk(o1[2], o1[3]));
                    kh[2 * h] = k2; kh[2 * h + 1] = k3; vh[2 * h] = v1; vh[2 * h + 1] = v3;
                }
                kh[6] = kt1; vh[6] = vt1;
                stg128(dst + 96, (pk(ot[0], ot[1]) & ~1u) | tag, pk(ot[2], ot[3]), 0, 0);
                TRG(u, 2);
            }
        }
    } else {
        asm volatile("setmaxnreg.dec.sync.aligned.u32 120;");
        if (b < 24) {
            const int kq = b / 6, nq = b % 6;
            const uint32_t blo = (((sb + O_WA) >> 4) & 0x3fff) | (8u << 16);
#pragma unroll 1
            for (int u = 0; u < NTA; u++) {
                hint_wait(g_cnt + (C_A + u * 4 + wq) * 8, 11 * (ep + 1));
                const uint32_t tag = ring_tag<NTA>(u, ep);
                TRG(u, 0);
                const uint4* src = g_oa + (((u & (RING - 1)) * 4 + wq) * 44 + kq * 11) * 32 + lane;
                uint4 a[11];
                float d[48];
#pragma unroll
                for (int i = 0; i < 11; i++) a[i] = ldg_pkt(src + i * 32);
                validate<11>(a, src, 512, tag);
                wg_fence();
#pragma unroll
                for (int i = 0; i < 11; i++) wgmma_rs96t(d, a[i].x, a[i].y, a[i].z, a[i].w, mkdesc(blo + i * 16, 176), i > 0);
                wg_commit();
                wg_wait<0>();
                TRG(u, 1);
                uint4* dst = g_pa + (((u & (RING - 1)) * 64 + (wq >> 1) * 32 + 2 * g + (wq & 1)) * 4 + kq) * 72 + nq * 12 + c;
#pragma unroll
                for (int m = 0; m < 3; m++) {
                    if (m == HW) cnt_hint(g_cnt + (C_WA + u * 4 + wq) * 8, lane);
                    stg128(dst + 4 * m, (pk(d[16 * m], d[16 * m + 1]) & ~1u) | tag, pk(d[16 * m + 4], d[16 * m + 5]), pk(d[16 * m + 8], d[16 * m + 9]), pk(d[16 * m + 12], d[16 * m + 13]));
                    stg128(dst + 4 * m + 16 * 288, (pk(d[16 * m + 2], d[16 * m + 3]) & ~1u) | tag, pk(d[16 * m + 6], d[16 * m + 7]), pk(d[16 * m + 10], d[16 * m + 11]), pk(d[16 * m + 14], d[16 * m + 15]));
                }
                TRG(u, 3);
            }
        } else if (warp == 4) {
            mbar_expect(bar + 64 + lane * 8, A_KB, lane < 9);
            int it = 0;
#pragma unroll 1
            for (int u = 0; u < NTA; u++) {
                if (u == 0) { cnt_wait(g_cnt + C_W * 8, 96 * (ep + 1)); TRG(78, 0); }
                if (u < NSEG) cnt_wait(g_cnt + (C_N0 + u) * 8, 32 * (ep + 1));
                if (u > LAGA + LAG) cnt_wait(g_cnt + (C_RB + NSEG + u - LAGA - LAG - 1) * 8, 32 * (ep + 1));
                if (u >= LAGA) cnt_wait(g_cnt + (C_RB + u - LAGA) * 8, 32 * (ep + 1));
                TRG(u, 0);
                asm volatile("fence.proxy.async.global;" ::: "memory");
                const bool on = lane == 0 ? u < NSEG : lane == 1 && u >= LAGA;
#pragma unroll 1
                for (int kb = 0; kb < 9; kb++, it++) {
                    if (it >= 4) mbar_wait(bar + 32 + (it & 3) * 8, ((it >> 2) - 1) & 1);
                    mbar_expect(bar + (it & 3) * 8, u < NSEG && u >= LAGA ? 8192 : 4096, lane == 0);
                    asm volatile("{.reg .pred p; setp.ne.u32 p, %3, 0; @p cp.async.bulk.shared::cluster.global.mbarrier::complete_tx::bytes [%0], [%1], 4096, [%2];}"
                        :: "r"(sb + O_RING + (it & 3) * 8192 + (lane & 1) * 4096), "l"(g_xa + u * 4608 + (lane & 1) * 2304 + kb * 256), "r"(bar + (it & 3) * 8), "r"((uint32_t)on) : "memory");
                    if (u == 0) asm volatile("{.reg .pred p; setp.ne.u32 p, %4, 0; @p cp.async.bulk.shared::cluster.global.mbarrier::complete_tx::bytes [%0], [%1], %3, [%2];}"
                        :: "r"(sb + lane * A_KB), "l"(g_wa + ((b - 24) * 9 + lane) * (A_KB / 16)), "r"(bar + 64 + lane * 8), "n"(A_KB),
                           "r"((uint32_t)(lane < 9 && kb == (lane < 4 ? lane : lane < 6 ? 3 : lane - 2))) : "memory");
                }
            }
        } else if ((warp - 5) * 11 + b - 24 < 32) rows_a(xin, 1, (warp - 5) * 11 + b - 24, lane, ep, warp);
    }
}

extern "C" void kernel_launch(void* const* d_in, const int* in_sizes, int n_in, void* d_out, int out_size) {
    const __nv_bfloat16* x = (const __nv_bfloat16*)d_in[0];
    const __nv_bfloat16* wqkv = (const __nv_bfloat16*)d_in[1];
    const __nv_bfloat16* wo = (const __nv_bfloat16*)d_in[2];
    const __nv_bfloat16* mem0 = (const __nv_bfloat16*)d_in[4];
    const __nv_bfloat16* Wq = (const __nv_bfloat16*)d_in[5];
    const __nv_bfloat16* Wk = (const __nv_bfloat16*)d_in[6];
    const __nv_bfloat16* Wv = (const __nv_bfloat16*)d_in[7];
    const __nv_bfloat16* Wo = (const __nv_bfloat16*)d_in[8];
    cudaFuncSetAttribute(k_main, cudaFuncAttributeMaxDynamicSharedMemorySize, km::SMEM);
    cudaFuncSetAttribute(k_aux, cudaFuncAttributeMaxDynamicSharedMemorySize, ka::SMEM);
    cudaStream_t s = cudaStreamPerThread;
    k_main<<<96, 384, km::SMEM, s>>>(x, wqkv, wo, mem0, Wq, Wk, Wv, Wo);
    cudaLaunchConfig_t cfg = {};
    cudaLaunchAttribute at[1];
    at[0].id = cudaLaunchAttributeProgrammaticStreamSerialization;
    at[0].val.programmaticStreamSerializationAllowed = 1;
    cfg.stream = s; cfg.attrs = at; cfg.numAttrs = 1;
    cfg.gridDim = dim3(36); cfg.blockDim = dim3(384); cfg.dynamicSmemBytes = ka::SMEM;
    cudaLaunchKernelEx(&cfg, k_aux, x, wqkv, wo, Wo, (__nv_bfloat16*)d_out);
}
```

```cpp
#include <cuda_runtime.h>
#include <cuda_bf16.h>
#include <stdint.h>

#define LAG 7
constexpr int NSEG = 64;
constexpr int NT = NSEG + LAG;
#define AHEAD 1
constexpr int LAGA = LAG + AHEAD;
constexpr int NTA = NSEG + LAGA;
#define RING_ 8
constexpr int RING = RING_;
constexpr int DM = 576;

__device__ __align__(1024) uint4 g_xt[NT * 2 * 9 * 256];
__device__ __align__(1024) uint4 g_o[RING * 4 * 256 * 32];
__device__ __align__(1024) uint4 g_ex[2 * 131072];
__device__ unsigned g_side[96];
__device__ __align__(1024) uint4 g_pb[RING * 64 * 8 * 72];
__device__ __align__(1024) uint4 g_pa[RING * 64 * 4 * 72];
__device__ __align__(1024) uint4 g_oa[RING * 4 * 44 * 32];
__device__ __align__(1024) uint4 g_xa[NTA * 2 * 9 * 256];
__device__ __align__(1024) uint4 g_wa[11 * 9 * 21 * 64];
__device__ __align__(1024) uint4 g_x[3 * 2048 * 72];

constexpr int C_X = 0;
constexpr int C_O = C_X + NT;
constexpr int C_WB = C_O + NT * 8;
constexpr int C_RB = C_WB + NT * 4;
constexpr int C_A = C_RB + 2 * NSEG;
constexpr int C_WA = C_A + NTA * 4;
constexpr int C_N0 = C_WA + NTA * 4;
constexpr int C_W = C_N0 + NSEG;
constexpr int C_DONE = C_W + 1;
constexpr int C_TOTAL = C_DONE + 1;
__device__ __align__(1024) unsigned g_cnt[C_TOTAL * 8];
__device__ unsigned g_epoch;

#define TR(i)
#define TR1(i)
#define TR_ON(t)
#define TR_INIT(base)
#define TR_DUMP(slot)
#define TRG(t, i)
constexpr int TR_BYTES = 0;

#define DEVI __device__ __forceinline__
DEVI uint32_t smem_u32(const void* p) { return (uint32_t)__cvta_generic_to_shared(p); }
DEVI uint32_t pk(float lo, float hi) { uint32_t r; asm("cvt.rn.bf16x2.f32 %0, %1, %2;" : "=r"(r) : "f"(hi), "f"(lo)); return r; }
DEVI float bf_lo(uint32_t u) { return __uint_as_float(u << 16); }
DEVI float bf_hi(uint32_t u) { return __uint_as_float(u & 0xffff0000u); }
DEVI uint32_t add2(uint32_t a, uint32_t b) { uint32_t d; asm("add.rn.bf16x2 %0, %1, %2;" : "=r"(d) : "r"(a), "r"(b)); return d; }
DEVI uint32_t movm(uint32_t a) { uint32_t d; asm volatile("movmatrix.sync.aligned.m8n8.trans.b16 %0, %1;" : "=r"(d) : "r"(a)); return d; }
DEVI float2 shfl2(float a, float b, int o) {
    float2 r; asm volatile("shfl.sync.bfly.b32 %0, %2, %4, 31, -1; shfl.sync.bfly.b32 %1, %3, %4, 31, -1;" : "=&f"(r.x), "=f"(r.y) : "f"(a), "f"(b), "r"(o)); return r;
}
DEVI float ex2(float x) { float y; asm("ex2.approx.ftz.f32 %0, %1;" : "=f"(y) : "f"(x)); return y; }
DEVI float rcp(float x) { float y; asm("rcp.approx.ftz.f32 %0, %1;" : "=f"(y) : "f"(x)); return y; }
DEVI void mma16(float (&d)[4], uint32_t a0, uint32_t a1, uint32_t a2, uint32_t a3, uint32_t b0, uint32_t b1) {
    asm volatile("mma.sync.aligned.m16n8k16.row.col.f32.bf16.bf16.f32 {%0,%1,%2,%3}, {%4,%5,%6,%7}, {%8,%9}, {%0,%1,%2,%3};"
        : "+f"(d[0]), "+f"(d[1]), "+f"(d[2]), "+f"(d[3]) : "r"(a0), "r"(a1), "r"(a2), "r"(a3), "r"(b0), "r"(b1));
}
DEVI void mma8(float (&d)[4], uint32_t a0, uint32_t a1, uint32_t b0) {
    asm volatile("mma.sync.aligned.m16n8k8.row.col.f32.bf16.bf16.f32 {%0,%1,%2,%3}, {%4,%5}, {%6}, {%0,%1,%2,%3};"
        : "+f"(d[0]), "+f"(d[1]), "+f"(d[2]), "+f"(d[3]) : "r"(a0), "r"(a1), "r"(b0));
}
DEVI uint4 lds128(uint32_t a) { uint4 v; asm volatile("ld.shared.v4.u32 {%0,%1,%2,%3}, [%4];" : "=r"(v.x), "=r"(v.y), "=r"(v.z), "=r"(v.w) : "r"(a) : "memory"); return v; }
DEVI uint2 lds64(uint32_t a) { uint2 v; asm volatile("ld.shared.v2.u32 {%0,%1}, [%2];" : "=r"(v.x), "=r"(v.y) : "r"(a) : "memory"); return v; }
DEVI uint32_t lds32(uint32_t a) { uint32_t v; asm volatile("ld.shared.u32 %0, [%1];" : "=r"(v) : "r"(a) : "memory"); return v; }
DEVI uint32_t lds32v(uint32_t a) { uint32_t v; asm volatile("ld.volatile.shared.u32 %0, [%1];" : "=r"(v) : "r"(a) : "memory"); return v; }
DEVI uint4 lds128v(uint32_t a) { uint4 v; asm volatile("ld.volatile.shared.v4.u32 {%0,%1,%2,%3}, [%4];" : "=r"(v.x), "=r"(v.y), "=r"(v.z), "=r"(v.w) : "r"(a) : "memory"); return v; }
DEVI uint32_t lds16(uint32_t a) { uint32_t v; asm volatile("ld.shared.u16 %0, [%1];" : "=r"(v) : "r"(a) : "memory"); return v; }
DEVI uint4 ldsm4(uint32_t a) { uint4 v; asm volatile("ldmatrix.sync.aligned.m8n8.x4.shared.b16 {%0,%1,%2,%3}, [%4];" : "=r"(v.x), "=r"(v.y), "=r"(v.z), "=r"(v.w) : "r"(a) : "memory"); return v; }
DEVI uint4 ldsm4p(uint32_t a, bool pred) {
    uint4 v; asm volatile("{.reg .pred p; setp.ne.u32 p, %5, 0; @p ldmatrix.sync.aligned.m8n8.x4.shared.b16 {%0,%1,%2,%3}, [%4];}" : "=r"(v.x), "=r"(v.y), "=r"(v.z), "=r"(v.w) : "r"(a), "r"((uint32_t)pred) : "memory"); return v;
}
DEVI uint4 ldsm4t(uint32_t a) { uint4 v; asm volatile("ldmatrix.sync.aligned.m8n8.x4.trans.shared.b16 {%0,%1,%2,%3}, [%4];" : "=r"(v.x), "=r"(v.y), "=r"(v.z), "=r"(v.w) : "r"(a) : "memory"); return v; }
DEVI uint2 ldsm2(uint32_t a) { uint2 v; asm volatile("ldmatrix.sync.aligned.m8n8.x2.shared.b16 {%0,%1}, [%2];" : "=r"(v.x), "=r"(v.y) : "r"(a) : "memory"); return v; }
DEVI void stsm4t(uint32_t a, uint32_t x, uint32_t y, uint32_t z, uint32_t w) { asm volatile("stmatrix.sync.aligned.m8n8.x4.trans.shared.b16 [%0], {%1,%2,%3,%4};" :: "r"(a), "r"(x), "r"(y), "r"(z), "r"(w) : "memory"); }
DEVI void sts128(uint32_t a, uint32_t x, uint32_t y, uint32_t z, uint32_t w) { asm volatile("st.shared.v4.u32 [%0], {%1,%2,%3,%4};" :: "r"(a), "r"(x), "r"(y), "r"(z), "r"(w) : "memory"); }
DEVI void sts64(uint32_t a, uint32_t x, uint32_t y) { asm volatile("st.shared.v2.u32 [%0], {%1,%2};" :: "r"(a), "r"(x), "r"(y) : "memory"); }
DEVI void sts32(uint32_t a, uint32_t x) { asm volatile("st.shared.u32 [%0], %1;" :: "r"(a), "r"(x) : "memory"); }
DEVI void sts32p(uint32_t a, uint32_t x, bool pred) { asm volatile("{.reg .pred p; setp.ne.u32 p, %2, 0; @p st.shared.u32 [%0], %1;}" :: "r"(a), "r"(x), "r"((uint32_t)pred) : "memory"); }
DEVI void sta128(uint32_t a, uint32_t x, uint32_t y, uint32_t z, uint32_t w, uint32_t bar) {
    asm volatile("st.async.weak.shared::cluster.mbarrier::complete_tx::bytes.v4.b32 [%0], {%1,%2,%3,%4}, [%5];" :: "r"(a), "r"(x), "r"(y), "r"(z), "r"(w), "r"(bar) : "memory");
}
DEVI void sta128p(uint32_t a, uint32_t x, uint32_t y, uint32_t z, uint32_t w, uint32_t bar, bool pred) {
    asm volatile("{.reg .pred p; setp.ne.u32 p, %6, 0; @p st.async.weak.shared::cluster.mbarrier::complete_tx::bytes.v4.b32 [%0], {%1,%2,%3,%4}, [%5];}" :: "r"(a), "r"(x), "r"(y), "r"(z), "r"(w), "r"(bar), "r"((uint32_t)pred) : "memory");
}
DEVI void sta64(uint32_t a, uint32_t x, uint32_t y, uint32_t bar) {
    asm volatile("st.async.weak.shared::cluster.mbarrier::complete_tx::bytes.v2.b32 [%0], {%1,%2}, [%3];" :: "r"(a), "r"(x), "r"(y), "r"(bar) : "memory");
}
DEVI void sta32(uint32_t a, uint32_t x, uint32_t bar) {
    asm volatile("st.async.weak.shared::cluster.mbarrier::complete_tx::bytes.b32 [%0], %1, [%2];" :: "r"(a), "r"(x), "r"(bar) : "memory");
}
DEVI uint4 ldg_pkt(const void* p) {
    uint4 v;
    asm volatile("ld.relaxed.gpu.global.v4.u32 {%0,%1,%2,%3}, [%4];" : "=r"(v.x), "=r"(v.y), "=r"(v.z), "=r"(v.w) : "l"(p) : "memory");
    return v;
}
DEVI void ldg_pkt_if(uint4& v, const void* p, bool pred) {
    asm volatile("{.reg .pred p; setp.ne.u32 p, %5, 0; @p ld.relaxed.gpu.global.v4.u32 {%0,%1,%2,%3}, [%4];}"
        : "+r"(v.x), "+r"(v.y), "+r"(v.z), "+r"(v.w) : "l"(p), "r"((uint32_t)pred) : "memory");
}
DEVI void ldg_pkt_retry(uint4& v, const void* p, uint32_t tag) {
    asm volatile("{.reg .pred p; .reg .b32 t; lop3.b32 t, %0, %5, 1, 0x28; setp.ne.u32 p, t, 0; @p ld.relaxed.gpu.global.v4.u32 {%0,%1,%2,%3}, [%4];}"
        : "+r"(v.x), "+r"(v.y), "+r"(v.z), "+r"(v.w) : "l"(p), "r"(tag) : "memory");
}
DEVI void stg_pkt(void* p, uint32_t x, uint32_t y, uint32_t z, uint32_t w) {
    asm volatile("st.relaxed.gpu.global.v4.u32 [%0], {%1,%2,%3,%4};" :: "l"(p), "r"(x), "r"(y), "r"(z), "r"(w) : "memory");
}
DEVI uint32_t ldg_word(const void* p) { uint32_t v; asm volatile("ld.relaxed.gpu.global.u32 %0, [%1];" : "=r"(v) : "l"(p) : "memory"); return v; }
DEVI void stg_word(void* p, uint32_t x, bool pred) {
    asm volatile("{.reg .pred p; setp.ne.u32 p, %2, 0; @p st.relaxed.gpu.global.u32 [%0], %1;}" :: "l"(p), "r"(x), "r"((uint32_t)pred) : "memory");
}
DEVI uint2 ldg64nc(const void* p) { uint2 v; asm volatile("ld.global.nc.L1::no_allocate.v2.u32 {%0,%1}, [%2];" : "=r"(v.x), "=r"(v.y) : "l"(p)); return v; }
DEVI void prefetch_l2(const void* p, uint32_t bytes) { asm volatile("cp.async.bulk.prefetch.L2.global [%0], %1;" :: "l"(p), "r"(bytes) : "memory"); }
DEVI uint4 ldg128(const void* p) { uint4 v; asm volatile("ld.global.cg.v4.u32 {%0,%1,%2,%3}, [%4];" : "=r"(v.x), "=r"(v.y), "=r"(v.z), "=r"(v.w) : "l"(p) : "memory"); return v; }
DEVI uint2 ldg64(const void* p) { uint2 v; asm volatile("ld.global.cg.v2.u32 {%0,%1}, [%2];" : "=r"(v.x), "=r"(v.y) : "l"(p) : "memory"); return v; }
DEVI uint32_t ldg32(const void* p) { uint32_t v; asm volatile("ld.global.cg.u32 %0, [%1];" : "=r"(v) : "l"(p) : "memory"); return v; }
DEVI void stg128(void* p, uint32_t x, uint32_t y, uint32_t z, uint32_t w) { asm volatile("st.global.cg.v4.u32 [%0], {%1,%2,%3,%4};" :: "l"(p), "r"(x), "r"(y), "r"(z), "r"(w) : "memory"); }
DEVI void stg128p(void* p, uint32_t x, uint32_t y, uint32_t z, uint32_t w, bool pred) { asm volatile("{.reg .pred p; setp.ne.u32 p, %5, 0; @p st.global.cg.v4.u32 [%0], {%1,%2,%3,%4};}" :: "l"(p), "r"(x), "r"(y), "r"(z), "r"(w), "r"((uint32_t)pred) : "memory"); }
DEVI void stg64(void* p, uint32_t x, uint32_t y) { asm volatile("st.global.cg.v2.u32 [%0], {%1,%2};" :: "l"(p), "r"(x), "r"(y) : "memory"); }
DEVI void stg32(void* p, uint32_t x) { asm volatile("st.global.cg.u32 [%0], %1;" :: "l"(p), "r"(x) : "memory"); }
DEVI void cp16(uint32_t dst, const void* src) { asm volatile("cp.async.cg.shared.global [%0], [%1], 16;" :: "r"(dst), "l"(src) : "memory"); }
DEVI void cp16_if(uint32_t dst, const void* src, bool pred) { asm volatile("{.reg .pred p; setp.ne.u32 p, %2, 0; @p cp.async.cg.shared.global [%0], [%1], 16;}" :: "r"(dst), "l"(src), "r"((uint32_t)pred) : "memory"); }
DEVI void cp_commit() { asm volatile("cp.async.commit_group;" ::: "memory"); }
DEVI void cp4(uint32_t dst, const void* src) { asm volatile("cp.async.ca.shared.global [%0], [%1], 4;" :: "r"(dst), "l"(src) : "memory"); }
template <int N> DEVI void cp_wait() { asm volatile("cp.async.wait_group %0;" :: "n"(N) : "memory"); }
DEVI void cp_wait_all() { asm volatile("cp.async.wait_all;" ::: "memory"); }
DEVI void bar_sync(int id, int n) { asm volatile("bar.sync %0, %1;" :: "r"(id), "r"(n) : "memory"); }
DEVI void bar_arrive(int id, int n) { asm volatile("bar.arrive %0, %1;" :: "r"(id), "r"(n) : "memory"); }
DEVI void fence_async_smem() { asm volatile("fence.proxy.async.shared::cta;" ::: "memory"); }
DEVI void fence_async_global() { asm volatile("fence.proxy.async.global;" ::: "memory"); }
DEVI void mbar_init(uint32_t b, int n) { asm volatile("mbarrier.init.shared.b64 [%0], %1;" :: "r"(b), "r"(n) : "memory"); }
DEVI void mbar_expect(uint32_t b, uint32_t bytes, bool pred) {
    asm volatile("{.reg .pred p; setp.ne.u32 p, %2, 0; @p mbarrier.arrive.expect_tx.shared.b64 _, [%0], %1;}" :: "r"(b), "r"(bytes), "r"((uint32_t)pred) : "memory");
}
DEVI void mbar_arrive(uint32_t b, bool pred) { asm volatile("{.reg .pred p; setp.ne.u32 p, %1, 0; @p mbarrier.arrive.shared.b64 _, [%0];}" :: "r"(b), "r"((uint32_t)pred) : "memory"); }
DEVI void mbar_arrive_all3(uint32_t b, uint32_t lane) {
    asm volatile("{.reg .pred p; .reg .u32 a; setp.lt.u32 p, %1, 3; @p mapa.shared::cluster.u32 a, %0, %1; @p mbarrier.arrive.relaxed.cluster.shared::cluster.b64 _, [a];}" :: "r"(b), "r"(lane) : "memory");
}
#define FAULT "or.b32 n, n, 1; st.volatile.shared.u32 [n], n;\n"
#define LIM1 "400000"
#define LIM2 "2000000"
DEVI void fault_if(bool p, uint32_t n) { asm volatile("{.reg .pred p; setp.ne.u32 p, %0, 0; @p st.volatile.shared.u32 [%1], %1;}" :: "r"((uint32_t)p), "r"(n | 1) : "memory"); }
DEVI void mbar_wait(uint32_t b, uint32_t parity) {
    asm volatile("{.reg .pred p; .reg .u32 n;\n"
        "mbarrier.try_wait.parity.shared::cta.b64 p, [%0], %1;\n"
        "@p bra.uni D%=;\n"
        "mov.u32 n, 0;\n"
        "W%=: mbarrier.try_wait.parity.shared::cta.b64 p, [%0], %1;\n"
        "@p bra.uni D%=;\n"
        "add.u32 n, n, 1; setp.lt.u32 p, n, " LIM1 "; @p bra.uni W%=;\n"
        FAULT
        "D%=:}" :: "r"(b), "r"(parity) : "memory");
}
constexpr int POLL_LIMIT = 2000000;
DEVI void cnt_wait(const unsigned* c, unsigned target) {
    asm volatile("{.reg .pred p; .reg .u32 n, v;\n"
        "ld.acquire.gpu.global.u32 v, [%0];\n"
        "setp.ge.u32 p, v, %1; vote.sync.all.pred p, p, 0xffffffff; @p bra.uni D%=;\n"
        "mov.u32 n, 0;\n"
        "W%=: ld.acquire.gpu.global.u32 v, [%0];\n"
        "setp.ge.u32 p, v, %1; vote.sync.all.pred p, p, 0xffffffff; @p bra.uni D%=;\n"
        "add.u32 n, n, 1; setp.lt.u32 p, n, " LIM2 "; @p bra.uni W%=;\n"
        FAULT
        "D%=:}" :: "l"(c), "r"(target) : "memory");
}
DEVI void hint_wait(const unsigned* c, unsigned target) {
    asm volatile("{.reg .pred p; .reg .u32 n, v;\n"
        "ld.relaxed.gpu.global.u32 v, [%0];\n"
        "setp.ge.u32 p, v, %1; vote.sync.all.pred p, p, 0xffffffff; @p bra.uni D%=;\n"
        "mov.u32 n, 0;\n"
        "W%=: ld.relaxed.gpu.global.u32 v, [%0];\n"
        "setp.ge.u32 p, v, %1; vote.sync.all.pred p, p, 0xffffffff; @p bra.uni D%=;\n"
        "add.u32 n, n, 1; setp.lt.u32 p, n, " LIM2 "; @p bra.uni W%=;\n"
        FAULT
        "D%=:}" :: "l"(c), "r"(target) : "memory");
}
DEVI bool cnt_poll(const unsigned* c, unsigned target, uint32_t b, uint32_t parity) {
    uint32_t r;
    asm volatile("{.reg .pred p; .reg .u32 n, v;\n"
        "mov.u32 n, 0; mov.u32 %0, 0;\n"
        "W%=: ld.acquire.gpu.global.u32 v, [%1];\n"
        "setp.ge.u32 p, v, %2; vote.sync.all.pred p, p, 0xffffffff; @p bra.uni D%=;\n"
        "mbarrier.test_wait.parity.shared::cta.b64 p, [%3], %4;\n"
        "add.u32 n, n, 1; setp.gt.or.u32 p, n, 1000, p; vote.sync.any.pred p, p, 0xffffffff; @!p bra.uni W%=;\n"
        "mov.u32 %0, 1;\n"
        "D%=:}" : "=r"(r) : "l"(c), "r"(target), "r"(b), "r"(parity) : "memory");
    return r;
}
template <int N = 1> DEVI void cnt_add(unsigned* c, int lane) {
    asm volatile("{.reg .pred p; setp.eq.u32 p, %1, 0; fence.acq_rel.gpu; bar.warp.sync 0xffffffff; @p red.relaxed.gpu.global.add.u32 [%0], %2;}" :: "l"(c + lane), "r"(lane), "n"(N) : "memory");
}
DEVI void cnt_hint(unsigned* c, int lane) {
    asm volatile("{.reg .pred p; setp.eq.u32 p, %1, 0; @p red.relaxed.gpu.global.add.u32 [%0], 1;}" :: "l"(c + lane), "r"(lane) : "memory");
}
template <int N = NT> DEVI uint32_t ring_tag(unsigned u, uint32_t ep) { return (u / RING + ep * ((N - 1 - u % RING) / RING + 1) + 1) & 1; }
static_assert(RING >= LAGA && RING > LAG, "ring too short");
DEVI uint32_t lop_bad(uint32_t acc, uint32_t x, uint32_t y, uint32_t tag) {
    uint32_t d; asm("{.reg .b32 t; lop3.b32 t, %2, %3, %4, 0x7e; or.b32 %0, t, %1;}" : "=r"(d) : "r"(acc), "r"(x), "r"(y), "r"(tag)); return d;
}
template <int N> DEVI void validate(uint4* v, const void* p, int step, uint32_t tag) {
    for (int n = 0;; n++) {
        uint32_t bad = 0;
#pragma unroll
        for (int i = 0; i < N; i += 2) bad = lop_bad(bad, v[i].x, v[i + 1 < N ? i + 1 : i].x, tag);
        if (!__any_sync(~0u, bad & 1)) break;
#pragma unroll
        for (int i = 0; i < N; i++) ldg_pkt_retry(v[i], static_cast<const char*>(p) + i * step, tag);
        fault_if(n > POLL_LIMIT, n);
    }
}
DEVI uint32_t page_par(uint32_t off) { return __popc((off >> 12) & 0xb2) & 1; }
DEVI uint32_t inbox_off(int b) { return (b >> 1) * 32768 + (b & 1) * 8192; }
DEVI uint32_t mem_off(int w, int i) { return 0x180000 + w * 1024 + (i & 1) * 512 + (i & 3) * 16384 + (i < 4 ? 0 : i < 8 ? 0x30000 : 0x40000); }
DEVI void sched_fence(uint32_t zero, uint32_t id) { asm volatile("{.reg .pred p; setp.ne.u32 p, %0, %1; @p bra.uni D%=; exit; D%=:}" :: "r"(zero), "r"(id) : "memory"); }
DEVI uint32_t clk() { uint32_t c; asm volatile("mov.u32 %0, %%clock;" : "=r"(c) :: "memory"); return c; }
DEVI void delay(uint32_t n) {
    if (n) asm volatile("{.reg .pred p; .reg .u32 c, e; mov.u32 e, %%clock;\n W%=: mov.u32 c, %%clock; sub.u32 c, c, e; setp.lt.u32 p, c, %0; @p bra.uni W%=;}" :: "r"(n) : "memory");
}
DEVI void delay_until(uint32_t t0, uint32_t n) {
    asm volatile("{.reg .pred p; .reg .u32 c;\n W%=: mov.u32 c, %%clock; sub.u32 c, c, %1; setp.lt.u32 p, c, %0; @p bra.uni W%=;}" :: "r"(n), "r"(t0) : "memory");
}
DEVI void wg_fence() { asm volatile("wgmma.fence.sync.aligned;" ::: "memory"); }
DEVI void wg_commit() { asm volatile("wgmma.commit_group.sync.aligned;" ::: "memory"); }
template <int N> DEVI void wg_wait() { asm volatile("wgmma.wait_group.sync.aligned %0;" :: "n"(N) : "memory"); }
DEVI uint64_t mkdesc(uint32_t lo, uint32_t hi) { uint64_t d; asm("mov.b64 %0, {%1,%2};" : "=l"(d) : "r"(lo), "r"(hi)); return d; }
DEVI void cluster_arrive() { asm volatile("barrier.cluster.arrive.relaxed.aligned;" ::: "memory"); }
DEVI void cluster_wait() { asm volatile("barrier.cluster.wait.aligned;" ::: "memory"); }
DEVI void cluster_sync() { asm volatile("barrier.cluster.arrive.aligned;\n barrier.cluster.wait.aligned;" ::: "memory"); }
DEVI void wgmma_ss16t(float (&d)[8], uint64_t da, uint64_t db, int acc) {
    asm volatile("{.reg .pred p; setp.ne.b32 p, %10, 0;\n"
        "wgmma.mma_async.sync.aligned.m64n16k16.f32.bf16.bf16 {%0,%1,%2,%3,%4,%5,%6,%7}, %8, %9, p, 1, 1, 0, 1;}"
        : "+f"(d[0]), "+f"(d[1]), "+f"(d[2]), "+f"(d[3]), "+f"(d[4]), "+f"(d[5]), "+f"(d[6]), "+f"(d[7])
        : "l"(da), "l"(db), "r"(acc));
}
DEVI void wgmma_ss16a(float (&d)[8], uint64_t da, uint64_t db, int acc) {
    asm volatile("{.reg .pred p; setp.ne.b32 p, %10, 0;\n"
        "wgmma.mma_async.sync.aligned.m64n16k16.f32.bf16.bf16 {%0,%1,%2,%3,%4,%5,%6,%7}, %8, %9, p, 1, 1, 1, 0;}"
        : "+f"(d[0]), "+f"(d[1]), "+f"(d[2]), "+f"(d[3]), "+f"(d[4]), "+f"(d[5]), "+f"(d[6]), "+f"(d[7])
        : "l"(da), "l"(db), "r"(acc));
}
DEVI void wgmma_ss64(float (&d)[32], uint64_t da, uint64_t db, int acc) {
    asm volatile("{.reg .pred p; setp.ne.b32 p, %34, 0;\n"
        "wgmma.mma_async.sync.aligned.m64n64k16.f32.bf16.bf16 {%0,%1,%2,%3,%4,%5,%6,%7,%8,%9,%10,%11,%12,%13,%14,%15,%16,%17,%18,%19,%20,%21,%22,%23,%24,%25,%26,%27,%28,%29,%30,%31}, %32, %33, p, 1, 1, 0, 0;}"
        : "+f"(d[0]), "+f"(d[1]), "+f"(d[2]), "+f"(d[3]), "+f"(d[4]), "+f"(d[5]), "+f"(d[6]), "+f"(d[7]), "+f"(d[8]), "+f"(d[9]), "+f"(d[10]), "+f"(d[11]), "+f"(d[12]), "+f"(d[13]), "+f"(d[14]), "+f"(d[15]), "+f"(d[16]), "+f"(d[17]), "+f"(d[18]), "+f"(d[19]), "+f"(d[20]), "+f"(d[21]), "+f"(d[22]), "+f"(d[23]), "+f"(d[24]), "+f"(d[25]), "+f"(d[26]), "+f"(d[27]), "+f"(d[28]), "+f"(d[29]), "+f"(d[30]), "+f"(d[31])
        : "l"(da), "l"(db), "r"(acc));
}
DEVI void wgmma_rs16t(float (&d)[8], uint32_t a0, uint32_t a1, uint32_t a2, uint32_t a3, uint64_t db, int acc) {
    asm volatile("{.reg .pred p; setp.ne.b32 p, %13, 0;\n"
        "wgmma.mma_async.sync.aligned.m64n16k16.f32.bf16.bf16 {%0,%1,%2,%3,%4,%5,%6,%7}, {%8,%9,%10,%11}, %12, p, 1, 1, 1;}"
        : "+f"(d[0]), "+f"(d[1]), "+f"(d[2]), "+f"(d[3]), "+f"(d[4]), "+f"(d[5]), "+f"(d[6]), "+f"(d[7])
        : "r"(a0), "r"(a1), "r"(a2), "r"(a3), "l"(db), "r"(acc));
}
DEVI void wgmma_rs64(float (&d)[32], uint32_t a0, uint32_t a1, uint32_t a2, uint32_t a3, uint64_t db, int acc) {
    asm volatile("{.reg .pred p; setp.ne.b32 p, %37, 0;\n"
        "wgmma.mma_async.sync.aligned.m64n64k16.f32.bf16.bf16 {%0,%1,%2,%3,%4,%5,%6,%7,%8,%9,%10,%11,%12,%13,%14,%15,%16,%17,%18,%19,%20,%21,%22,%23,%24,%25,%26,%27,%28,%29,%30,%31}, {%32,%33,%34,%35}, %36, p, 1, 1, 0;}"
        : "+f"(d[0]), "+f"(d[1]), "+f"(d[2]), "+f"(d[3]), "+f"(d[4]), "+f"(d[5]), "+f"(d[6]), "+f"(d[7]), "+f"(d[8]), "+f"(d[9]), "+f"(d[10]), "+f"(d[11]), "+f"(d[12]), "+f"(d[13]), "+f"(d[14]), "+f"(d[15]), "+f"(d[16]), "+f"(d[17]), "+f"(d[18]), "+f"(d[19]), "+f"(d[20]), "+f"(d[21]), "+f"(d[22]), "+f"(d[23]), "+f"(d[24]), "+f"(d[25]), "+f"(d[26]), "+f"(d[27]), "+f"(d[28]), "+f"(d[29]), "+f"(d[30]), "+f"(d[31])
        : "r"(a0), "r"(a1), "r"(a2), "r"(a3), "l"(db), "r"(acc));
}
DEVI void wgmma_ss168t(float (&d)[84], uint64_t da, uint64_t db, int acc) {
    asm volatile("{.reg .pred p; setp.ne.b32 p, %86, 0;\n"
        "wgmma.mma_async.sync.aligned.m64n168k16.f32.bf16.bf16 {%0,%1,%2,%3,%4,%5,%6,%7,%8,%9,%10,%11,%12,%13,%14,%15,%16,%17,%18,%19,%20,%21,%22,%23,%24,%25,%26,%27,%28,%29,%30,%31,%32,%33,%34,%35,%36,%37,%38,%39,%40,%41,%42,%43,%44,%45,%46,%47,%48,%49,%50,%51,%52,%53,%54,%55,%56,%57,%58,%59,%60,%61,%62,%63,%64,%65,%66,%67,%68,%69,%70,%71,%72,%73,%74,%75,%76,%77,%78,%79,%80,%81,%82,%83}, %84, %85, p, 1, 1, 0, 1;}"
        : "+f"(d[0]), "+f"(d[1]), "+f"(d[2]), "+f"(d[3]), "+f"(d[4]), "+f"(d[5]), "+f"(d[6]), "+f"(d[7]), "+f"(d[8]), "+f"(d[9]), "+f"(d[10]), "+f"(d[11]), "+f"(d[12]), "+f"(d[13]), "+f"(d[14]), "+f"(d[15]), "+f"(d[16]), "+f"(d[17]), "+f"(d[18]), "+f"(d[19]), "+f"(d[20]), "+f"(d[21]), "+f"(d[22]), "+f"(d[23]), "+f"(d[24]), "+f"(d[25]), "+f"(d[26]), "+f"(d[27]), "+f"(d[28]), "+f"(d[29]), "+f"(d[30]), "+f"(d[31]), "+f"(d[32]), "+f"(d[33]), "+f"(d[34]), "+f"(d[35]), "+f"(d[36]), "+f"(d[37]), "+f"(d[38]), "+f"(d[39]), "+f"(d[40]), "+f"(d[41]), "+f"(d[42]), "+f"(d[43]), "+f"(d[44]), "+f"(d[45]), "+f"(d[46]), "+f"(d[47]), "+f"(d[48]), "+f"(d[49]), "+f"(d[50]), "+f"(d[51]), "+f"(d[52]), "+f"(d[53]), "+f"(d[54]), "+f"(d[55]), "+f"(d[56]), "+f"(d[57]), "+f"(d[58]), "+f"(d[59]), "+f"(d[60]), "+f"(d[61]), "+f"(d[62]), "+f"(d[63]), "+f"(d[64]), "+f"(d[65]), "+f"(d[66]), "+f"(d[67]), "+f"(d[68]), "+f"(d[69]), "+f"(d[70]), "+f"(d[71]), "+f"(d[72]), "+f"(d[73]), "+f"(d[74]), "+f"(d[75]), "+f"(d[76]), "+f"(d[77]), "+f"(d[78]), "+f"(d[79]), "+f"(d[80]), "+f"(d[81]), "+f"(d[82]), "+f"(d[83])
        : "l"(da), "l"(db), "r"(acc));
}
DEVI void wgmma_rs96t(float (&d)[48], uint32_t a0, uint32_t a1, uint32_t a2, uint32_t a3, uint64_t db, int acc) {
    asm volatile("{.reg .pred p; setp.ne.b32 p, %53, 0;\n"
        "wgmma.mma_async.sync.aligned.m64n96k16.f32.bf16.bf16 {%0,%1,%2,%3,%4,%5,%6,%7,%8,%9,%10,%11,%12,%13,%14,%15,%16,%17,%18,%19,%20,%21,%22,%23,%24,%25,%26,%27,%28,%29,%30,%31,%32,%33,%34,%35,%36,%37,%38,%39,%40,%41,%42,%43,%44,%45,%46,%47}, {%48,%49,%50,%51}, %52, p, 1, 1, 1;}"
        : "+f"(d[0]), "+f"(d[1]), "+f"(d[2]), "+f"(d[3]), "+f"(d[4]), "+f"(d[5]), "+f"(d[6]), "+f"(d[7]), "+f"(d[8]), "+f"(d[9]), "+f"(d[10]), "+f"(d[11]), "+f"(d[12]), "+f"(d[13]), "+f"(d[14]), "+f"(d[15]), "+f"(d[16]), "+f"(d[17]), "+f"(d[18]), "+f"(d[19]), "+f"(d[20]), "+f"(d[21]), "+f"(d[22]), "+f"(d[23]), "+f"(d[24]), "+f"(d[25]), "+f"(d[26]), "+f"(d[27]), "+f"(d[28]), "+f"(d[29]), "+f"(d[30]), "+f"(d[31]), "+f"(d[32]), "+f"(d[33]), "+f"(d[34]), "+f"(d[35]), "+f"(d[36]), "+f"(d[37]), "+f"(d[38]), "+f"(d[39]), "+f"(d[40]), "+f"(d[41]), "+f"(d[42]), "+f"(d[43]), "+f"(d[44]), "+f"(d[45]), "+f"(d[46]), "+f"(d[47])
        : "r"(a0), "r"(a1), "r"(a2), "r"(a3), "l"(db), "r"(acc));
}
DEVI void wgmma_rs192t(float (&d)[96], uint32_t a0, uint32_t a1, uint32_t a2, uint32_t a3, uint64_t db, int acc) {
    asm volatile("{.reg .pred p; setp.ne.b32 p, %101, 0;\n"
        "wgmma.mma_async.sync.aligned.m64n192k16.f32.bf16.bf16 {%0,%1,%2,%3,%4,%5,%6,%7,%8,%9,%10,%11,%12,%13,%14,%15,%16,%17,%18,%19,%20,%21,%22,%23,%24,%25,%26,%27,%28,%29,%30,%31,%32,%33,%34,%35,%36,%37,%38,%39,%40,%41,%42,%43,%44,%45,%46,%47,%48,%49,%50,%51,%52,%53,%54,%55,%56,%57,%58,%59,%60,%61,%62,%63,%64,%65,%66,%67,%68,%69,%70,%71,%72,%73,%74,%75,%76,%77,%78,%79,%80,%81,%82,%83,%84,%85,%86,%87,%88,%89,%90,%91,%92,%93,%94,%95}, {%96,%97,%98,%99}, %100, p, 1, 1, 1;}"
        : "+f"(d[0]), "+f"(d[1]), "+f"(d[2]), "+f"(d[3]), "+f"(d[4]), "+f"(d[5]), "+f"(d[6]), "+f"(d[7]), "+f"(d[8]), "+f"(d[9]), "+f"(d[10]), "+f"(d[11]), "+f"(d[12]), "+f"(d[13]), "+f"(d[14]), "+f"(d[15]), "+f"(d[16]), "+f"(d[17]), "+f"(d[18]), "+f"(d[19]), "+f"(d[20]), "+f"(d[21]), "+f"(d[22]), "+f"(d[23]), "+f"(d[24]), "+f"(d[25]), "+f"(d[26]), "+f"(d[27]), "+f"(d[28]), "+f"(d[29]), "+f"(d[30]), "+f"(d[31]), "+f"(d[32]), "+f"(d[33]), "+f"(d[34]), "+f"(d[35]), "+f"(d[36]), "+f"(d[37]), "+f"(d[38]), "+f"(d[39]), "+f"(d[40]), "+f"(d[41]), "+f"(d[42]), "+f"(d[43]), "+f"(d[44]), "+f"(d[45]), "+f"(d[46]), "+f"(d[47]), "+f"(d[48]), "+f"(d[49]), "+f"(d[50]), "+f"(d[51]), "+f"(d[52]), "+f"(d[53]), "+f"(d[54]), "+f"(d[55]), "+f"(d[56]), "+f"(d[57]), "+f"(d[58]), "+f"(d[59]), "+f"(d[60]), "+f"(d[61]), "+f"(d[62]), "+f"(d[63]), "+f"(d[64]), "+f"(d[65]), "+f"(d[66]), "+f"(d[67]), "+f"(d[68]), "+f"(d[69]), "+f"(d[70]), "+f"(d[71]), "+f"(d[72]), "+f"(d[73]), "+f"(d[74]), "+f"(d[75]), "+f"(d[76]), "+f"(d[77]), "+f"(d[78]), "+f"(d[79]), "+f"(d[80]), "+f"(d[81]), "+f"(d[82]), "+f"(d[83]), "+f"(d[84]), "+f"(d[85]), "+f"(d[86]), "+f"(d[87]), "+f"(d[88]), "+f"(d[89]), "+f"(d[90]), "+f"(d[91]), "+f"(d[92]), "+f"(d[93]), "+f"(d[94]), "+f"(d[95])
        : "r"(a0), "r"(a1), "r"(a2), "r"(a3), "l"(db), "r"(acc));
}

#define TRD(t, i)
namespace km {
#define NSS 6
#define RG "184"
#define RW "136"
#define NFL 2
#define NR1 3
#define NR2 3
#define FK 5
#define LDP 3
#define SND 1
#define NGAP 0
constexpr int O_H = 0;
constexpr int O_MB = 73728;
constexpr int O_VX = 96768;
constexpr int O_KX = 113152;
constexpr int O_QX = 119296;
constexpr int O_VM = 125440;
constexpr int O_KM = 129536;
constexpr int O_QM = 131072;
constexpr int O_SM = 132608;
constexpr int O_ST = 135168;
constexpr int O_OX = 145408;
constexpr int O_WO = 149504;
constexpr int O_OS = O_WO;
constexpr int O_WS = O_WO + 49152;
constexpr int O_RL = 110592;
constexpr int O_BAR = O_WS + NSS * 4096;
constexpr int SMEM = O_BAR + 128 + 1024 + TR_BYTES;
enum { B_X = 0, B_XFREE = 8, B_WIN = 16, B_VX = 24, B_SM = 32, B_ST = 40, B_EP = 56 };
#define DLY1 (100 * w)
#define DLY2 300
#define XON 1
#define GON 1
#define DLY0 1000
#define PFON 0
#define PLACE 1
#define XST 0
#define DLYW 12000
#define DLYB 14000
constexpr uint32_t DESC_HI = (1024 >> 4) | (1u << 30);
constexpr float SC = 0.08838834764831845f * 1.4426950408889634f;
}

__global__ void __cluster_dims__(3, 1, 1) __launch_bounds__(384, 1)
k_main(const __nv_bfloat16* __restrict__ x0, const __nv_bfloat16* __restrict__ wqkv, const __nv_bfloat16* __restrict__ wo,
       const __nv_bfloat16* __restrict__ mem0, const __nv_bfloat16* __restrict__ Wq, const __nv_bfloat16* __restrict__ Wk,
       const __nv_bfloat16* __restrict__ Wv, const __nv_bfloat16* __restrict__ Wo) {
    using namespace km;
    extern __shared__ unsigned char smem_raw[];
    const uint32_t sb = (smem_u32(smem_raw) + 1023) & ~1023u;
    const int tid = threadIdx.x, lane = tid & 31, warp = __shfl_sync(~0u, tid >> 5, 0);
    uint32_t l16 = __shfl_sync(~0u, lane * 16, lane);
#define OPQ() asm volatile("" : "+r"(l16))
    const int b = blockIdx.x, h = b / 3, r = b % 3;
    const int nq = r == 2 ? 2 : 3;
    const uint32_t bar = sb + O_BAR;
    asm volatile("griddepcontrol.launch_dependents;");
    const uint32_t t_start = clk();
    if (warp == 0 && b < 72) {
        if (lane == 0) { mbar_init(bar + 96, 1); fence_async_smem(); mbar_expect(bar + 96, 8 * 3456, true); }
        __syncwarp();
        if (lane < 8) asm volatile("cp.async.bulk.shared::cluster.global.mbarrier::complete_tx::bytes [%0], [%1], 3456, [%2];" :: "r"(sb + O_RL + lane * 3472), "l"(wqkv + (b * 8 + lane) * 1728), "r"(bar + 96) : "memory");
    }
    if (tid == 352) {
        prefetch_l2(x0 + b * (2 * DM), 2 * 1152); prefetch_l2(wo + b * (6 * DM), 6 * 1152);
    }
    if (tid == 320) sts32(bar + 64, ldg32(&g_epoch));
#define EP lds32(bar + 64)
    TR_INIT(bar + 128);
    TRG(79, 0);
    uint32_t roff0, roff1;
    {
        uint32_t y0, y1;
        asm("mapa.shared::cluster.u32 %0, %1, %2;" : "=r"(y0) : "r"(sb), "r"((r + 1) % 3));
        asm("mapa.shared::cluster.u32 %0, %1, %2;" : "=r"(y1) : "r"(sb), "r"((r + 2) % 3));
        roff0 = y0 - sb; roff1 = y1 - sb;
    }
#define LSWAP ((l16 & 0x70) | ((l16 & 0x80) << 1) | ((l16 & 0x100) >> 1))
    const uint32_t nv_remote = 8 - (8 - 2 * nq);

    if (warp < 8) {
        asm volatile("setmaxnreg.inc.sync.aligned.u32 " RG ";");
        constexpr int SSP = 36 / NSS;
#define IS_SS(kk) ((kk) % SSP == 3)
#define AI(kk) (4 * ((kk) - ((kk) + SSP - 4) / SSP))
        uint32_t a[144 - 4 * NSS];
        {
            const int ci = tid & 15, slot = ci >> 1, d0 = tid >> 4;
            const __nv_bfloat16* src = slot < nq ? Wq + (3 * r + slot) * 16 : slot < 2 * nq ? Wk + (3 * r + slot - nq) * 16 : Wv + (2 * r + slot - 2 * nq) * 16;
            src += h * 128 + (ci & 1) * 8 + d0 * 4096;
            auto issue = [&](int q) {
#pragma unroll
                for (int i = 0; i < 3; i++) if (q < 12) cp16(sb + (q * 3 + i) * 4096 + d0 * 256 + ((ci ^ (d0 & 7)) << 4), src + (size_t)(q * 3 + i) * 65536);
                asm volatile("cp.async.commit_group;" ::: "memory");
            };
            if (b < 72) {
                bar_sync(10, 256);
                mbar_wait(bar + 96, 0);
                TR1(4);
#pragma unroll 2
                for (int ag = tid >> 3; ag < 231; ag += 32) {
                    const int a = ag / 21, gr = ag % 21, tl = gr >= 18;
                    const int head = 3 * a + (tl ? 0 : (gr % 6) >> 1), nw = tl ? min(3, 32 - head) : head < 32 ? 4 : 0;
                    const uint32_t p = sb + O_RL + (tid & 7) * 3472 + (tl ? gr - 18 : gr / 6) * 1152 + head * 36 + (tl ? 32 : (gr & 1) * 16), step = tl ? 36 : 4;
                    uint32_t v[4];
#pragma unroll
                    for (int i = 0; i < 4; i++) { v[i] = lds32(p + i * step); if (i >= nw) v[i] = 0; }
                    stg128(g_wa + ((a * 9 + (b >> 3)) * 21 + gr) * 64 + (b & 7) * 8 + (tid & 7), v[0], v[1], v[2], v[3]);
                }
            }
            {
                bar_arrive(15, 288);
                TR1(5);
                delay_until(t_start, DLY0);
#pragma unroll
                for (int q = 0; q < NFL; q++) issue(q);
            }
            TR1(1);
            const int mi = lane >> 3;
            const uint32_t ad = sb + ((mi >> 1) * 8 + (lane & 7)) * 256 + (((warp * 2 + (mi & 1)) ^ (lane & 7)) << 4);
#pragma unroll
            for (int kk = 0; kk < 36; kk++) {
                if (kk % 3 == 0) { cp_wait<NFL - 1>(); issue(kk / 3 + NFL); bar_sync(10, 256); }
                const uint4 f = ldsm4t(ad + kk * 4096);
                if (IS_SS(kk)) {
                    const uint32_t o0 = sb + O_WS + (kk / SSP) * 4096 + warp * 512 + lane * 4;
                    sts32(o0, f.x); sts32(o0 + 256, f.y); sts32(o0 + 128, f.z); sts32(o0 + 384, f.w);
                } else { a[AI(kk)] = f.x; a[AI(kk) + 1] = f.y; a[AI(kk) + 2] = f.z; a[AI(kk) + 3] = f.w; }
            }
            TR1(2);
            bar_sync(9, 384);
#pragma unroll
            for (int i = 0; i < 9; i++) sts128(sb + O_H + i * 8192 + 4096 + tid * 16, 0, 0, 0, 0);
#pragma unroll
            for (int i = 0; i < 8; i++) if (i * 256 + tid < (O_OX - O_KX) / 16) sts128(sb + O_KX + i * 4096 + tid * 16, 0, 0, 0, 0);
            fence_async_smem();
            cluster_sync();
        }
        TR1(3);
        const int kind = warp < nq ? 0 : warp < 2 * nq ? 1 : 2;
        const int sl = kind == 0 ? warp : kind == 1 ? warp - nq : 2 * r + warp - 2 * nq;
        const uint32_t adX0 = sb + (kind == 0 ? O_QX : kind == 1 ? O_KX : O_VX) + sl * 2048;
        const uint32_t adM0 = sb + (kind == 0 ? O_QM : kind == 1 ? O_KM : O_VM) + sl * 512;
        const uint32_t hlo = (((sb + O_H) >> 4) & 0x3fff) | (1u << 16);
        const uint32_t mlo = (((sb + O_MB) >> 4) & 0x3fff) | (16u << 16);
        const uint32_t wlo = (((sb + O_WS + (warp >> 2) * 2048) >> 4) & 0x3fff) | (8u << 16);
        const int L = (warp >> 1) & 1, qh = warp & 1;
        const uint32_t st = sb + O_ST + warp * 1280;

#pragma unroll 1
        for (int t = -1;; t++) {
            TR_ON(t);
            OPQ();
            const uint32_t adX = adX0 + l16, adM = adM0 + l16, l8 = l16 >> 1;
            const uint32_t lq = LSWAP;
            if (t >= 0) {
                float d0[8], d1[8];
                {
#pragma unroll
                    for (int G = 0; G < 3; G++) {
                        if (warp < 4) bar_sync(1 + G, 160); else bar_sync(12 + G, 160);
                        if (G == 0) wg_fence();
#pragma unroll
                        for (int q = 0; q < 12; q++) {
                            const int kk = 12 * G + q;
                            const uint64_t db = mkdesc(mlo + kk * 32, 8);
                            if (IS_SS(kk)) wgmma_ss16t((kk & 1) ? d1 : d0, mkdesc(wlo + (kk / SSP) * 256, 16), db, 1);
                            else wgmma_rs16t((kk & 1) ? d1 : d0, a[AI(kk)], a[AI(kk) + 1], a[AI(kk) + 2], a[AI(kk) + 3], db, kk >= 2);
                            if (kk == 0) TR(0);
                        }
                    }
                    wg_commit();
                }
#define PM(i) pk(d0[2 * (i)] + d1[2 * (i)], d0[2 * (i) + 1] + d1[2 * (i) + 1])
                if (warp >= 4) {
                    wg_wait<0>();
                    TR(1);
                    const uint32_t p0 = PM(0), p1 = PM(1), p2 = PM(2), p3 = PM(3);
                    if (kind == 2) {
                        sts128(adM, p0, p1, p2, p3);
                        bar_arrive(4, 384);
                        sta128(adM + roff0, p0, p1, p2, p3, bar + B_SM + roff0);
                        sta128(adM + roff1, p0, p1, p2, p3, bar + B_SM + roff1);
                    } else {
                        stsm4t(adM, p0, p1, p2, p3);
                        bar_arrive(4, 384);
                    }
                } else {
                    uint4 q[3], k[3][2];
                    mbar_wait(bar + B_EP, t & 1);
#pragma unroll
                    for (int m = 0; m < LDP; m++) {
                        q[m] = ldsm4(sb + O_QX + m * 2048 + warp * 512 + lq);
                        k[m][0] = ldsm4(sb + O_KX + m * 2048 + L * 1024 + l16); k[m][1] = ldsm4(sb + O_KX + m * 2048 + L * 1024 + 512 + l16);
                    }
                    wg_wait<0>();
                    TR(1);
                    stsm4t(adM, PM(0), PM(1), PM(2), PM(3));
                    bar_arrive(4, 384);
                    sched_fence(gridDim.y, 6);
#pragma unroll
                    for (int m = LDP; m < 3; m++) {
                        q[m] = ldsm4(sb + O_QX + m * 2048 + warp * 512 + lq);
                        k[m][0] = ldsm4(sb + O_KX + m * 2048 + L * 1024 + l16); k[m][1] = ldsm4(sb + O_KX + m * 2048 + L * 1024 + 512 + l16);
                    }
                    float s[5][4];
                    {
                        float y[4] = {0, 0, 0, 0};
#pragma unroll
                        for (int n = 0; n < 5; n++) s[n][0] = s[n][1] = s[n][2] = s[n][3] = 0.f;
#pragma unroll
                        for (int m = 0; m < 3; m++) {
                            mma16(s[0], q[m].x, q[m].y, q[m].z, q[m].w, k[m][0].x, k[m][0].y); mma16(s[1], q[m].x, q[m].y, q[m].z, q[m].w, k[m][0].z, k[m][0].w);
                            mma16(s[2], q[m].x, q[m].y, q[m].z, q[m].w, k[m][1].x, k[m][1].y); mma16(s[3], q[m].x, q[m].y, q[m].z, q[m].w, k[m][1].z, k[m][1].w);
                        }
                        auto send = [&]() {
                            uint32_t w0 = pk(s[0][0], s[0][1]), w1 = pk(s[0][2], s[0][3]), w2 = pk(s[1][0], s[1][1]), w3 = pk(s[1][2], s[1][3]);
                            sta128(st + l16 + 5120 + roff0, w0, w1, w2, w3, bar + B_ST + roff0);
                            sta128(st + l16 + roff1, w0, w1, w2, w3, bar + B_ST + roff1);
                            w0 = pk(s[2][0], s[2][1]); w1 = pk(s[2][2], s[2][3]); w2 = pk(s[3][0], s[3][1]); w3 = pk(s[3][2], s[3][3]);
                            sta128p(st + l16 + 5120 + 512 + roff0, w0, w1, w2, w3, bar + B_ST + roff0, qh);
                            sta128p(st + l16 + 512 + roff1, w0, w1, w2, w3, bar + B_ST + roff1, qh);
                        };
                        bar_sync(5, 256);
                        const uint4 k01 = ldsm4(sb + O_KM + L * 256 + l16 + (l16 & 256));
                        const uint2 k2 = ldsm2(sb + O_KM + 1024 + L * 256 + l16);
                        if (SND == 0) send();
                        mma16(s[4], q[0].x, q[0].y, q[0].z, q[0].w, k01.x, k01.y);
                        mma16(y, q[1].x, q[1].y, q[1].z, q[1].w, k01.z, k01.w);
                        mma16(s[4], q[2].x, q[2].y, q[2].z, q[2].w, k2.x, k2.y);
#pragma unroll
                        for (int j = 0; j < 4; j++) s[4][j] += y[j];
                        const uint32_t w0 = pk(s[4][0], s[4][1]), w1 = pk(s[4][2], s[4][3]);
                        if (NGAP > 0) bar_arrive(11, 256);
                        sta64(st + l8 + 5120 + 1024 + roff0, w0, w1, bar + B_ST + roff0);
                        sta64(st + l8 + 1024 + roff1, w0, w1, bar + B_ST + roff1);
                        if (SND == 1) send();
                        TR(2);
                        const int lim = 16 * qh + (int)(l16 >> 6) - (int)((l16 >> 3) & 6);
#pragma unroll
                        for (int n = 0; n < 4; n++)
#pragma unroll
                            for (int j = 0; j < 4; j++) if (!(n == 0 && j >= 2) && 8 * (n - (j >> 1)) + (j & 1) > lim) s[n][j] = -1e30f;
#pragma unroll
                        for (int n = 0; n < 4; n++) asm volatile("" : "+f"(s[n][0]), "+f"(s[n][1]), "+f"(s[n][2]), "+f"(s[n][3]));
                    }
                    uint4 v0[3], v1[3]; uint2 vm[3];
                    const uint32_t vad = sb + O_VX + 3 * r * 2048 + L * 1024 + l16;
#pragma unroll
                    for (int m = 0; m < 3; m++) v0[m] = lds128(vad + m * 2048);
                    const uint32_t otag = ring_tag(t, EP);
                    mbar_wait(bar + B_SM, t & 1);
                    mbar_wait(bar + B_ST, t & 1);
                    TR(3);
                    float mx0, mx1;
                    {
                        const uint4 u = lds128(st + l16), x = lds128(st + 5120 + l16), v = lds128(st + 512 + l16), y = lds128(st + 5120 + 512 + l16);
                        const uint2 w = lds64(st + 1024 + l8), z = lds64(st + 5120 + 1024 + l8);
                        s[0][0] += bf_lo(u.x) + bf_lo(x.x); s[0][1] += bf_hi(u.x) + bf_hi(x.x); s[0][2] += bf_lo(u.y) + bf_lo(x.y); s[0][3] += bf_hi(u.y) + bf_hi(x.y);
                        s[1][0] += bf_lo(u.z) + bf_lo(x.z); s[1][1] += bf_hi(u.z) + bf_hi(x.z); s[1][2] += bf_lo(u.w) + bf_lo(x.w); s[1][3] += bf_hi(u.w) + bf_hi(x.w);
                        s[2][0] += bf_lo(v.x) + bf_lo(y.x); s[2][1] += bf_hi(v.x) + bf_hi(y.x); s[2][2] += bf_lo(v.y) + bf_lo(y.y); s[2][3] += bf_hi(v.y) + bf_hi(y.y);
                        s[3][0] += bf_lo(v.z) + bf_lo(y.z); s[3][1] += bf_hi(v.z) + bf_hi(y.z); s[3][2] += bf_lo(v.w) + bf_lo(y.w); s[3][3] += bf_hi(v.w) + bf_hi(y.w);
                        s[4][0] += bf_lo(w.x) + bf_lo(z.x); s[4][1] += bf_hi(w.x) + bf_hi(z.x); s[4][2] += bf_lo(w.y) + bf_lo(z.y); s[4][3] += bf_hi(w.y) + bf_hi(z.y);
                        mx0 = fmaxf(fmaxf(fmaxf(s[0][0], s[0][1]), fmaxf(s[1][0], s[1][1])), fmaxf(fmaxf(s[2][0], s[2][1]), fmaxf(s[3][0], s[3][1])));
                        mx1 = fmaxf(fmaxf(fmaxf(s[0][2], s[0][3]), fmaxf(s[1][2], s[1][3])), fmaxf(fmaxf(s[2][2], s[2][3]), fmaxf(s[3][2], s[3][3])));
                        mx0 = fmaxf(mx0, fmaxf(s[4][0], s[4][1])); mx1 = fmaxf(mx1, fmaxf(s[4][2], s[4][3]));
                    }
#pragma unroll
                    for (int o = 1; o < 4; o <<= 1) { const float2 z = shfl2(mx0, mx1, o); mx0 = fmaxf(mx0, z.x); mx1 = fmaxf(mx1, z.y); }
                    mx0 *= -SC; mx1 *= -SC;
                    float l0 = 0.f, l1 = 0.f;
                    uint32_t p[10];
#pragma unroll
                    for (int n = 0; n < 5; n++) {
                        const float e0 = ex2(fmaf(s[n][0], SC, mx0)), e1 = ex2(fmaf(s[n][1], SC, mx0));
                        const float e2 = ex2(fmaf(s[n][2], SC, mx1)), e3 = ex2(fmaf(s[n][3], SC, mx1));
                        l0 += e0 + e1; l1 += e2 + e3;
                        p[2 * n] = pk(e0, e1); p[2 * n + 1] = pk(e2, e3);
                    }
#pragma unroll
                    for (int m = 0; m < 3; m++) vm[m] = lds64(sb + O_VM + (3 * r + m) * 512 + l16 + L * 8);
                    asm volatile("" : "+f"(l0), "+f"(l1));
                    sched_fence(gridDim.y, 5);
                    float o[6][4];
#pragma unroll
                    for (int m = 0; m < 6; m++) o[m][0] = o[m][1] = o[m][2] = o[m][3] = 0.f;
#pragma unroll
                    for (int m = 0; m < 3; m++) { mma8(o[2 * m], p[0], p[1], v0[m].x); mma8(o[2 * m + 1], p[0], p[1], v0[m].y); }
                    { const float2 z = shfl2(l0, l1, 1); l0 += z.x; l1 += z.y; }
#pragma unroll
                    for (int m = 0; m < 3; m++) { mma8(o[2 * m], p[2], p[3], v0[m].z); mma8(o[2 * m + 1], p[2], p[3], v0[m].w); v1[m] = lds128(vad + m * 2048 + 512); }
                    { const float2 z = shfl2(l0, l1, 2); l0 += z.x; l1 += z.y; }
#pragma unroll
                    for (int m = 0; m < 3; m++) { mma8(o[2 * m], p[8], p[9], vm[m].x); mma8(o[2 * m + 1], p[8], p[9], vm[m].y); }
#pragma unroll
                    for (int m = 0; m < 3; m++) { mma8(o[2 * m], p[4], p[5], v1[m].x); mma8(o[2 * m + 1], p[4], p[5], v1[m].y); }
                    l0 = rcp(l0); l1 = rcp(l1);
#pragma unroll
                    for (int m = 0; m < 3; m++) { mma8(o[2 * m], p[6], p[7], v1[m].z); mma8(o[2 * m + 1], p[6], p[7], v1[m].w); }
#pragma unroll
                    for (int m = 0; m < 3; m++)
                        sts128(sb + O_OS + warp * 512 + m * 2048 + l16, (pk(o[2 * m][0] * l0, o[2 * m][1] * l0) & ~1u) | otag, pk(o[2 * m][2] * l1, o[2 * m][3] * l1),
                               pk(o[2 * m + 1][0] * l0, o[2 * m + 1][1] * l0), pk(o[2 * m + 1][2] * l1, o[2 * m + 1][3] * l1));
                    TR(4);
                }
            }
            if (t + 1 >= NT) break;
            {
                float d[32];
                mbar_wait(bar + B_X, (t + 1) & 1);
                if (NGAP == 0 || warp < 4) bar_sync(7, 384); else if (t >= 0) bar_sync(11, 256);
                wg_fence();
                TR(6);
#pragma unroll
                for (int kk = 0; kk < 36; kk++) {
                    if (NGAP > 0 && kk == NGAP) asm volatile("{.reg .pred p; setp.ge.u32 p, %0, 4; @p bar.sync 7, 384;}" :: "r"(warp) : "memory");
                    const uint64_t db = mkdesc(hlo + ((kk >> 2) * 8192 + (kk & 3) * 32) / 16, DESC_HI);
                    if (IS_SS(kk)) wgmma_ss64(d, mkdesc(wlo + (kk / SSP) * 256, 16), db, 1);
                    else wgmma_rs64(d, a[AI(kk)], a[AI(kk) + 1], a[AI(kk) + 2], a[AI(kk) + 3], db, kk > 0);
                }
                wg_commit();
                TR(5);
                mbar_wait(bar + B_WIN, (t + 1) & 1);
                wg_wait<0>();
                TR(7);
                mbar_arrive_all3(bar + B_XFREE, l16 >> 4);
                uint32_t p[16];
#pragma unroll
                for (int u = 0; u < 16; u++) p[u] = pk(d[2 * u], d[2 * u + 1]);
                if (kind == 2) {
#pragma unroll
                    for (int u = 0; u < 4; u++) sts128(adX + u * 512, p[4 * u], p[4 * u + 1], p[4 * u + 2], p[4 * u + 3]);
                } else {
#pragma unroll
                    for (int u = 0; u < 4; u++) stsm4t(adX + u * 512, p[4 * u], p[4 * u + 1], p[4 * u + 2], p[4 * u + 3]);
                }
                __syncwarp();
                asm volatile("{.reg .pred p; setp.eq.u32 p, %1, 0; @p mbarrier.arrive.shared.b64 _, [%0];}" :: "r"(bar + B_EP), "r"(l16) : "memory");
                if (kind == 2) {
                    fence_async_smem();
                    __syncwarp();
                    asm volatile("{.reg .pred p; setp.eq.u32 p, %5, 0;\n"
                        "@p cp.async.bulk.shared::cluster.shared::cta.mbarrier::complete_tx::bytes [%0], [%2], 2048, [%3];\n"
                        "@p cp.async.bulk.shared::cluster.shared::cta.mbarrier::complete_tx::bytes [%1], [%2], 2048, [%4];}"
                        :: "r"(adX0 + roff0), "r"(adX0 + roff1), "r"(adX0), "r"(bar + B_VX + roff0), "r"(bar + B_VX + roff1), "r"(l16) : "memory");
                }
                TR(8);
            }
        }
        if (warp < 4) bar_arrive(7, 160); else if (NGAP > 0) bar_sync(11, 256);
        cluster_sync();
    } else {
        asm volatile("setmaxnreg.dec.sync.aligned.u32 " RW ";");
        const int w = warp - 8, t2 = tid - 256;
        if (t2 == 0) {
            mbar_init(bar + B_X, 1); mbar_init(bar + B_XFREE, 24); mbar_init(bar + B_WIN, 3);
            mbar_init(bar + B_VX, 1); mbar_init(bar + B_SM, 1); mbar_init(bar + B_ST, 1); mbar_init(bar + B_EP, 8);
            asm volatile("fence.mbarrier_init.release.cluster;" ::: "memory");
        }
        char* const ex = reinterpret_cast<char*>((reinterpret_cast<uintptr_t>(g_ex) + 0x1fffff) & ~(uintptr_t)0x1fffff);
        char* rbase = ex; uint32_t side = 0;
        {
            uint32_t m0[5][4];
#pragma unroll
            for (int i = 0; i < 5; i++) {
                const unsigned short* m = reinterpret_cast<const unsigned short*>(mem0) + min(i * 128 + t2, DM - 1);
#pragma unroll
                for (int j = 0; j < 4; j++) m0[i][j] = m[2 * j * DM] | (m[(2 * j + 1) * DM] << 16);
            }
            if (w == 3) { bar_sync(15, 288); cnt_add(g_cnt + C_W * 8, lane); TR1(1); }
            if (t2 >= 96 && t2 < 99 && PFON) prefetch_l2((t2 == 96 ? Wq : t2 == 97 ? Wk : Wv) + b * (6 * 4096), 6 * 8192);
            delay_until(t_start, DLYW);
#pragma unroll 4
            for (int i = t2; i < 128 * 24; i += 128) {
                const int e = (i >> 3) & 127, G = i >> 10, q = i & 7;
                cp16(sb + O_WO + G * 16384 + e * 128 + ((q ^ (e & 7) ^ ((h >> 1) & 1)) << 4), Wo + (size_t)(h * 128 + e) * DM + G * 192 + r * 64 + q * 8);
            }
            bar_sync(9, 384);
#pragma unroll
            for (int i = 0; i < 5; i++) {
                const int k = min(i * 128 + t2, DM - 1);
                const uint32_t ad = sb + O_MB + (k >> 3) * 256 + (k & 7) * 16;
                sts128(ad, m0[i][0], m0[i][1], m0[i][2], m0[i][3]); sts128(ad + 128, m0[i][0], m0[i][1], m0[i][2], m0[i][3]);
            }
            fence_async_smem();
        }
        auto arm = [&]() {
            const uint32_t ln = l16 >> 4;
            mbar_expect(bar + B_VX + (ln & 3) * 8, ln == 0 ? nv_remote * 2048 : ln == 1 ? nv_remote * 512 + 2560 : 8192, ln < 3);
        };
        if (w == 3) arm();
        cluster_sync();
        TR1(3);
        const int L = w >> 1, hf = w & 1;
        const uint32_t rd = hf ? roff1 : roff0;
        const uint32_t rzero = gridDim.y + 100;
#define WOAD (sb + O_WO + ((l16 & 0x100) << 2) + ((l16 & 0x70) << 3) + (((w * 32) | ((l16 >> 3) & 16)) ^ (l16 & 0x70)))

        auto fetch_tile = [&](int u) {
            const bool a0 = u < NSEG, a1 = u >= LAG;
            mbar_expect(bar + B_X, ((int)a0 + (int)a1) * 36864, l16 == 0);
            const uint32_t off = r * 24576 + (l16 << 9) + (a0 ? 0 : 4096);
            asm volatile("{.reg .pred p; setp.lt.u32 p, %5, %6;\n"
                "@p cp.async.bulk.shared::cluster.global.mbarrier::complete_tx::bytes.multicast::cluster [%0], [%1], %4, [%2], %3;}"
                :: "r"(sb + O_H + off), "l"(reinterpret_cast<const char*>(g_xt + u * 4608) + off), "r"(bar + B_X), "h"((uint16_t)7),
                   "r"(a0 && a1 ? 24576 : 4096), "r"(l16), "r"(a0 && a1 ? 16 : 48) : "memory");
        };
        auto store_o = [&](int u) {
            asm volatile("{.reg .pred p; setp.eq.u32 p, %3, 0;\n"
                "@p cp.async.bulk.global.shared::cta.bulk_group [%0], [%1], %2;\n cp.async.bulk.commit_group;}"
                :: "l"(g_o + ((u & (RING - 1)) * 256 + h * 8 + 3 * r) * 128), "r"(sb + O_OS), "r"(nq * 2048), "r"(l16) : "memory");
            cnt_hint(g_cnt + (C_O + u * 8 + (h >> 2)) * 8, l16);
            TRG(u, 2);
        };
        bar_arrive(7, 384);
        if (w < 3) {
            bar_arrive(1 + w, 160); bar_arrive(12 + w, 160); if (w == 0) bar_arrive(8, 64);
            if (w < 2) {
                unsigned* pp = reinterpret_cast<unsigned*>(ex + inbox_off(b) + 16384 + w * 4096 + 2048);
                uint32_t best = ~0u, v = 0;
                if (lane == 0) {
#pragma unroll 1
                    for (int i = 0; i < 6; i++) {
                        const uint32_t c0 = clk();
                        v = atomicAdd(pp + (v >> 31), 0);
                        asm volatile("" :: "r"(v) : "memory");
                        sts32(bar + 80, v);
                        best = min(best, clk() - c0);
                    }
                    sts32(bar + 72 + w * 4, best);
                }
            }
            bar_sync(15, 96);
            const uint32_t xs = PLACE ? lds32(bar + 76) < lds32(bar + 72) : 0, ep = EP;
            side = PLACE ? xs ^ page_par(inbox_off(b)) : 0;
            rbase = ex + inbox_off(b) + xs * 4096;
            const uint32_t inv = (ep * (NT - 1)) & 1;
#pragma unroll
            for (int i = 0; i < 4; i++) stg128(rbase + (w == 2 ? 16384 : w * 2048) + i * 512 + lane * 16, inv, 0, 0, 0);
            __threadfence();
            bar_sync(15, 96);
            if (t2 == 0) stg_word(g_side + b, (ep + 1) * 2 + xs, true);
            TR1(4);
        } else {
            mbar_arrive_all3(bar + B_WIN, l16 >> 4);
            cnt_wait(g_cnt + C_X * 8, 64 * (EP + 1)); fence_async_global();
            TRG(0, 0);
            fetch_tile(0);
            TRG(0, 1);
        }
        cp_wait_all();
        bar_sync(6, 128);
        uint32_t poff;
        {
            const int rb = r * 32 + w * 8 + (lane >> 2);
            const uint32_t want = EP + 1;
            uint32_t v;
            for (int n = 0; __any_sync(~0u, ((v = ldg_word(g_side + rb)) >> 1) != want); n++) fault_if(n > POLL_LIMIT, n);
            __threadfence();
            poff = inbox_off(rb) + (v & 1) * 4096 + h * 64 + (lane & 3) * 16;
        }
        side = __shfl_sync(~0u, side, 0);
        const uint32_t roff = __shfl_sync(~0u, (uint32_t)(rbase - ex), 0) + (w == 2 ? 16384 : (w & 1) * 2048);
        bool late = true;
        uint4 a0[8];
#pragma unroll
        for (int kk = 0; kk < 8; kk++) a0[kk] = ldsm4t(WOAD + kk * 2048);
#pragma unroll 1
        for (int t = 0;; t++) {
            TR_ON(t);
            OPQ();
            mbar_wait(bar + B_EP, t & 1);
            uint4 kx[3][2], vx[4][2];
            const uint32_t lp = LSWAP;
#pragma unroll
            for (int m = 0; m < 3; m++) {
                kx[m][0] = ldsm4(sb + O_KX + m * 2048 + L * 1024 + lp);
                kx[m][1] = ldsm4(sb + O_KX + m * 2048 + L * 1024 + 512 + lp);
            }
            if (w == 3) {
                mbar_wait(bar + B_XFREE, t & 1);
                bar_sync(8, 64);
                TR(6);
                if (t > 0) store_o(t - 1);
                if (late) { cnt_wait(g_cnt + (C_X + t + 1) * 8, 64 * (EP + 1)); fence_async_global(); }
                TRG(t + 1, 0);
                if (t + 1 < NT) { fetch_tile(t + 1); TRG(t + 1, 1); }
                asm volatile("cp.async.bulk.wait_group.read 0;" ::: "memory");
                TR(7);
            }
            mbar_wait(bar + B_VX, t & 1);
            TR(0);
            bar_sync(4, 384);
            float s0[4] = {0, 0, 0, 0}, s1[4] = {0, 0, 0, 0}, sm[4] = {0, 0, 0, 0};
            {
                const uint4 q01 = ldsm4(sb + O_QM + L * 256 + l16 + (l16 & 256));
                const uint2 q2 = ldsm2(sb + O_QM + 1024 + L * 256 + l16);
                uint4 km_[3];
#pragma unroll
                for (int m = 0; m < 3; m++) km_[m] = ldsm4(sb + O_KM + m * 512 + (lp ^ (L << 8)));
                bar_arrive(5, 256);
                mma16(s0, kx[0][0].x, kx[0][0].y, kx[0][0].z, kx[0][0].w, q01.x, q01.y);
                mma16(s1, kx[0][1].x, kx[0][1].y, kx[0][1].z, kx[0][1].w, q01.x, q01.y);
                mma16(sm, km_[0].x, km_[0].y, km_[0].z, km_[0].w, q01.x, q01.y);
                mma16(s0, kx[1][0].x, kx[1][0].y, kx[1][0].z, kx[1][0].w, q01.z, q01.w);
                mma16(s1, kx[1][1].x, kx[1][1].y, kx[1][1].z, kx[1][1].w, q01.z, q01.w);
                mma16(sm, km_[1].x, km_[1].y, km_[1].z, km_[1].w, q01.z, q01.w);
                mma16(s0, kx[2][0].x, kx[2][0].y, kx[2][0].z, kx[2][0].w, q2.x, q2.y);
                mma16(s1, kx[2][1].x, kx[2][1].y, kx[2][1].z, kx[2][1].w, q2.x, q2.y);
                mma16(sm, km_[2].x, km_[2].y, km_[2].z, km_[2].w, q2.x, q2.y);
                const uint32_t ad = sb + O_SM + (1 - hf) * 1280 + L * 640 + rd;
                sta128(ad + l16, pk(s0[0], s0[1]), pk(s0[2], s0[3]), pk(s1[0], s1[1]), pk(s1[2], s1[3]), bar + B_SM + rd);
                sta32(ad + 512 + (l16 >> 2), pk(sm[0], sm[1]), bar + B_SM + rd);
            }
            TR(1);
            if (t + 1 == NT) break;
#pragma unroll
            for (int m = 0; m < 8; m++) vx[m >> 1][m & 1] = lds128(sb + O_VX + (hf * 4 + (m >> 1)) * 2048 + L * 1024 + (m & 1) * 512 + l16);
            const uint32_t tag = (t + EP * (NT - 1) + 1) & 1;
            mbar_wait(bar + B_SM, t & 1);
            TR(2);
            {
                const uint32_t ad = sb + O_SM + L * 640;
                const uint4 u = lds128(ad + l16), v = lds128(ad + 1280 + l16);
                const uint32_t x = lds32(ad + 512 + (l16 >> 2)), y = lds32(ad + 1280 + 512 + (l16 >> 2));
                s0[0] += bf_lo(u.x) + bf_lo(v.x); s0[1] += bf_hi(u.x) + bf_hi(v.x); s0[2] += bf_lo(u.y) + bf_lo(v.y); s0[3] += bf_hi(u.y) + bf_hi(v.y);
                s1[0] += bf_lo(u.z) + bf_lo(v.z); s1[1] += bf_hi(u.z) + bf_hi(v.z); s1[2] += bf_lo(u.w) + bf_lo(v.w); s1[3] += bf_hi(u.w) + bf_hi(v.w);
                sm[0] += bf_lo(x) + bf_lo(y); sm[1] += bf_hi(x) + bf_hi(y);
            }
            uint2 vm[4];
#pragma unroll
            for (int m = 0; m < 4; m++) vm[m] = lds64(sb + O_VM + (hf * 4 + m) * 512 + l16 + L * 8);
            float mx0 = fmaxf(fmaxf(fmaxf(s0[0], s0[2]), fmaxf(s1[0], s1[2])), sm[0]);
            float mx1 = fmaxf(fmaxf(fmaxf(s0[1], s0[3]), fmaxf(s1[1], s1[3])), sm[1]);
#pragma unroll
            for (int o = 4; o < 32; o <<= 1) { mx0 = fmaxf(mx0, __shfl_xor_sync(~0u, mx0, o)); mx1 = fmaxf(mx1, __shfl_xor_sync(~0u, mx1, o)); }
            mx0 *= -SC; mx1 *= -SC;
            s0[0] = ex2(fmaf(s0[0], SC, mx0)); s0[1] = ex2(fmaf(s0[1], SC, mx1));
            s0[2] = ex2(fmaf(s0[2], SC, mx0)); s0[3] = ex2(fmaf(s0[3], SC, mx1));
            const uint32_t pb0 = movm(pk(s0[0], s0[1])), pb1 = movm(pk(s0[2], s0[3]));
            s1[0] = ex2(fmaf(s1[0], SC, mx0)); s1[1] = ex2(fmaf(s1[1], SC, mx1));
            s1[2] = ex2(fmaf(s1[2], SC, mx0)); s1[3] = ex2(fmaf(s1[3], SC, mx1));
            const uint32_t pb2 = movm(pk(s1[0], s1[1])), pb3 = movm(pk(s1[2], s1[3]));
            sm[0] = ex2(fmaf(sm[0], SC, mx0)); sm[1] = ex2(fmaf(sm[1], SC, mx1));
            const uint32_t pm = movm(pk(sm[0], sm[1]));
            float l0 = (s0[0] + s0[2]) + (s1[0] + s1[2]) + sm[0], l1 = (s0[1] + s0[3]) + (s1[1] + s1[3]) + sm[1];
            float o[4][4];
#pragma unroll
            for (int m = 0; m < 4; m++) { o[m][0] = o[m][1] = o[m][2] = o[m][3] = 0.f; mma16(o[m], vx[m][0].x, vx[m][0].y, vx[m][0].z, vx[m][0].w, pb0, pb1); }
            l0 += __shfl_xor_sync(~0u, l0, 4); l1 += __shfl_xor_sync(~0u, l1, 4);
#pragma unroll
            for (int m = 0; m < 4; m++) mma16(o[m], vx[m][1].x, vx[m][1].y, vx[m][1].z, vx[m][1].w, pb2, pb3);
            l0 += __shfl_xor_sync(~0u, l0, 8); l1 += __shfl_xor_sync(~0u, l1, 8);
#pragma unroll
            for (int m = 0; m < 4; m++) mma8(o[m], vm[m].x, vm[m].y, pm);
            l0 += __shfl_xor_sync(~0u, l0, 16); l1 += __shfl_xor_sync(~0u, l1, 16);
            l0 = rcp(l0); l1 = rcp(l1);
#pragma unroll
            for (int m = 0; m < 4; m += 2)
                stsm4t(sb + O_OX + (hf * 4 + m) * 512 + (L ^ ((h >> 2) & 1)) * 256   + ((l16 & 0x100) << 1) + (l16 & 0xf0),
                       pk(o[m][0] * l0, o[m][1] * l1), pk(o[m][2] * l0, o[m][3] * l1), pk(o[m + 1][0] * l0, o[m + 1][1] * l1), pk(o[m + 1][2] * l0, o[m + 1][3] * l1));
            TR(3);
            char* const pdst = ex + poff;
            bar_sync(6, 128);
            {
                uint4 bo[8], a1[8], z;
                const uint32_t wad = WOAD;
#pragma unroll
                for (int kk = 0; kk < 8; kk++) bo[kk] = ldsm4(sb + O_OX + kk * 512 + l16);
#pragma unroll
                for (int G = 0; G < 3; G++) {
                    float e[4][4];
#pragma unroll
                    for (int q = 0; q < 4; q++) e[q][0] = e[q][1] = e[q][2] = e[q][3] = 0.f;
#pragma unroll
                    for (int kk = 0; kk < 8; kk++) {
                        const uint4 f = G == 0 ? a0[kk] : a1[kk];
                        mma16(e[(kk & 1) * 2], f.x, f.y, f.z, f.w, bo[kk].x, bo[kk].y);
                        mma16(e[(kk & 1) * 2 + 1], f.x, f.y, f.z, f.w, bo[kk].z, bo[kk].w);
                        if (G == 1) a1[kk] = ldsm4t(wad + 32768 + kk * 2048);
                        if (G == 0 && kk == FK) {
                            sched_fence(rzero, 2);
#pragma unroll
                            for (int j = 0; j < 8; j++) a1[j] = ldsm4t(wad + 16384 + j * 2048);
                        }
                    }
                    if (G > 0) asm volatile("{.reg .pred p; setp.eq.u32 p, %5, 0; @p st.shared.v4.u32 [%0], {%1,%2,%3,%4};}" :: "r"(__float_as_uint(e[0][0])), "r"(z.x), "r"(z.y), "r"(z.z), "r"(z.w), "r"(rzero));
                    z = make_uint4((pk(e[0][0] + e[2][0], e[0][1] + e[2][1]) & ~1u) | tag, pk(e[0][2] + e[2][2], e[0][3] + e[2][3]),
                                   pk(e[1][0] + e[3][0], e[1][1] + e[3][1]), pk(e[1][2] + e[3][2], e[1][3] + e[3][3]));
                    stg_pkt(pdst + (G == 2 ? 16384 : G * 2048), z.x, z.y, z.z, z.w);
                    if (G == 0) { TR(9); TRD(t, 0); }
                    if (G < 2) sched_fence(rzero, 3 + G);
                }
            }
            TR(4);
            if (w < 3) {
                bar_arrive(7, 384);
                OPQ();
                const uint32_t tagm = tag;
                uint32_t m0v = 0;
                if (t + 1 <= LAG) {
                    const unsigned short* m = reinterpret_cast<const unsigned short*>(mem0) + ((l16 >> 3) & 6) * DM + 192 * w + 16 * (b >> 3) + (b & 7) + ((l16 >> 4) & 8);
                    m0v = m[0] | (m[DM] << 16);
                }
                const char* const rsrc = ex + roff + l16;
                uint4 v[4];
                delay(DLY1);
#pragma unroll
                for (int i = 0; i < 4; i++) v[i] = ldg_pkt(rsrc + i * 512);
                for (int n = 0; __any_sync(~0u, lop_bad(lop_bad(0, v[0].x, v[1].x, tagm), v[2].x, v[3].x, tagm) & 1); n++) {
#pragma unroll
                    for (int i = 0; i < 4; i++) v[i] = ldg_pkt(rsrc + i * 512);
                    fault_if(n > POLL_LIMIT, n);
                }
                TR(5); TRD(t, 1);
                float s[8];
                s[4] = (bf_lo(v[0].z) + bf_lo(v[1].z)) + (bf_lo(v[2].z) + bf_lo(v[3].z)); s[5] = (bf_hi(v[0].z) + bf_hi(v[1].z)) + (bf_hi(v[2].z) + bf_hi(v[3].z));
                s[6] = (bf_lo(v[0].w) + bf_lo(v[1].w)) + (bf_lo(v[2].w) + bf_lo(v[3].w)); s[7] = (bf_hi(v[0].w) + bf_hi(v[1].w)) + (bf_hi(v[2].w) + bf_hi(v[3].w));
                s[2] = (bf_lo(v[0].y) + bf_lo(v[1].y)) + (bf_lo(v[2].y) + bf_lo(v[3].y)); s[3] = (bf_hi(v[0].y) + bf_hi(v[1].y)) + (bf_hi(v[2].y) + bf_hi(v[3].y));
                s[0] = (bf_lo(v[0].x) + bf_lo(v[1].x)) + (bf_lo(v[2].x) + bf_lo(v[3].x)); s[1] = (bf_hi(v[0].x) + bf_hi(v[1].x)) + (bf_hi(v[2].x) + bf_hi(v[3].x));
#pragma unroll
                for (int j = 0; j < 4; j++) s[j] += __shfl_xor_sync(~0u, s[j + 4], 16);
#pragma unroll
                for (int j = 0; j < 2; j++) s[j] += __shfl_xor_sync(~0u, s[j + 2], 8);
#pragma unroll
                for (int j = 0; j < 2; j++) s[j] += __shfl_xor_sync(~0u, s[j], 4);
                char* const mem_w = ex + mem_off(w, 0);
                uint32_t res = t + 1 <= LAG && l16 >= 256 ? m0v : pk(s[0], s[1]);
                if ((l16 & 48) == 0) res = (res & ~1u) | tag;
                stg_word(mem_w + (mem_off(0, b >> 3) - mem_off(0, 0)) + (b & 7) * 16 + (((l16 & 64) << 6) + ((l16 & 128) << 1) + ((l16 & 256) >> 1) + ((l16 >> 2) & 12)), res, true);
                TR(6); TRD(t, 2);
                delay(DLY2);
                const char* src = mem_w + (side ^ page_par(0x180000)) * 4096 + l16;
                const uint32_t gdst = sb + O_MB + w * 6144 + l16;
                uint4 x[12];
#pragma unroll
                for (int i = 0; i < 12; i++) x[i] = ldg_pkt(src + (mem_off(0, i) - mem_off(0, 0)));
                for (int n = 0;; n++) {
                    uint32_t bad = 0;
#pragma unroll
                    for (int i = 0; i < 12; i += 2) bad = lop_bad(bad, x[i].x, x[i + 1].x, tagm);
                    if (!__any_sync(~0u, bad & 1)) break;
#pragma unroll
                    for (int i = 0; i < 12; i++) ldg_pkt_retry(x[i], src + (mem_off(0, i) - mem_off(0, 0)), tagm);
                    fault_if(n > POLL_LIMIT, n);
                }
#pragma unroll
                for (int i = 0; i < 12; i++) sts128(gdst + i * 512, x[i].x, x[i].y, x[i].z, x[i].w);
                TR(7); TRD(t, 3);
                fence_async_smem();
                bar_arrive(12 + w, 160);
                bar_arrive(1 + w, 160);
                if (w == XST) bar_arrive(8, 64);
                TR(8);
            } else {
                bar_sync(7, 384);
                fence_async_smem();
                arm();
                __syncwarp();
                mbar_arrive_all3(bar + B_WIN, l16 >> 4);
                late = t + 2 < NT && cnt_poll(g_cnt + (C_X + t + 2) * 8, 64 * (EP + 1), bar + B_EP, (t + 1) & 1);
                fence_async_global();
                TR(5);
            }
        }
        if (w == 3) { bar_sync(7, 160); fence_async_smem(); store_o(NT - 1); asm volatile("cp.async.bulk.wait_group 0;" ::: "memory"); }
        cluster_sync();
    }
    TR_DUMP(b);
}

#define VG 12
#define HB 3
#define HA 2
#define HW 0
namespace ka {
constexpr int O_WA = 196608;
constexpr int A_KB = 21504;
constexpr int O_RING = 194560;
constexpr int O_BAR = 230400;
constexpr int SMEM = O_BAR + 256 + 1024;
constexpr float SC = 0.23570226039551584f * 1.4426950408889634f;
}

template <int NP, int KB = 4096>
DEVI void row_task(const uint4* res, const uint4* part, uint4* xout, char* img, int pos, int lane, uint32_t tag) {
    const bool on = lane < 24;
    const int ln = on ? lane : 0;
    uint4 rv[3], pv[NP > 0 ? NP * 3 : 1];
#pragma unroll
    for (int i = 0; i < 3; i++) rv[i] = ldg128(res + i * 24 + ln);
#pragma unroll
    for (int i = 0; i < NP * 3; i++) pv[i] = ldg_pkt(part + i * 24 + ln);
    if (NP > 0) validate<NP * 3>(pv, part + ln, 384, tag);
#pragma unroll
    for (int q = 0; q < NP * 3 / 2; q++) {
        const uint4 y = pv[q + NP * 3 / 2];
        pv[q] = make_uint4(add2(pv[q].x, y.x), add2(pv[q].y, y.y), add2(pv[q].z, y.z), add2(pv[q].w, y.w));
    }
    float x[24];
#pragma unroll
    for (int i = 0; i < 3; i++) {
        x[8 * i] = bf_lo(rv[i].x); x[8 * i + 1] = bf_hi(rv[i].x); x[8 * i + 2] = bf_lo(rv[i].y); x[8 * i + 3] = bf_hi(rv[i].y);
        x[8 * i + 4] = bf_lo(rv[i].z); x[8 * i + 5] = bf_hi(rv[i].z); x[8 * i + 6] = bf_lo(rv[i].w); x[8 * i + 7] = bf_hi(rv[i].w);
    }
    if (NP > 0) {
#pragma unroll
        for (int q = 0; q < NP * 3 / 2; q++) {
            const int i = q % 3;
            x[8 * i] += bf_lo(pv[q].x); x[8 * i + 1] += bf_hi(pv[q].x); x[8 * i + 2] += bf_lo(pv[q].y); x[8 * i + 3] += bf_hi(pv[q].y);
            x[8 * i + 4] += bf_lo(pv[q].z); x[8 * i + 5] += bf_hi(pv[q].z); x[8 * i + 6] += bf_lo(pv[q].w); x[8 * i + 7] += bf_hi(pv[q].w);
        }
#pragma unroll
        for (int i = 0; i < 3; i++) {
            uint32_t w[4];
#pragma unroll
            for (int j = 0; j < 4; j++) { w[j] = pk(x[8 * i + 2 * j], x[8 * i + 2 * j + 1]); x[8 * i + 2 * j] = bf_lo(w[j]); x[8 * i + 2 * j + 1] = bf_hi(w[j]); }
            stg128p(xout + i * 24 + ln, w[0], w[1], w[2], w[3], on);
        }
    }
    if (img) {
        float s = 0.f;
#pragma unroll
        for (int j = 0; j < 24; j++) s += x[j];
        if (!on) s = 0.f;
#pragma unroll
        for (int o = 1; o < 32; o <<= 1) s += __shfl_xor_sync(~0u, s, o);
        const float mean = s * (1.f / DM);
        float v = 0.f;
#pragma unroll
        for (int j = 0; j < 24; j++) { x[j] -= mean; v = fmaf(x[j], x[j], v); }
        if (!on) v = 0.f;
#pragma unroll
        for (int o = 1; o < 32; o <<= 1) v += __shfl_xor_sync(~0u, v, o);
        const float rs = rsqrtf(v * (1.f / DM) + 1e-5f);
        char* dst = img + (ln >> 3) * KB + pos * 128 + (((ln ^ pos) & 7) << 4);
#pragma unroll
        for (int i = 0; i < 3; i++)
            stg128p(dst + i * (3 * KB), pk(x[8 * i] * rs, x[8 * i + 1] * rs), pk(x[8 * i + 2] * rs, x[8 * i + 3] * rs),
                    pk(x[8 * i + 4] * rs, x[8 * i + 5] * rs), pk(x[8 * i + 6] * rs, x[8 * i + 7] * rs), on);
    }
}

DEVI void rows_a(const uint4* xin, int f, int i, int lane, uint32_t ep, int warp) {
    for (int u = 0; u < LAG; u++) cnt_hint(g_cnt + (C_X + u + (f ? 0 : NSEG)) * 8, lane);
#pragma unroll 1
    for (int seg = 0; seg < NSEG; seg++) {
        const int j = seg + f * LAGA, u = seg + f * LAG, row = seg * 32 + i;
        hint_wait(g_cnt + (C_WA + j * 4 + f * 2 + (i & 1)) * 8, 24 * (ep + 1));
        TRG(u, 0);
        row_task<4, 8192>((f ? g_x + 2048 * 72 : xin) + row * 72, g_pa + ((j & (RING - 1)) * 64 + f * 32 + i) * 288,
                    g_x + (f * 4096 + row) * 72, reinterpret_cast<char*>(g_xt + u * 4608 + f * 256), i, lane, ring_tag<NTA>(j, ep));
        TRG(u, 1);
        cnt_add(g_cnt + (C_X + u) * 8, lane);
        TRG(u, 2);
    }
}

__global__ void __launch_bounds__(384, 1)
k_aux(const __nv_bfloat16* __restrict__ x0, const __nv_bfloat16* __restrict__ wqkv, const __nv_bfloat16* __restrict__ wo,
      const __nv_bfloat16* __restrict__ Wo, __nv_bfloat16* __restrict__ out) {
    using namespace ka;
    extern __shared__ unsigned char smem_raw[];
    const uint32_t sb = (smem_u32(smem_raw) + 1023) & ~1023u;
    const int tid = threadIdx.x, lane = tid & 31, warp = __shfl_sync(~0u, tid >> 5, 0), g = lane >> 2, c = lane & 3;
    const int b = blockIdx.x;
    const uint32_t bar = sb + O_BAR;
    const uint32_t ep = __shfl_sync(~0u, ldg32(&g_epoch), 0);

    TRG(79, 0);
    const uint4* xin = reinterpret_cast<const uint4*>(x0);
    if (warp >= 8 || b == 35) {
        asm volatile("setmaxnreg.dec.sync.aligned.u32 128;");
        const int rw = b < 24 ? (warp - 8) * 24 + b : b < 35 ? (warp - 8) * 11 + b - 24 : 96 + 2 * warp;
        if (b < 24 || b == 35) {
#pragma unroll 1
            for (int row = rw; row < 2048; row += (row & 1) ? 23 : 1) {
                if (lane == 0 && b == 35 && row < 2024) prefetch_l2(xin + (row + 24) * 72, 1152);
                row_task<0>(xin + row * 72, nullptr, nullptr, reinterpret_cast<char*>(g_xa + (row >> 5) * 4608), (row & 1) * 16 + ((row & 31) >> 1), lane, 0);
                if (b < 24) { cnt_add(g_cnt + (C_N0 + (row >> 5)) * 8, lane); break; }
                if (row & 1) cnt_add<2>(g_cnt + (C_N0 + (row >> 5)) * 8, lane);
            }
        }
        if (rw < 32) {
            const int f = b < 24, i = rw;
#pragma unroll 1
            for (int seg = 0; seg < NSEG; seg++) {
                const int u = seg + f * LAG, row = seg * 32 + i;
                hint_wait(g_cnt + (C_WB + u * 4 + f * 2 + (i >> 4)) * 8, 24 * (ep + 1));
                TRG(u, 0);
                row_task<8>(g_x + (f * 4096 + row) * 72, g_pb + ((u & (RING - 1)) * 64 + f * 32 + i) * 576,
                            f ? reinterpret_cast<uint4*>(out) + row * 72 : g_x + (2048 + row) * 72,
                            f ? nullptr : reinterpret_cast<char*>(g_xa + (seg + LAGA) * 4608 + 2304), (i & 1) * 16 + (i >> 1), lane, ring_tag(u, ep));
                TRG(u, 1);
                cnt_add(g_cnt + (C_RB + f * NSEG + seg) * 8, lane);
                TRG(u, 2);
            }
            if (f && rw == 31) {
                asm volatile("griddepcontrol.wait;" ::: "memory");
                if (lane == 0) g_epoch = ep + 1;
            }
        } else if (rw < 64 && b < 24) rows_a(xin, 0, rw - 32, lane, ep, warp);
        return;
    }

    if (b < 24) {
        if (warp >= 4) {
            const int kq = b / 6, nq = b % 6;
            uint4 v[17];
#pragma unroll
            for (int q = 0; q < 17; q++) {
                const int it = q * 4 + warp - 4, kr = (it / 3) * 8 + g, s = kq * 11 + (kr >> 4), a = s >> 2, j = s & 3, e = kr & 15;
                const int head = 3 * a + (j < 3 ? j : e >> 1), row = head * 18 + (j < 3 ? e : 16 + (e & 1));
                v[q] = make_uint4(0, 0, 0, 0);
                if (it < 66 && head < 32 && (j < 3 || e < 6)) v[q] = *reinterpret_cast<const uint4*>(wo + row * DM + nq * 96 + (it % 3) * 32 + c * 8);
            }
#pragma unroll
            for (int q = 0; q < 17; q++) {
                const int it = q * 4 + warp - 4;
                const uint32_t ad = sb + O_WA + (it % 3) * 4 * 2816 + (it / 3) * 128 + lane * 4;
                if (it < 66) { sts32(ad, v[q].x); sts32(ad + 2816, v[q].y); sts32(ad + 2 * 2816, v[q].z); sts32(ad + 3 * 2816, v[q].w); }
            }
        } else {
            const int kg = b / 3, ng = b % 3;
            delay(DLYB);
#pragma unroll 1
            for (int bt = 0; bt < 4; bt++) {
                uint4 v[24];
#pragma unroll
                for (int q = 0; q < 24; q++)
                    v[q] = *reinterpret_cast<const uint4*>(Wo + (size_t)(kg * 512 + (bt * 4 + q / 6) * 32 + warp * 8 + g) * DM + ng * 192 + (q % 6) * 32 + c * 8);
#pragma unroll
                for (int q = 0; q < 24; q++) {
                    const uint32_t ad = sb + (q % 6) * 4 * 8192 + ((bt * 4 + q / 6) * 4 + warp) * 128 + lane * 4;
                    sts32(ad, v[q].x); sts32(ad + 8192, v[q].y); sts32(ad + 2 * 8192, v[q].z); sts32(ad + 3 * 8192, v[q].w);
                }
            }
        }
        fence_async_smem();
        bar_sync(2 + (warp >> 2), 128);
    } else {
        for (int i = tid; i < 2048; i += 256) sts128(sb + O_RING + i * 16, 0, 0, 0, 0);
        if (tid < 17) mbar_init(bar + tid * 8, tid >= 4 && tid < 8 ? 4 : 1);
        fence_async_smem();
        bar_sync(1, 256);
    }
    TRG(79, 1);
    const int wq = warp & 3;

    if (warp < 4) {
        asm volatile("setmaxnreg.inc.sync.aligned.u32 256;");
        if (b < 24) {
            const int kg = b / 3, ng = b % 3;
            const uint32_t blo = ((sb >> 4) & 0x3fff) | (8u << 16);
            uint4 a[32];
            bool pre = false;
#pragma unroll 1
            for (int u = 0; u < NT; u++) {
                const uint32_t tag = ring_tag(u, ep);
                const uint4* src = g_o + (((u & (RING - 1)) * 256 + kg * 32) * 4 + wq) * 32 + lane;
                if (!pre) {
                    hint_wait(g_cnt + (C_O + u * 8 + kg) * 8, 12 * (ep + 1));
#pragma unroll
                    for (int i = 0; i < VG; i++) a[i] = ldg_pkt(src + i * 128);
                }
                TRG(u, 0);
                float d[96];
                validate<VG>(a, src, 2048, tag);
#pragma unroll
                for (int i = VG; i < 32; i++) a[i] = ldg_pkt(src + i * 128);
                wg_fence();
#pragma unroll
                for (int i = 0; i < 32; i++) {
                    if (i == VG) { validate<32 - VG>(a + VG, src + VG * 128, 2048, tag); wg_fence(); }
                    wgmma_rs192t(d, a[i].x, a[i].y, a[i].z, a[i].w, mkdesc(blo + i * 16, 512), i > 0);
                    if (i == 23 || i == 31) wg_commit();
                }
                wg_wait<1>();
                pre = u + 1 < NT && __all_sync(~0u, ldg_word(g_cnt + (C_O + (u + 1) * 8 + kg) * 8) >= 12 * (ep + 1));
                if (pre) {
                    const uint4* nx = g_o + ((((u + 1) & (RING - 1)) * 256 + kg * 32) * 4 + wq) * 32 + lane;
#pragma unroll
                    for (int i = 0; i < VG; i++) a[i] = ldg_pkt(nx + i * 128);
                }
                wg_wait<0>();
                TRG(u, 1);
                uint4* dst = g_pb + (((u & (RING - 1)) * 64 + wq * 16 + g) * 8 + kg) * 72 + ng * 24 + c;
#pragma unroll
                for (int m = 0; m < 6; m++) {
                    if (m == HB) cnt_hint(g_cnt + (C_WB + u * 4 + wq) * 8, lane);
                    stg128(dst + 4 * m, (pk(d[16 * m], d[16 * m + 1]) & ~1u) | tag, pk(d[16 * m + 4], d[16 * m + 5]), pk(d[16 * m + 8], d[16 * m + 9]), pk(d[16 * m + 12], d[16 * m + 13]));
                    stg128(dst + 4 * m + 8 * 576, (pk(d[16 * m + 2], d[16 * m + 3]) & ~1u) | tag, pk(d[16 * m + 6], d[16 * m + 7]), pk(d[16 * m + 10], d[16 * m + 11]), pk(d[16 * m + 14], d[16 * m + 15]));
                }
                TRG(u, 3);
            }
        } else {
            const int a = b - 24, f = wq >> 1;
            const uint32_t blo = ((sb >> 4) & 0x3fff) | (8u << 16), alo = (((sb + O_RING) >> 4) & 0x3fff) | (1u << 16);
            const bool m0 = 2 * c <= g, m1 = 2 * c + 1 <= g;
            const uint32_t M = (m0 ? 0xffffu : 0u) | (m1 ? 0xffff0000u : 0u);
            uint32_t kh[7], vh[7];
#pragma unroll
            for (int i = 0; i < 7; i++) kh[i] = vh[i] = 0;
            int it = 0;
#pragma unroll 1
            for (int u = 0; u < NTA; u++) {
                float d[84];
#pragma unroll 1
                for (int kb = 0; kb < 9; kb++, it++) {
                    mbar_wait(bar + (it & 3) * 8, (it >> 2) & 1);
                    if (u == 0) mbar_wait(bar + 64 + kb * 8, 0);
                    if (kb == 0) TRG(u, 0);
                    wg_fence();
#pragma unroll
                    for (int q = 0; q < 4; q++)
                        wgmma_ss168t(d, mkdesc(alo + (it & 3) * 512 + q * 2, km::DESC_HI), mkdesc(blo + kb * (A_KB >> 4) + q * 16, 64), kb + q > 0);
                    wg_commit();
                    wg_wait<1>();
                    mbar_arrive(bar + 32 + ((it - 1) & 3) * 8, lane == 0 && kb > 0);
                }
                wg_wait<0>();
                mbar_arrive(bar + 32 + ((it - 1) & 3) * 8, lane == 0);
                TRG(u, 1);
                const bool first = u == f * LAGA;
                const uint32_t tag = ring_tag<NTA>(u, ep);
                const uint32_t qt0 = pk(d[72], d[73]), qt1 = pk(d[74], d[75]), kt0 = pk(d[76], d[77]), kt1 = pk(d[78], d[79]);
                const uint32_t vt0 = movm(pk(d[80], d[81])), vt1 = movm(pk(d[82], d[83]));
                float ot[4] = {0, 0, 0, 0};
                uint4* dst = g_oa + (((u & (RING - 1)) * 4 + wq) * 44 + a * 4) * 32 + lane;
#pragma unroll
                for (int h = 0; h < 3; h++) {
                    const float* q = d + 8 * h; const float* k = d + 24 + 8 * h; const float* v = d + 48 + 8 * h;
                    const uint32_t q0 = pk(q[0], q[1]), q1 = pk(q[2], q[3]), q2 = pk(q[4], q[5]), q3 = pk(q[6], q[7]);
                    const uint32_t k0 = pk(k[0], k[1]), k1 = pk(k[4], k[5]), k2 = pk(k[2], k[3]), k3 = pk(k[6], k[7]);
                    const uint32_t v0 = movm(pk(v[0], v[1])), v1 = movm(pk(v[2], v[3])), v2 = movm(pk(v[4], v[5])), v3 = movm(pk(v[6], v[7]));
                    const uint32_t t0 = c == h ? qt0 : 0, t1 = c == h ? qt1 : 0;
                    float sp[4] = {0, 0, 0, 0}, sl[4] = {0, 0, 0, 0}, sh[4] = {0, 0, 0, 0};
                    mma16(sp, q0, q1, q2, q3, kh[2 * h], kh[2 * h + 1]); mma16(sl, q0, q1, q2, q3, k0, k1); mma16(sh, q0, q1, q2, q3, k2, k3);
                    mma8(sp, t0, t1, kh[6]); mma8(sl, t0, t1, kt0); mma8(sh, t0, t1, kt1);
                    float x0_ = m0 ? sl[0] : first ? -INFINITY : sp[0], x1_ = m1 ? sl[1] : first ? -INFINITY : sp[1];
                    float y0_ = m0 ? sh[2] : sl[2], y1_ = m1 ? sh[3] : sl[3];
                    float mx = fmaxf(x0_, x1_), my = fmaxf(y0_, y1_);
#pragma unroll
                    for (int o = 1; o < 4; o <<= 1) { mx = fmaxf(mx, __shfl_xor_sync(~0u, mx, o)); my = fmaxf(my, __shfl_xor_sync(~0u, my, o)); }
                    mx *= -SC; my *= -SC;
                    x0_ = ex2(fmaf(x0_, SC, mx)); x1_ = ex2(fmaf(x1_, SC, mx)); y0_ = ex2(fmaf(y0_, SC, my)); y1_ = ex2(fmaf(y1_, SC, my));
                    float lx = x0_ + x1_, ly = y0_ + y1_;
#pragma unroll
                    for (int o = 1; o < 4; o <<= 1) { lx += __shfl_xor_sync(~0u, lx, o); ly += __shfl_xor_sync(~0u, ly, o); }
                    lx = rcp(lx); ly = rcp(ly);
                    const uint32_t px = pk(x0_ * lx, x1_ * lx), py = pk(y0_ * ly, y1_ * ly);
                    const uint32_t hm = (g >> 1) == h ? ~0u : 0u;
                    float o0[4] = {0, 0, 0, 0}, o1[4] = {0, 0, 0, 0};
                    mma16(o0, px & M, py & ~M, 0, py & M, v0, v1); mma16(o1, px & M, py & ~M, 0, py & M, v2, v3);
                    mma16(ot, px & M, py & ~M, 0, py & M, vt0 & hm, vt1 & hm);
                    mma8(o0, px & ~M, 0, vh[2 * h]); mma8(o1, px & ~M, 0, vh[2 * h + 1]); mma8(ot, px & ~M, 0, vh[6] & hm);
                    if (h == HA) cnt_hint(g_cnt + (C_A + u * 4 + wq) * 8, lane);
                    stg128(dst + h * 32, (pk(o0[0], o0[1]) & ~1u) | tag, pk(o0[2], o0[3]), pk(o1[0], o1[1]), pk(o1[2], o1[3]));
                    kh[2 * h] = k2; kh[2 * h + 1] = k3; vh[2 * h] = v1; vh[2 * h + 1] = v3;
                }
                kh[6] = kt1; vh[6] = vt1;
                stg128(dst + 96, (pk(ot[0], ot[1]) & ~1u) | tag, pk(ot[2], ot[3]), 0, 0);
                TRG(u, 2);
            }
        }
    } else {
        asm volatile("setmaxnreg.dec.sync.aligned.u32 120;");
        if (b < 24) {
            const int kq = b / 6, nq = b % 6;
            const uint32_t blo = (((sb + O_WA) >> 4) & 0x3fff) | (8u << 16);
#pragma unroll 1
            for (int u = 0; u < NTA; u++) {
                hint_wait(g_cnt + (C_A + u * 4 + wq) * 8, 11 * (ep + 1));
                const uint32_t tag = ring_tag<NTA>(u, ep);
                TRG(u, 0);
                const uint4* src = g_oa + (((u & (RING - 1)) * 4 + wq) * 44 + kq * 11) * 32 + lane;
                uint4 a[11];
                float d[48];
#pragma unroll
                for (int i = 0; i < 11; i++) a[i] = ldg_pkt(src + i * 32);
                validate<11>(a, src, 512, tag);
                wg_fence();
#pragma unroll
                for (int i = 0; i < 11; i++) wgmma_rs96t(d, a[i].x, a[i].y, a[i].z, a[i].w, mkdesc(blo + i * 16, 176), i > 0);
                wg_commit();
                wg_wait<0>();
                TRG(u, 1);
                uint4* dst = g_pa + (((u & (RING - 1)) * 64 + (wq >> 1) * 32 + 2 * g + (wq & 1)) * 4 + kq) * 72 + nq * 12 + c;
#pragma unroll
                for (int m = 0; m < 3; m++) {
                    if (m == HW) cnt_hint(g_cnt + (C_WA + u * 4 + wq) * 8, lane);
                    stg128(dst + 4 * m, (pk(d[16 * m], d[16 * m + 1]) & ~1u) | tag, pk(d[16 * m + 4], d[16 * m + 5]), pk(d[16 * m + 8], d[16 * m + 9]), pk(d[16 * m + 12], d[16 * m + 13]));
                    stg128(dst + 4 * m + 16 * 288, (pk(d[16 * m + 2], d[16 * m + 3]) & ~1u) | tag, pk(d[16 * m + 6], d[16 * m + 7]), pk(d[16 * m + 10], d[16 * m + 11]), pk(d[16 * m + 14], d[16 * m + 15]));
                }
                TRG(u, 3);
            }
        } else if (warp == 4) {
            mbar_expect(bar + 64 + lane * 8, A_KB, lane < 9);
            int it = 0;
#pragma unroll 1
            for (int u = 0; u < NTA; u++) {
                if (u == 0) { cnt_wait(g_cnt + C_W * 8, 96 * (ep + 1)); TRG(78, 0); }
                if (u < NSEG) cnt_wait(g_cnt + (C_N0 + u) * 8, 32 * (ep + 1));
                if (u > LAGA + LAG) cnt_wait(g_cnt + (C_RB + NSEG + u - LAGA - LAG - 1) * 8, 32 * (ep + 1));
                if (u >= LAGA) cnt_wait(g_cnt + (C_RB + u - LAGA) * 8, 32 * (ep + 1));
                TRG(u, 0);
                asm volatile("fence.proxy.async.global;" ::: "memory");
                const bool on = lane == 0 ? u < NSEG : lane == 1 && u >= LAGA;
#pragma unroll 1
                for (int kb = 0; kb < 9; kb++, it++) {
                    if (it >= 4) mbar_wait(bar + 32 + (it & 3) * 8, ((it >> 2) - 1) & 1);
                    mbar_expect(bar + (it & 3) * 8, u < NSEG && u >= LAGA ? 8192 : 4096, lane == 0);
                    asm volatile("{.reg .pred p; setp.ne.u32 p, %3, 0; @p cp.async.bulk.shared::cluster.global.mbarrier::complete_tx::bytes [%0], [%1], 4096, [%2];}"
                        :: "r"(sb + O_RING + (it & 3) * 8192 + (lane & 1) * 4096), "l"(g_xa + u * 4608 + (lane & 1) * 2304 + kb * 256), "r"(bar + (it & 3) * 8), "r"((uint32_t)on) : "memory");
                    if (u == 0) asm volatile("{.reg .pred p; setp.ne.u32 p, %4, 0; @p cp.async.bulk.shared::cluster.global.mbarrier::complete_tx::bytes [%0], [%1], %3, [%2];}"
                        :: "r"(sb + lane * A_KB), "l"(g_wa + ((b - 24) * 9 + lane) * (A_KB / 16)), "r"(bar + 64 + lane * 8), "n"(A_KB),
                           "r"((uint32_t)(lane < 9 && kb == (lane < 4 ? lane : lane < 6 ? 3 : lane - 2))) : "memory");
                }
            }
        } else if ((warp - 5) * 11 + b - 24 < 32) rows_a(xin, 1, (warp - 5) * 11 + b - 24, lane, ep, warp);
    }
}

extern "C" void kernel_launch(void* const* d_in, const int* in_sizes, int n_in, void* d_out, int out_size) {
    const __nv_bfloat16* x = (const __nv_bfloat16*)d_in[0];
    const __nv_bfloat16* wqkv = (const __nv_bfloat16*)d_in[1];
    const __nv_bfloat16* wo = (const __nv_bfloat16*)d_in[2];
    const __nv_bfloat16* mem0 = (const __nv_bfloat16*)d_in[4];
    const __nv_bfloat16* Wq = (const __nv_bfloat16*)d_in[5];
    const __nv_bfloat16* Wk = (const __nv_bfloat16*)d_in[6];
    const __nv_bfloat16* Wv = (const __nv_bfloat16*)d_in[7];
    const __nv_bfloat16* Wo = (const __nv_bfloat16*)d_in[8];
    cudaFuncSetAttribute(k_main, cudaFuncAttributeMaxDynamicSharedMemorySize, km::SMEM);
    cudaFuncSetAttribute(k_aux, cudaFuncAttributeMaxDynamicSharedMemorySize, ka::SMEM);
    cudaStream_t s = cudaStreamPerThread;
    k_main<<<96, 384, km::SMEM, s>>>(x, wqkv, wo, mem0, Wq, Wk, Wv, Wo);
    cudaLaunchConfig_t cfg = {};
    cudaLaunchAttribute at[1];
    at[0].id = cudaLaunchAttributeProgrammaticStreamSerialization;
    at[0].val.programmaticStreamSerializationAllowed = 1;
    cfg.stream = s; cfg.attrs = at; cfg.numAttrs = 1;
    cfg.gridDim = dim3(36); cfg.blockDim = dim3(384); cfg.dynamicSmemBytes = ka::SMEM;
    cudaLaunchKernelEx(&cfg, k_aux, x, wqkv, wo, Wo, (__nv_bfloat16*)d_out);
}
```

```cpp
#include <cuda_runtime.h>
#include <cuda_bf16.h>
#include <stdint.h>

#define LAG 7
constexpr int NSEG = 64;
constexpr int NT = NSEG + LAG;
#define AHEAD 1
constexpr int LAGA = LAG + AHEAD;
constexpr int NTA = NSEG + LAGA;
#define RING_ 8
constexpr int RING = RING_;
constexpr int DM = 576;

__device__ __align__(1024) uint4 g_xt[NT * 2 * 9 * 256];
__device__ __align__(1024) uint4 g_o[RING * 4 * 256 * 32];
__device__ __align__(1024) uint4 g_ex[2 * 131072];
__device__ unsigned g_side[96];
__device__ __align__(1024) uint4 g_pb[RING * 64 * 8 * 72];
__device__ __align__(1024) uint4 g_pa[RING * 64 * 4 * 72];
__device__ __align__(1024) uint4 g_oa[RING * 4 * 44 * 32];
__device__ __align__(1024) uint4 g_xa[NTA * 2 * 9 * 256];
__device__ __align__(1024) uint4 g_wa[11 * 9 * 21 * 64];
__device__ __align__(1024) uint4 g_x[3 * 2048 * 72];

constexpr int C_X = 0;
constexpr int C_O = C_X + NT;
constexpr int C_WB = C_O + NT * 8;
constexpr int C_RB = C_WB + NT * 4;
constexpr int C_A = C_RB + 2 * NSEG;
constexpr int C_WA = C_A + NTA * 4;
constexpr int C_N0 = C_WA + NTA * 4;
constexpr int C_W = C_N0 + NSEG;
constexpr int C_DONE = C_W + 1;
constexpr int C_TOTAL = C_DONE + 1;
__device__ __align__(1024) unsigned g_cnt[C_TOTAL * 8];
__device__ unsigned g_epoch;

#define TR(i)
#define TR1(i)
#define TR_ON(t)
#define TR_INIT(base)
#define TR_DUMP(slot)
#define TRG(t, i)
constexpr int TR_BYTES = 0;

#define DEVI __device__ __forceinline__
DEVI uint32_t smem_u32(const void* p) { return (uint32_t)__cvta_generic_to_shared(p); }
DEVI uint32_t pk(float lo, float hi) { uint32_t r; asm("cvt.rn.bf16x2.f32 %0, %1, %2;" : "=r"(r) : "f"(hi), "f"(lo)); return r; }
DEVI float bf_lo(uint32_t u) { return __uint_as_float(u << 16); }
DEVI float bf_hi(uint32_t u) { return __uint_as_float(u & 0xffff0000u); }
DEVI uint32_t add2(uint32_t a, uint32_t b) { uint32_t d; asm("add.rn.bf16x2 %0, %1, %2;" : "=r"(d) : "r"(a), "r"(b)); return d; }
DEVI uint32_t movm(uint32_t a) { uint32_t d; asm volatile("movmatrix.sync.aligned.m8n8.trans.b16 %0, %1;" : "=r"(d) : "r"(a)); return d; }
DEVI float2 shfl2(float a, float b, int o) {
    float2 r; asm volatile("shfl.sync.bfly.b32 %0, %2, %4, 31, -1; shfl.sync.bfly.b32 %1, %3, %4, 31, -1;" : "=&f"(r.x), "=f"(r.y) : "f"(a), "f"(b), "r"(o)); return r;
}
DEVI float ex2(float x) { float y; asm("ex2.approx.ftz.f32 %0, %1;" : "=f"(y) : "f"(x)); return y; }
DEVI float rcp(float x) { float y; asm("rcp.approx.ftz.f32 %0, %1;" : "=f"(y) : "f"(x)); return y; }
DEVI void mma16(float (&d)[4], uint32_t a0, uint32_t a1, uint32_t a2, uint32_t a3, uint32_t b0, uint32_t b1) {
    asm volatile("mma.sync.aligned.m16n8k16.row.col.f32.bf16.bf16.f32 {%0,%1,%2,%3}, {%4,%5,%6,%7}, {%8,%9}, {%0,%1,%2,%3};"
        : "+f"(d[0]), "+f"(d[1]), "+f"(d[2]), "+f"(d[3]) : "r"(a0), "r"(a1), "r"(a2), "r"(a3), "r"(b0), "r"(b1));
}
DEVI void mma8(float (&d)[4], uint32_t a0, uint32_t a1, uint32_t b0) {
    asm volatile("mma.sync.aligned.m16n8k8.row.col.f32.bf16.bf16.f32 {%0,%1,%2,%3}, {%4,%5}, {%6}, {%0,%1,%2,%3};"
        : "+f"(d[0]), "+f"(d[1]), "+f"(d[2]), "+f"(d[3]) : "r"(a0), "r"(a1), "r"(b0));
}
DEVI uint4 lds128(uint32_t a) { uint4 v; asm volatile("ld.shared.v4.u32 {%0,%1,%2,%3}, [%4];" : "=r"(v.x), "=r"(v.y), "=r"(v.z), "=r"(v.w) : "r"(a) : "memory"); return v; }
DEVI uint2 lds64(uint32_t a) { uint2 v; asm volatile("ld.shared.v2.u32 {%0,%1}, [%2];" : "=r"(v.x), "=r"(v.y) : "r"(a) : "memory"); return v; }
DEVI uint32_t lds32(uint32_t a) { uint32_t v; asm volatile("ld.shared.u32 %0, [%1];" : "=r"(v) : "r"(a) : "memory"); return v; }
DEVI uint32_t lds32v(uint32_t a) { uint32_t v; asm volatile("ld.volatile.shared.u32 %0, [%1];" : "=r"(v) : "r"(a) : "memory"); return v; }
DEVI uint4 lds128v(uint32_t a) { uint4 v; asm volatile("ld.volatile.shared.v4.u32 {%0,%1,%2,%3}, [%4];" : "=r"(v.x), "=r"(v.y), "=r"(v.z), "=r"(v.w) : "r"(a) : "memory"); return v; }
DEVI uint32_t lds16(uint32_t a) { uint32_t v; asm volatile("ld.shared.u16 %0, [%1];" : "=r"(v) : "r"(a) : "memory"); return v; }
DEVI uint4 ldsm4(uint32_t a) { uint4 v; asm volatile("ldmatrix.sync.aligned.m8n8.x4.shared.b16 {%0,%1,%2,%3}, [%4];" : "=r"(v.x), "=r"(v.y), "=r"(v.z), "=r"(v.w) : "r"(a) : "memory"); return v; }
DEVI uint4 ldsm4p(uint32_t a, bool pred) {
    uint4 v; asm volatile("{.reg .pred p; setp.ne.u32 p, %5, 0; @p ldmatrix.sync.aligned.m8n8.x4.shared.b16 {%0,%1,%2,%3}, [%4];}" : "=r"(v.x), "=r"(v.y), "=r"(v.z), "=r"(v.w) : "r"(a), "r"((uint32_t)pred) : "memory"); return v;
}
DEVI uint4 ldsm4t(uint32_t a) { uint4 v; asm volatile("ldmatrix.sync.aligned.m8n8.x4.trans.shared.b16 {%0,%1,%2,%3}, [%4];" : "=r"(v.x), "=r"(v.y), "=r"(v.z), "=r"(v.w) : "r"(a) : "memory"); return v; }
DEVI uint2 ldsm2(uint32_t a) { uint2 v; asm volatile("ldmatrix.sync.aligned.m8n8.x2.shared.b16 {%0,%1}, [%2];" : "=r"(v.x), "=r"(v.y) : "r"(a) : "memory"); return v; }
DEVI void stsm4t(uint32_t a, uint32_t x, uint32_t y, uint32_t z, uint32_t w) { asm volatile("stmatrix.sync.aligned.m8n8.x4.trans.shared.b16 [%0], {%1,%2,%3,%4};" :: "r"(a), "r"(x), "r"(y), "r"(z), "r"(w) : "memory"); }
DEVI void sts128(uint32_t a, uint32_t x, uint32_t y, uint32_t z, uint32_t w) { asm volatile("st.shared.v4.u32 [%0], {%1,%2,%3,%4};" :: "r"(a), "r"(x), "r"(y), "r"(z), "r"(w) : "memory"); }
DEVI void sts64(uint32_t a, uint32_t x, uint32_t y) { asm volatile("st.shared.v2.u32 [%0], {%1,%2};" :: "r"(a), "r"(x), "r"(y) : "memory"); }
DEVI void sts32(uint32_t a, uint32_t x) { asm volatile("st.shared.u32 [%0], %1;" :: "r"(a), "r"(x) : "memory"); }
DEVI void sts32p(uint32_t a, uint32_t x, bool pred) { asm volatile("{.reg .pred p; setp.ne.u32 p, %2, 0; @p st.shared.u32 [%0], %1;}" :: "r"(a), "r"(x), "r"((uint32_t)pred) : "memory"); }
DEVI void sta128(uint32_t a, uint32_t x, uint32_t y, uint32_t z, uint32_t w, uint32_t bar) {
    asm volatile("st.async.weak.shared::cluster.mbarrier::complete_tx::bytes.v4.b32 [%0], {%1,%2,%3,%4}, [%5];" :: "r"(a), "r"(x), "r"(y), "r"(z), "r"(w), "r"(bar) : "memory");
}
DEVI void sta128p(uint32_t a, uint32_t x, uint32_t y, uint32_t z, uint32_t w, uint32_t bar, bool pred) {
    asm volatile("{.reg .pred p; setp.ne.u32 p, %6, 0; @p st.async.weak.shared::cluster.mbarrier::complete_tx::bytes.v4.b32 [%0], {%1,%2,%3,%4}, [%5];}" :: "r"(a), "r"(x), "r"(y), "r"(z), "r"(w), "r"(bar), "r"((uint32_t)pred) : "memory");
}
DEVI void sta64(uint32_t a, uint32_t x, uint32_t y, uint32_t bar) {
    asm volatile("st.async.weak.shared::cluster.mbarrier::complete_tx::bytes.v2.b32 [%0], {%1,%2}, [%3];" :: "r"(a), "r"(x), "r"(y), "r"(bar) : "memory");
}
DEVI void sta32(uint32_t a, uint32_t x, uint32_t bar) {
    asm volatile("st.async.weak.shared::cluster.mbarrier::complete_tx::bytes.b32 [%0], %1, [%2];" :: "r"(a), "r"(x), "r"(bar) : "memory");
}
DEVI uint4 ldg_pkt(const void* p) {
    uint4 v;
    asm volatile("ld.relaxed.gpu.global.v4.u32 {%0,%1,%2,%3}, [%4];" : "=r"(v.x), "=r"(v.y), "=r"(v.z), "=r"(v.w) : "l"(p) : "memory");
    return v;
}
DEVI void ldg_pkt_if(uint4& v, const void* p, bool pred) {
    asm volatile("{.reg .pred p; setp.ne.u32 p, %5, 0; @p ld.relaxed.gpu.global.v4.u32 {%0,%1,%2,%3}, [%4];}"
        : "+r"(v.x), "+r"(v.y), "+r"(v.z), "+r"(v.w) : "l"(p), "r"((uint32_t)pred) : "memory");
}
DEVI void ldg_pkt_retry(uint4& v, const void* p, uint32_t tag) {
    asm volatile("{.reg .pred p; .reg .b32 t; lop3.b32 t, %0, %5, 1, 0x28; setp.ne.u32 p, t, 0; @p ld.relaxed.gpu.global.v4.u32 {%0,%1,%2,%3}, [%4];}"
        : "+r"(v.x), "+r"(v.y), "+r"(v.z), "+r"(v.w) : "l"(p), "r"(tag) : "memory");
}
DEVI void stg_pkt(void* p, uint32_t x, uint32_t y, uint32_t z, uint32_t w) {
    asm volatile("st.relaxed.gpu.global.v4.u32 [%0], {%1,%2,%3,%4};" :: "l"(p), "r"(x), "r"(y), "r"(z), "r"(w) : "memory");
}
DEVI uint32_t ldg_word(const void* p) { uint32_t v; asm volatile("ld.relaxed.gpu.global.u32 %0, [%1];" : "=r"(v) : "l"(p) : "memory"); return v; }
DEVI void stg_word(void* p, uint32_t x, bool pred) {
    asm volatile("{.reg .pred p; setp.ne.u32 p, %2, 0; @p st.relaxed.gpu.global.u32 [%0], %1;}" :: "l"(p), "r"(x), "r"((uint32_t)pred) : "memory");
}
DEVI uint2 ldg64nc(const void* p) { uint2 v; asm volatile("ld.global.nc.L1::no_allocate.v2.u32 {%0,%1}, [%2];" : "=r"(v.x), "=r"(v.y) : "l"(p)); return v; }
DEVI void prefetch_l2(const void* p, uint32_t bytes) { asm volatile("cp.async.bulk.prefetch.L2.global [%0], %1;" :: "l"(p), "r"(bytes) : "memory"); }
DEVI uint4 ldg128(const void* p) { uint4 v; asm volatile("ld.global.cg.v4.u32 {%0,%1,%2,%3}, [%4];" : "=r"(v.x), "=r"(v.y), "=r"(v.z), "=r"(v.w) : "l"(p) : "memory"); return v; }
DEVI uint2 ldg64(const void* p) { uint2 v; asm volatile("ld.global.cg.v2.u32 {%0,%1}, [%2];" : "=r"(v.x), "=r"(v.y) : "l"(p) : "memory"); return v; }
DEVI uint32_t ldg32(const void* p) { uint32_t v; asm volatile("ld.global.cg.u32 %0, [%1];" : "=r"(v) : "l"(p) : "memory"); return v; }
DEVI void stg128(void* p, uint32_t x, uint32_t y, uint32_t z, uint32_t w) { asm volatile("st.global.cg.v4.u32 [%0], {%1,%2,%3,%4};" :: "l"(p), "r"(x), "r"(y), "r"(z), "r"(w) : "memory"); }
DEVI void stg128p(void* p, uint32_t x, uint32_t y, uint32_t z, uint32_t w, bool pred) { asm volatile("{.reg .pred p; setp.ne.u32 p, %5, 0; @p st.global.cg.v4.u32 [%0], {%1,%2,%3,%4};}" :: "l"(p), "r"(x), "r"(y), "r"(z), "r"(w), "r"((uint32_t)pred) : "memory"); }
DEVI void stg64(void* p, uint32_t x, uint32_t y) { asm volatile("st.global.cg.v2.u32 [%0], {%1,%2};" :: "l"(p), "r"(x), "r"(y) : "memory"); }
DEVI void stg32(void* p, uint32_t x) { asm volatile("st.global.cg.u32 [%0], %1;" :: "l"(p), "r"(x) : "memory"); }
DEVI void cp16(uint32_t dst, const void* src) { asm volatile("cp.async.cg.shared.global [%0], [%1], 16;" :: "r"(dst), "l"(src) : "memory"); }
DEVI void cp16_if(uint32_t dst, const void* src, bool pred) { asm volatile("{.reg .pred p; setp.ne.u32 p, %2, 0; @p cp.async.cg.shared.global [%0], [%1], 16;}" :: "r"(dst), "l"(src), "r"((uint32_t)pred) : "memory"); }
DEVI void cp_commit() { asm volatile("cp.async.commit_group;" ::: "memory"); }
DEVI void cp4(uint32_t dst, const void* src) { asm volatile("cp.async.ca.shared.global [%0], [%1], 4;" :: "r"(dst), "l"(src) : "memory"); }
template <int N> DEVI void cp_wait() { asm volatile("cp.async.wait_group %0;" :: "n"(N) : "memory"); }
DEVI void cp_wait_all() { asm volatile("cp.async.wait_all;" ::: "memory"); }
DEVI void bar_sync(int id, int n) { asm volatile("bar.sync %0, %1;" :: "r"(id), "r"(n) : "memory"); }
DEVI void bar_arrive(int id, int n) { asm volatile("bar.arrive %0, %1;" :: "r"(id), "r"(n) : "memory"); }
DEVI void fence_async_smem() { asm volatile("fence.proxy.async.shared::cta;" ::: "memory"); }
DEVI void fence_async_global() { asm volatile("fence.proxy.async.global;" ::: "memory"); }
DEVI void mbar_init(uint32_t b, int n) { asm volatile("mbarrier.init.shared.b64 [%0], %1;" :: "r"(b), "r"(n) : "memory"); }
DEVI void mbar_expect(uint32_t b, uint32_t bytes, bool pred) {
    asm volatile("{.reg .pred p; setp.ne.u32 p, %2, 0; @p mbarrier.arrive.expect_tx.shared.b64 _, [%0], %1;}" :: "r"(b), "r"(bytes), "r"((uint32_t)pred) : "memory");
}
DEVI void mbar_arrive(uint32_t b, bool pred) { asm volatile("{.reg .pred p; setp.ne.u32 p, %1, 0; @p mbarrier.arrive.shared.b64 _, [%0];}" :: "r"(b), "r"((uint32_t)pred) : "memory"); }
DEVI void mbar_arrive_all3(uint32_t b, uint32_t lane) {
    asm volatile("{.reg .pred p; .reg .u32 a; setp.lt.u32 p, %1, 3; @p mapa.shared::cluster.u32 a, %0, %1; @p mbarrier.arrive.relaxed.cluster.shared::cluster.b64 _, [a];}" :: "r"(b), "r"(lane) : "memory");
}
#define FAULT "or.b32 n, n, 1; st.volatile.shared.u32 [n], n;\n"
#define LIM1 "400000"
#define LIM2 "2000000"
DEVI void fault_if(bool p, uint32_t n) { asm volatile("{.reg .pred p; setp.ne.u32 p, %0, 0; @p st.volatile.shared.u32 [%1], %1;}" :: "r"((uint32_t)p), "r"(n | 1) : "memory"); }
DEVI void mbar_wait(uint32_t b, uint32_t parity) {
    asm volatile("{.reg .pred p; .reg .u32 n;\n"
        "mbarrier.try_wait.parity.shared::cta.b64 p, [%0], %1;\n"
        "@p bra.uni D%=;\n"
        "mov.u32 n, 0;\n"
        "W%=: mbarrier.try_wait.parity.shared::cta.b64 p, [%0], %1;\n"
        "@p bra.uni D%=;\n"
        "add.u32 n, n, 1; setp.lt.u32 p, n, " LIM1 "; @p bra.uni W%=;\n"
        FAULT
        "D%=:}" :: "r"(b), "r"(parity) : "memory");
}
constexpr int POLL_LIMIT = 2000000;
DEVI void cnt_wait(const unsigned* c, unsigned target) {
    asm volatile("{.reg .pred p; .reg .u32 n, v;\n"
        "ld.acquire.gpu.global.u32 v, [%0];\n"
        "setp.ge.u32 p, v, %1; vote.sync.all.pred p, p, 0xffffffff; @p bra.uni D%=;\n"
        "mov.u32 n, 0;\n"
        "W%=: ld.acquire.gpu.global.u32 v, [%0];\n"
        "setp.ge.u32 p, v, %1; vote.sync.all.pred p, p, 0xffffffff; @p bra.uni D%=;\n"
        "add.u32 n, n, 1; setp.lt.u32 p, n, " LIM2 "; @p bra.uni W%=;\n"
        FAULT
        "D%=:}" :: "l"(c), "r"(target) : "memory");
}
DEVI void hint_wait(const unsigned* c, unsigned target) {
    asm volatile("{.reg .pred p; .reg .u32 n, v;\n"
        "ld.relaxed.gpu.global.u32 v, [%0];\n"
        "setp.ge.u32 p, v, %1; vote.sync.all.pred p, p, 0xffffffff; @p bra.uni D%=;\n"
        "mov.u32 n, 0;\n"
        "W%=: ld.relaxed.gpu.global.u32 v, [%0];\n"
        "setp.ge.u32 p, v, %1; vote.sync.all.pred p, p, 0xffffffff; @p bra.uni D%=;\n"
        "add.u32 n, n, 1; setp.lt.u32 p, n, " LIM2 "; @p bra.uni W%=;\n"
        FAULT
        "D%=:}" :: "l"(c), "r"(target) : "memory");
}
DEVI bool cnt_poll(const unsigned* c, unsigned target, uint32_t b, uint32_t parity) {
    uint32_t r;
    asm volatile("{.reg .pred p; .reg .u32 n, v;\n"
        "mov.u32 n, 0; mov.u32 %0, 0;\n"
        "W%=: ld.acquire.gpu.global.u32 v, [%1];\n"
        "setp.ge.u32 p, v, %2; vote.sync.all.pred p, p, 0xffffffff; @p bra.uni D%=;\n"
        "mbarrier.test_wait.parity.shared::cta.b64 p, [%3], %4;\n"
        "add.u32 n, n, 1; setp.gt.or.u32 p, n, 1000, p; vote.sync.any.pred p, p, 0xffffffff; @!p bra.uni W%=;\n"
        "mov.u32 %0, 1;\n"
        "D%=:}" : "=r"(r) : "l"(c), "r"(target), "r"(b), "r"(parity) : "memory");
    return r;
}
template <int N = 1> DEVI void cnt_add(unsigned* c, int lane) {
    asm volatile("{.reg .pred p; setp.eq.u32 p, %1, 0; fence.acq_rel.gpu; bar.warp.sync 0xffffffff; @p red.relaxed.gpu.global.add.u32 [%0], %2;}" :: "l"(c + lane), "r"(lane), "n"(N) : "memory");
}
DEVI void cnt_hint(unsigned* c, int lane) {
    asm volatile("{.reg .pred p; setp.eq.u32 p, %1, 0; @p red.relaxed.gpu.global.add.u32 [%0], 1;}" :: "l"(c + lane), "r"(lane) : "memory");
}
template <int N = NT> DEVI uint32_t ring_tag(unsigned u, uint32_t ep) { return (u / RING + ep * ((N - 1 - u % RING) / RING + 1) + 1) & 1; }
static_assert(RING >= LAGA && RING > LAG, "ring too short");
DEVI uint32_t lop_bad(uint32_t acc, uint32_t x, uint32_t y, uint32_t tag) {
    uint32_t d; asm("{.reg .b32 t; lop3.b32 t, %2, %3, %4, 0x7e; or.b32 %0, t, %1;}" : "=r"(d) : "r"(acc), "r"(x), "r"(y), "r"(tag)); return d;
}
template <int N> DEVI void validate(uint4* v, const void* p, int step, uint32_t tag) {
    for (int n = 0;; n++) {
        uint32_t bad = 0;
#pragma unroll
        for (int i = 0; i < N; i += 2) bad = lop_bad(bad, v[i].x, v[i + 1 < N ? i + 1 : i].x, tag);
        if (!__any_sync(~0u, bad & 1)) break;
#pragma unroll
        for (int i = 0; i < N; i++) ldg_pkt_retry(v[i], static_cast<const char*>(p) + i * step, tag);
        fault_if(n > POLL_LIMIT, n);
    }
}
DEVI uint32_t page_par(uint32_t off) { return __popc((off >> 12) & 0xb2) & 1; }
DEVI uint32_t inbox_off(int b) { return (b >> 1) * 32768 + (b & 1) * 8192; }
DEVI uint32_t mem_off(int w, int i) { return 0x180000 + w * 1024 + (i & 1) * 512 + (i & 3) * 16384 + (i < 4 ? 0 : i < 8 ? 0x30000 : 0x40000); }
DEVI void sched_fence(uint32_t zero, uint32_t id) { asm volatile("{.reg .pred p; setp.ne.u32 p, %0, %1; @p bra.uni D%=; exit; D%=:}" :: "r"(zero), "r"(id) : "memory"); }
DEVI uint32_t clk() { uint32_t c; asm volatile("mov.u32 %0, %%clock;" : "=r"(c) :: "memory"); return c; }
DEVI void delay(uint32_t n) {
    if (n) asm volatile("{.reg .pred p; .reg .u32 c, e; mov.u32 e, %%clock;\n W%=: mov.u32 c, %%clock; sub.u32 c, c, e; setp.lt.u32 p, c, %0; @p bra.uni W%=;}" :: "r"(n) : "memory");
}
DEVI void delay_until(uint32_t t0, uint32_t n) {
    asm volatile("{.reg .pred p; .reg .u32 c;\n W%=: mov.u32 c, %%clock; sub.u32 c, c, %1; setp.lt.u32 p, c, %0; @p bra.uni W%=;}" :: "r"(n), "r"(t0) : "memory");
}
DEVI void wg_fence() { asm volatile("wgmma.fence.sync.aligned;" ::: "memory"); }
DEVI void wg_commit() { asm volatile("wgmma.commit_group.sync.aligned;" ::: "memory"); }
template <int N> DEVI void wg_wait() { asm volatile("wgmma.wait_group.sync.aligned %0;" :: "n"(N) : "memory"); }
DEVI uint64_t mkdesc(uint32_t lo, uint32_t hi) { uint64_t d; asm("mov.b64 %0, {%1,%2};" : "=l"(d) : "r"(lo), "r"(hi)); return d; }
DEVI void cluster_arrive() { asm volatile("barrier.cluster.arrive.relaxed.aligned;" ::: "memory"); }
DEVI void cluster_wait() { asm volatile("barrier.cluster.wait.aligned;" ::: "memory"); }
DEVI void cluster_sync() { asm volatile("barrier.cluster.arrive.aligned;\n barrier.cluster.wait.aligned;" ::: "memory"); }
DEVI void wgmma_ss16t(float (&d)[8], uint64_t da, uint64_t db, int acc) {
    asm volatile("{.reg .pred p; setp.ne.b32 p, %10, 0;\n"
        "wgmma.mma_async.sync.aligned.m64n16k16.f32.bf16.bf16 {%0,%1,%2,%3,%4,%5,%6,%7}, %8, %9, p, 1, 1, 0, 1;}"
        : "+f"(d[0]), "+f"(d[1]), "+f"(d[2]), "+f"(d[3]), "+f"(d[4]), "+f"(d[5]), "+f"(d[6]), "+f"(d[7])
        : "l"(da), "l"(db), "r"(acc));
}
DEVI void wgmma_ss16a(float (&d)[8], uint64_t da, uint64_t db, int acc) {
    asm volatile("{.reg .pred p; setp.ne.b32 p, %10, 0;\n"
        "wgmma.mma_async.sync.aligned.m64n16k16.f32.bf16.bf16 {%0,%1,%2,%3,%4,%5,%6,%7}, %8, %9, p, 1, 1, 1, 0;}"
        : "+f"(d[0]), "+f"(d[1]), "+f"(d[2]), "+f"(d[3]), "+f"(d[4]), "+f"(d[5]), "+f"(d[6]), "+f"(d[7])
        : "l"(da), "l"(db), "r"(acc));
}
DEVI void wgmma_ss64(float (&d)[32], uint64_t da, uint64_t db, int acc) {
    asm volatile("{.reg .pred p; setp.ne.b32 p, %34, 0;\n"
        "wgmma.mma_async.sync.aligned.m64n64k16.f32.bf16.bf16 {%0,%1,%2,%3,%4,%5,%6,%7,%8,%9,%10,%11,%12,%13,%14,%15,%16,%17,%18,%19,%20,%21,%22,%23,%24,%25,%26,%27,%28,%29,%30,%31}, %32, %33, p, 1, 1, 0, 0;}"
        : "+f"(d[0]), "+f"(d[1]), "+f"(d[2]), "+f"(d[3]), "+f"(d[4]), "+f"(d[5]), "+f"(d[6]), "+f"(d[7]), "+f"(d[8]), "+f"(d[9]), "+f"(d[10]), "+f"(d[11]), "+f"(d[12]), "+f"(d[13]), "+f"(d[14]), "+f"(d[15]), "+f"(d[16]), "+f"(d[17]), "+f"(d[18]), "+f"(d[19]), "+f"(d[20]), "+f"(d[21]), "+f"(d[22]), "+f"(d[23]), "+f"(d[24]), "+f"(d[25]), "+f"(d[26]), "+f"(d[27]), "+f"(d[28]), "+f"(d[29]), "+f"(d[30]), "+f"(d[31])
        : "l"(da), "l"(db), "r"(acc));
}
DEVI void wgmma_rs16t(float (&d)[8], uint32_t a0, uint32_t a1, uint32_t a2, uint32_t a3, uint64_t db, int acc) {
    asm volatile("{.reg .pred p; setp.ne.b32 p, %13, 0;\n"
        "wgmma.mma_async.sync.aligned.m64n16k16.f32.bf16.bf16 {%0,%1,%2,%3,%4,%5,%6,%7}, {%8,%9,%10,%11}, %12, p, 1, 1, 1;}"
        : "+f"(d[0]), "+f"(d[1]), "+f"(d[2]), "+f"(d[3]), "+f"(d[4]), "+f"(d[5]), "+f"(d[6]), "+f"(d[7])
        : "r"(a0), "r"(a1), "r"(a2), "r"(a3), "l"(db), "r"(acc));
}
DEVI void wgmma_rs64(float (&d)[32], uint32_t a0, uint32_t a1, uint32_t a2, uint32_t a3, uint64_t db, int acc) {
    asm volatile("{.reg .pred p; setp.ne.b32 p, %37, 0;\n"
        "wgmma.mma_async.sync.aligned.m64n64k16.f32.bf16.bf16 {%0,%1,%2,%3,%4,%5,%6,%7,%8,%9,%10,%11,%12,%13,%14,%15,%16,%17,%18,%19,%20,%21,%22,%23,%24,%25,%26,%27,%28,%29,%30,%31}, {%32,%33,%34,%35}, %36, p, 1, 1, 0;}"
        : "+f"(d[0]), "+f"(d[1]), "+f"(d[2]), "+f"(d[3]), "+f"(d[4]), "+f"(d[5]), "+f"(d[6]), "+f"(d[7]), "+f"(d[8]), "+f"(d[9]), "+f"(d[10]), "+f"(d[11]), "+f"(d[12]), "+f"(d[13]), "+f"(d[14]), "+f"(d[15]), "+f"(d[16]), "+f"(d[17]), "+f"(d[18]), "+f"(d[19]), "+f"(d[20]), "+f"(d[21]), "+f"(d[22]), "+f"(d[23]), "+f"(d[24]), "+f"(d[25]), "+f"(d[26]), "+f"(d[27]), "+f"(d[28]), "+f"(d[29]), "+f"(d[30]), "+f"(d[31])
        : "r"(a0), "r"(a1), "r"(a2), "r"(a3), "l"(db), "r"(acc));
}
DEVI void wgmma_ss168t(float (&d)[84], uint64_t da, uint64_t db, int acc) {
    asm volatile("{.reg .pred p; setp.ne.b32 p, %86, 0;\n"
        "wgmma.mma_async.sync.aligned.m64n168k16.f32.bf16.bf16 {%0,%1,%2,%3,%4,%5,%6,%7,%8,%9,%10,%11,%12,%13,%14,%15,%16,%17,%18,%19,%20,%21,%22,%23,%24,%25,%26,%27,%28,%29,%30,%31,%32,%33,%34,%35,%36,%37,%38,%39,%40,%41,%42,%43,%44,%45,%46,%47,%48,%49,%50,%51,%52,%53,%54,%55,%56,%57,%58,%59,%60,%61,%62,%63,%64,%65,%66,%67,%68,%69,%70,%71,%72,%73,%74,%75,%76,%77,%78,%79,%80,%81,%82,%83}, %84, %85, p, 1, 1, 0, 1;}"
        : "+f"(d[0]), "+f"(d[1]), "+f"(d[2]), "+f"(d[3]), "+f"(d[4]), "+f"(d[5]), "+f"(d[6]), "+f"(d[7]), "+f"(d[8]), "+f"(d[9]), "+f"(d[10]), "+f"(d[11]), "+f"(d[12]), "+f"(d[13]), "+f"(d[14]), "+f"(d[15]), "+f"(d[16]), "+f"(d[17]), "+f"(d[18]), "+f"(d[19]), "+f"(d[20]), "+f"(d[21]), "+f"(d[22]), "+f"(d[23]), "+f"(d[24]), "+f"(d[25]), "+f"(d[26]), "+f"(d[27]), "+f"(d[28]), "+f"(d[29]), "+f"(d[30]), "+f"(d[31]), "+f"(d[32]), "+f"(d[33]), "+f"(d[34]), "+f"(d[35]), "+f"(d[36]), "+f"(d[37]), "+f"(d[38]), "+f"(d[39]), "+f"(d[40]), "+f"(d[41]), "+f"(d[42]), "+f"(d[43]), "+f"(d[44]), "+f"(d[45]), "+f"(d[46]), "+f"(d[47]), "+f"(d[48]), "+f"(d[49]), "+f"(d[50]), "+f"(d[51]), "+f"(d[52]), "+f"(d[53]), "+f"(d[54]), "+f"(d[55]), "+f"(d[56]), "+f"(d[57]), "+f"(d[58]), "+f"(d[59]), "+f"(d[60]), "+f"(d[61]), "+f"(d[62]), "+f"(d[63]), "+f"(d[64]), "+f"(d[65]), "+f"(d[66]), "+f"(d[67]), "+f"(d[68]), "+f"(d[69]), "+f"(d[70]), "+f"(d[71]), "+f"(d[72]), "+f"(d[73]), "+f"(d[74]), "+f"(d[75]), "+f"(d[76]), "+f"(d[77]), "+f"(d[78]), "+f"(d[79]), "+f"(d[80]), "+f"(d[81]), "+f"(d[82]), "+f"(d[83])
        : "l"(da), "l"(db), "r"(acc));
}
DEVI void wgmma_rs96t(float (&d)[48], uint32_t a0, uint32_t a1, uint32_t a2, uint32_t a3, uint64_t db, int acc) {
    asm volatile("{.reg .pred p; setp.ne.b32 p, %53, 0;\n"
        "wgmma.mma_async.sync.aligned.m64n96k16.f32.bf16.bf16 {%0,%1,%2,%3,%4,%5,%6,%7,%8,%9,%10,%11,%12,%13,%14,%15,%16,%17,%18,%19,%20,%21,%22,%23,%24,%25,%26,%27,%28,%29,%30,%31,%32,%33,%34,%35,%36,%37,%38,%39,%40,%41,%42,%43,%44,%45,%46,%47}, {%48,%49,%50,%51}, %52, p, 1, 1, 1;}"
        : "+f"(d[0]), "+f"(d[1]), "+f"(d[2]), "+f"(d[3]), "+f"(d[4]), "+f"(d[5]), "+f"(d[6]), "+f"(d[7]), "+f"(d[8]), "+f"(d[9]), "+f"(d[10]), "+f"(d[11]), "+f"(d[12]), "+f"(d[13]), "+f"(d[14]), "+f"(d[15]), "+f"(d[16]), "+f"(d[17]), "+f"(d[18]), "+f"(d[19]), "+f"(d[20]), "+f"(d[21]), "+f"(d[22]), "+f"(d[23]), "+f"(d[24]), "+f"(d[25]), "+f"(d[26]), "+f"(d[27]), "+f"(d[28]), "+f"(d[29]), "+f"(d[30]), "+f"(d[31]), "+f"(d[32]), "+f"(d[33]), "+f"(d[34]), "+f"(d[35]), "+f"(d[36]), "+f"(d[37]), "+f"(d[38]), "+f"(d[39]), "+f"(d[40]), "+f"(d[41]), "+f"(d[42]), "+f"(d[43]), "+f"(d[44]), "+f"(d[45]), "+f"(d[46]), "+f"(d[47])
        : "r"(a0), "r"(a1), "r"(a2), "r"(a3), "l"(db), "r"(acc));
}
DEVI void wgmma_rs192t(float (&d)[96], uint32_t a0, uint32_t a1, uint32_t a2, uint32_t a3, uint64_t db, int acc) {
    asm volatile("{.reg .pred p; setp.ne.b32 p, %101, 0;\n"
        "wgmma.mma_async.sync.aligned.m64n192k16.f32.bf16.bf16 {%0,%1,%2,%3,%4,%5,%6,%7,%8,%9,%10,%11,%12,%13,%14,%15,%16,%17,%18,%19,%20,%21,%22,%23,%24,%25,%26,%27,%28,%29,%30,%31,%32,%33,%34,%35,%36,%37,%38,%39,%40,%41,%42,%43,%44,%45,%46,%47,%48,%49,%50,%51,%52,%53,%54,%55,%56,%57,%58,%59,%60,%61,%62,%63,%64,%65,%66,%67,%68,%69,%70,%71,%72,%73,%74,%75,%76,%77,%78,%79,%80,%81,%82,%83,%84,%85,%86,%87,%88,%89,%90,%91,%92,%93,%94,%95}, {%96,%97,%98,%99}, %100, p, 1, 1, 1;}"
        : "+f"(d[0]), "+f"(d[1]), "+f"(d[2]), "+f"(d[3]), "+f"(d[4]), "+f"(d[5]), "+f"(d[6]), "+f"(d[7]), "+f"(d[8]), "+f"(d[9]), "+f"(d[10]), "+f"(d[11]), "+f"(d[12]), "+f"(d[13]), "+f"(d[14]), "+f"(d[15]), "+f"(d[16]), "+f"(d[17]), "+f"(d[18]), "+f"(d[19]), "+f"(d[20]), "+f"(d[21]), "+f"(d[22]), "+f"(d[23]), "+f"(d[24]), "+f"(d[25]), "+f"(d[26]), "+f"(d[27]), "+f"(d[28]), "+f"(d[29]), "+f"(d[30]), "+f"(d[31]), "+f"(d[32]), "+f"(d[33]), "+f"(d[34]), "+f"(d[35]), "+f"(d[36]), "+f"(d[37]), "+f"(d[38]), "+f"(d[39]), "+f"(d[40]), "+f"(d[41]), "+f"(d[42]), "+f"(d[43]), "+f"(d[44]), "+f"(d[45]), "+f"(d[46]), "+f"(d[47]), "+f"(d[48]), "+f"(d[49]), "+f"(d[50]), "+f"(d[51]), "+f"(d[52]), "+f"(d[53]), "+f"(d[54]), "+f"(d[55]), "+f"(d[56]), "+f"(d[57]), "+f"(d[58]), "+f"(d[59]), "+f"(d[60]), "+f"(d[61]), "+f"(d[62]), "+f"(d[63]), "+f"(d[64]), "+f"(d[65]), "+f"(d[66]), "+f"(d[67]), "+f"(d[68]), "+f"(d[69]), "+f"(d[70]), "+f"(d[71]), "+f"(d[72]), "+f"(d[73]), "+f"(d[74]), "+f"(d[75]), "+f"(d[76]), "+f"(d[77]), "+f"(d[78]), "+f"(d[79]), "+f"(d[80]), "+f"(d[81]), "+f"(d[82]), "+f"(d[83]), "+f"(d[84]), "+f"(d[85]), "+f"(d[86]), "+f"(d[87]), "+f"(d[88]), "+f"(d[89]), "+f"(d[90]), "+f"(d[91]), "+f"(d[92]), "+f"(d[93]), "+f"(d[94]), "+f"(d[95])
        : "r"(a0), "r"(a1), "r"(a2), "r"(a3), "l"(db), "r"(acc));
}

#define TRD(t, i)
namespace km {
#define NSS 6
#define RG "184"
#define RW "136"
#define NFL 2
#define NR1 3
#define NR2 3
#define FK 5
#define LDP 3
#define SND 1
#define NGAP 0
constexpr int O_H = 0;
constexpr int O_MB = 73728;
constexpr int O_VX = 96768;
constexpr int O_KX = 113152;
constexpr int O_QX = 119296;
constexpr int O_VM = 125440;
constexpr int O_KM = 129536;
constexpr int O_QM = 131072;
constexpr int O_SM = 132608;
constexpr int O_ST = 135168;
constexpr int O_OX = 145408;
constexpr int O_WO = 149504;
constexpr int O_OS = O_WO;
constexpr int O_WS = O_WO + 49152;
constexpr int O_RL = 110592;
constexpr int O_BAR = O_WS + NSS * 4096;
constexpr int SMEM = O_BAR + 128 + 1024 + TR_BYTES;
enum { B_X = 0, B_XFREE = 8, B_WIN = 16, B_VX = 24, B_SM = 32, B_ST = 40, B_EP = 56 };
#define DLY1 (100 * w)
#define DLY2 300
#define XON 1
#define GON 1
#define DLY0 1000
#define PFON 0
#define PLACE 1
#define XST 0
#define DLYW 12000
#define DLYB 14000
constexpr uint32_t DESC_HI = (1024 >> 4) | (1u << 30);
constexpr float SC = 0.08838834764831845f * 1.4426950408889634f;
}

__global__ void __cluster_dims__(3, 1, 1) __launch_bounds__(384, 1)
k_main(const __nv_bfloat16* __restrict__ x0, const __nv_bfloat16* __restrict__ wqkv, const __nv_bfloat16* __restrict__ wo,
       const __nv_bfloat16* __restrict__ mem0, const __nv_bfloat16* __restrict__ Wq, const __nv_bfloat16* __restrict__ Wk,
       const __nv_bfloat16* __restrict__ Wv, const __nv_bfloat16* __restrict__ Wo) {
    using namespace km;
    extern __shared__ unsigned char smem_raw[];
    const uint32_t sb = (smem_u32(smem_raw) + 1023) & ~1023u;
    const int tid = threadIdx.x, lane = tid & 31, warp = __shfl_sync(~0u, tid >> 5, 0);
    uint32_t l16 = __shfl_sync(~0u, lane * 16, lane);
#define OPQ() asm volatile("" : "+r"(l16))
    const int b = blockIdx.x, h = b / 3, r = b % 3;
    const int nq = r == 2 ? 2 : 3;
    const uint32_t bar = sb + O_BAR;
    asm volatile("griddepcontrol.launch_dependents;");
    const uint32_t t_start = clk();
    if (warp == 0 && b < 72) {
        if (lane == 0) { mbar_init(bar + 96, 1); fence_async_smem(); mbar_expect(bar + 96, 8 * 3456, true); }
        __syncwarp();
        if (lane < 8) asm volatile("cp.async.bulk.shared::cluster.global.mbarrier::complete_tx::bytes [%0], [%1], 3456, [%2];" :: "r"(sb + O_RL + lane * 3472), "l"(wqkv + (b * 8 + lane) * 1728), "r"(bar + 96) : "memory");
    }
    if (tid == 352) {
        prefetch_l2(x0 + b * (2 * DM), 2 * 1152); prefetch_l2(wo + b * (6 * DM), 6 * 1152);
    }
    if (tid == 320) sts32(bar + 64, ldg32(&g_epoch));
#define EP lds32(bar + 64)
    TR_INIT(bar + 128);
    TRG(79, 0);
    uint32_t roff0, roff1;
    {
        uint32_t y0, y1;
        asm("mapa.shared::cluster.u32 %0, %1, %2;" : "=r"(y0) : "r"(sb), "r"((r + 1) % 3));
        asm("mapa.shared::cluster.u32 %0, %1, %2;" : "=r"(y1) : "r"(sb), "r"((r + 2) % 3));
        roff0 = y0 - sb; roff1 = y1 - sb;
    }
#define IDENT (((l16 >> 7) == ((l16 >> 4) & 3) ? 0x3f80u : 0u) << ((l16 >> 2) & 16))
#define LSWAP ((l16 & 0x70) | ((l16 & 0x80) << 1) | ((l16 & 0x100) >> 1))
    const uint32_t nv_remote = 8 - (8 - 2 * nq);

    if (warp < 8) {
        asm volatile("setmaxnreg.inc.sync.aligned.u32 " RG ";");
        constexpr int SSP = 36 / NSS;
#define IS_SS(kk) ((kk) % SSP == 3)
#define AI(kk) (4 * ((kk) - ((kk) + SSP - 4) / SSP))
        uint32_t a[144 - 4 * NSS];
        {
            const int ci = tid & 15, slot = ci >> 1, d0 = tid >> 4;
            const __nv_bfloat16* src = slot < nq ? Wq + (3 * r + slot) * 16 : slot < 2 * nq ? Wk + (3 * r + slot - nq) * 16 : Wv + (2 * r + slot - 2 * nq) * 16;
            src += h * 128 + (ci & 1) * 8 + d0 * 4096;
            auto issue = [&](int q) {
#pragma unroll
                for (int i = 0; i < 3; i++) if (q < 12) cp16(sb + (q * 3 + i) * 4096 + d0 * 256 + ((ci ^ (d0 & 7)) << 4), src + (size_t)(q * 3 + i) * 65536);
                asm volatile("cp.async.commit_group;" ::: "memory");
            };
            if (b < 72) {
                bar_sync(10, 256);
                mbar_wait(bar + 96, 0);
                TR1(4);
#pragma unroll 2
                for (int ag = tid >> 3; ag < 231; ag += 32) {
                    const int a = ag / 21, gr = ag % 21, tl = gr >= 18;
                    const int head = 3 * a + (tl ? 0 : (gr % 6) >> 1), nw = tl ? min(3, 32 - head) : head < 32 ? 4 : 0;
                    const uint32_t p = sb + O_RL + (tid & 7) * 3472 + (tl ? gr - 18 : gr / 6) * 1152 + head * 36 + (tl ? 32 : (gr & 1) * 16), step = tl ? 36 : 4;
                    uint32_t v[4];
#pragma unroll
                    for (int i = 0; i < 4; i++) { v[i] = lds32(p + i * step); if (i >= nw) v[i] = 0; }
                    stg128(g_wa + ((a * 9 + (b >> 3)) * 21 + gr) * 64 + (b & 7) * 8 + (tid & 7), v[0], v[1], v[2], v[3]);
                }
            }
            {
                bar_arrive(15, 288);
                TR1(5);
                delay_until(t_start, DLY0);
#pragma unroll
                for (int q = 0; q < NFL; q++) issue(q);
            }
            TR1(1);
            const int mi = lane >> 3;
            const uint32_t ad = sb + ((mi >> 1) * 8 + (lane & 7)) * 256 + (((warp * 2 + (mi & 1)) ^ (lane & 7)) << 4);
#pragma unroll
            for (int kk = 0; kk < 36; kk++) {
                if (kk % 3 == 0) { cp_wait<NFL - 1>(); issue(kk / 3 + NFL); bar_sync(10, 256); }
                const uint4 f = ldsm4t(ad + kk * 4096);
                if (IS_SS(kk)) {
                    const uint32_t o0 = sb + O_WS + (kk / SSP) * 4096 + warp * 512 + lane * 4;
                    sts32(o0, f.x); sts32(o0 + 256, f.y); sts32(o0 + 128, f.z); sts32(o0 + 384, f.w);
                } else { a[AI(kk)] = f.x; a[AI(kk) + 1] = f.y; a[AI(kk) + 2] = f.z; a[AI(kk) + 3] = f.w; }
            }
            TR1(2);
            bar_sync(9, 384);
#pragma unroll
            for (int i = 0; i < 9; i++) sts128(sb + O_H + i * 8192 + 4096 + tid * 16, 0, 0, 0, 0);
#pragma unroll
            for (int i = 0; i < 8; i++) if (i * 256 + tid < (O_OX - O_KX) / 16) sts128(sb + O_KX + i * 4096 + tid * 16, 0, 0, 0, 0);
            fence_async_smem();
            cluster_sync();
        }
        TR1(3);
        const int kind = warp < nq ? 0 : warp < 2 * nq ? 1 : 2;
        const int sl = kind == 0 ? warp : kind == 1 ? warp - nq : 2 * r + warp - 2 * nq;
        const uint32_t adX0 = sb + (kind == 0 ? O_QX : kind == 1 ? O_KX : O_VX) + sl * 2048;
        const uint32_t adM0 = sb + (kind == 0 ? O_QM : kind == 1 ? O_KM : O_VM) + sl * 512;
        const uint32_t hlo = (((sb + O_H) >> 4) & 0x3fff) | (1u << 16);
        const uint32_t mlo = (((sb + O_MB) >> 4) & 0x3fff) | (16u << 16);
        const uint32_t wlo = (((sb + O_WS + (warp >> 2) * 2048) >> 4) & 0x3fff) | (8u << 16);
        const int L = (warp >> 1) & 1, qh = warp & 1;
        const uint32_t st = sb + O_ST + warp * 1280;

#pragma unroll 1
        for (int t = -1;; t++) {
            TR_ON(t);
            OPQ();
            const uint32_t adX = adX0 + l16, adM = adM0 + l16, l8 = l16 >> 1;
            const uint32_t lq = LSWAP;
            if (t >= 0) {
                float d0[8], d1[8];
                {
#pragma unroll
                    for (int G = 0; G < 3; G++) {
                        if (warp < 4) bar_sync(1 + G, 160); else bar_sync(12 + G, 160);
                        if (G == 0) wg_fence();
#pragma unroll
                        for (int q = 0; q < 12; q++) {
                            const int kk = 12 * G + q;
                            const uint64_t db = mkdesc(mlo + kk * 32, 8);
                            if (IS_SS(kk)) wgmma_ss16t((kk & 1) ? d1 : d0, mkdesc(wlo + (kk / SSP) * 256, 16), db, 1);
                            else wgmma_rs16t((kk & 1) ? d1 : d0, a[AI(kk)], a[AI(kk) + 1], a[AI(kk) + 2], a[AI(kk) + 3], db, kk >= 2);
                            if (kk == 0) TR(0);
                        }
                    }
                    wg_commit();
                }
#define PM(i) pk(d0[2 * (i)] + d1[2 * (i)], d0[2 * (i) + 1] + d1[2 * (i) + 1])
                if (warp >= 4) {
                    wg_wait<0>();
                    TR(1);
                    const uint32_t p0 = PM(0), p1 = PM(1), p2 = PM(2), p3 = PM(3);
                    if (kind == 2) {
                        sts128(adM, p0, p1, p2, p3);
                        bar_arrive(4, 384);
                        sta128(adM + roff0, p0, p1, p2, p3, bar + B_SM + roff0);
                        sta128(adM + roff1, p0, p1, p2, p3, bar + B_SM + roff1);
                    } else {
                        stsm4t(adM, p0, p1, p2, p3);
                        bar_arrive(4, 384);
                    }
                } else {
                    uint4 q[3], k[3][2];
                    mbar_wait(bar + B_EP, t & 1);
#pragma unroll
                    for (int m = 0; m < LDP; m++) {
                        q[m] = ldsm4(sb + O_QX + m * 2048 + warp * 512 + lq);
                        k[m][0] = ldsm4(sb + O_KX + m * 2048 + L * 1024 + l16); k[m][1] = ldsm4(sb + O_KX + m * 2048 + L * 1024 + 512 + l16);
                    }
                    wg_wait<0>();
                    TR(1);
                    stsm4t(adM, PM(0), PM(1), PM(2), PM(3));
                    bar_arrive(4, 384);
                    sched_fence(gridDim.y, 6);
#pragma unroll
                    for (int m = LDP; m < 3; m++) {
                        q[m] = ldsm4(sb + O_QX + m * 2048 + warp * 512 + lq);
                        k[m][0] = ldsm4(sb + O_KX + m * 2048 + L * 1024 + l16); k[m][1] = ldsm4(sb + O_KX + m * 2048 + L * 1024 + 512 + l16);
                    }
                    float s[5][4];
                    {
                        float y[4] = {0, 0, 0, 0};
#pragma unroll
                        for (int n = 0; n < 5; n++) s[n][0] = s[n][1] = s[n][2] = s[n][3] = 0.f;
#pragma unroll
                        for (int m = 0; m < 3; m++) {
                            mma16(s[0], q[m].x, q[m].y, q[m].z, q[m].w, k[m][0].x, k[m][0].y); mma16(s[1], q[m].x, q[m].y, q[m].z, q[m].w, k[m][0].z, k[m][0].w);
                            mma16(s[2], q[m].x, q[m].y, q[m].z, q[m].w, k[m][1].x, k[m][1].y); mma16(s[3], q[m].x, q[m].y, q[m].z, q[m].w, k[m][1].z, k[m][1].w);
                        }
                        auto send = [&]() {
                            uint32_t w0 = pk(s[0][0], s[0][1]), w1 = pk(s[0][2], s[0][3]), w2 = pk(s[1][0], s[1][1]), w3 = pk(s[1][2], s[1][3]);
                            sta128(st + l16 + 5120 + roff0, w0, w1, w2, w3, bar + B_ST + roff0);
                            sta128(st + l16 + roff1, w0, w1, w2, w3, bar + B_ST + roff1);
                            w0 = pk(s[2][0], s[2][1]); w1 = pk(s[2][2], s[2][3]); w2 = pk(s[3][0], s[3][1]); w3 = pk(s[3][2], s[3][3]);
                            sta128p(st + l16 + 5120 + 512 + roff0, w0, w1, w2, w3, bar + B_ST + roff0, qh);
                            sta128p(st + l16 + 512 + roff1, w0, w1, w2, w3, bar + B_ST + roff1, qh);
                        };
                        bar_sync(5, 256);
                        const uint4 k01 = ldsm4(sb + O_KM + L * 256 + l16 + (l16 & 256));
                        const uint2 k2 = ldsm2(sb + O_KM + 1024 + L * 256 + l16);
                        if (SND == 0) send();
                        mma16(s[4], q[0].x, q[0].y, q[0].z, q[0].w, k01.x, k01.y);
                        mma16(y, q[1].x, q[1].y, q[1].z, q[1].w, k01.z, k01.w);
                        mma16(s[4], q[2].x, q[2].y, q[2].z, q[2].w, k2.x, k2.y);
#pragma unroll
                        for (int j = 0; j < 4; j++) s[4][j] += y[j];
                        const uint32_t w0 = pk(s[4][0], s[4][1]), w1 = pk(s[4][2], s[4][3]);
                        if (NGAP > 0) bar_arrive(11, 256);
                        sta64(st + l8 + 5120 + 1024 + roff0, w0, w1, bar + B_ST + roff0);
                        sta64(st + l8 + 1024 + roff1, w0, w1, bar + B_ST + roff1);
                        if (SND == 1) send();
                        TR(2);
                        const int lim = 16 * qh + (int)(l16 >> 6) - (int)((l16 >> 3) & 6);
#pragma unroll
                        for (int n = 0; n < 4; n++)
#pragma unroll
                            for (int j = 0; j < 4; j++) if (!(n == 0 && j >= 2) && 8 * (n - (j >> 1)) + (j & 1) > lim) s[n][j] = -1e30f;
#pragma unroll
                        for (int n = 0; n < 4; n++) asm volatile("" : "+f"(s[n][0]), "+f"(s[n][1]), "+f"(s[n][2]), "+f"(s[n][3]));
                    }
                    uint4 v0[3], v1[3]; uint2 vm[3];
                    const uint32_t vad = sb + O_VX + 3 * r * 2048 + L * 1024 + l16;
#pragma unroll
                    for (int m = 0; m < 3; m++) v0[m] = lds128(vad + m * 2048);
                    const uint32_t otag = ring_tag(t, EP);
                    uint32_t ident = IDENT;
                    asm volatile("" : "+r"(ident));
                    mbar_wait(bar + B_SM, t & 1);
                    mbar_wait(bar + B_ST, t & 1);
                    TR(3);
                    float mx0, mx1;
                    {
                        const uint4 u = lds128(st + l16), v = lds128(st + 512 + l16); const uint2 w = lds64(st + 1024 + l8);
                        const uint4 x = lds128(st + 5120 + l16), y = lds128(st + 5120 + 512 + l16); const uint2 z = lds64(st + 5120 + 1024 + l8);
                        mma8(s[0], u.x, u.y, ident); mma8(s[1], u.z, u.w, ident); mma8(s[2], v.x, v.y, ident); mma8(s[3], v.z, v.w, ident); mma8(s[4], w.x, w.y, ident);
                        mma8(s[0], x.x, x.y, ident); mma8(s[1], x.z, x.w, ident); mma8(s[2], y.x, y.y, ident); mma8(s[3], y.z, y.w, ident); mma8(s[4], z.x, z.y, ident);
                        mx0 = fmaxf(fmaxf(fmaxf(s[0][0], s[0][1]), fmaxf(s[1][0], s[1][1])), fmaxf(fmaxf(s[2][0], s[2][1]), fmaxf(s[3][0], s[3][1])));
                        mx1 = fmaxf(fmaxf(fmaxf(s[0][2], s[0][3]), fmaxf(s[1][2], s[1][3])), fmaxf(fmaxf(s[2][2], s[2][3]), fmaxf(s[3][2], s[3][3])));
                        mx0 = fmaxf(mx0, fmaxf(s[4][0], s[4][1])); mx1 = fmaxf(mx1, fmaxf(s[4][2], s[4][3]));
                    }
#pragma unroll
                    for (int o = 1; o < 4; o <<= 1) { const float2 z = shfl2(mx0, mx1, o); mx0 = fmaxf(mx0, z.x); mx1 = fmaxf(mx1, z.y); }
                    mx0 *= -SC; mx1 *= -SC;
                    float l[4] = {0, 0, 0, 0};
                    uint32_t p[10];
#pragma unroll
                    for (int n = 0; n < 5; n++) {
                        const float e0 = ex2(fmaf(s[n][0], SC, mx0)), e1 = ex2(fmaf(s[n][1], SC, mx0));
                        const float e2 = ex2(fmaf(s[n][2], SC, mx1)), e3 = ex2(fmaf(s[n][3], SC, mx1));
                        p[2 * n] = pk(e0, e1); p[2 * n + 1] = pk(e2, e3);
                        mma8(l, p[2 * n], p[2 * n + 1], 0x3f803f80);
                    }
#pragma unroll
                    for (int m = 0; m < 3; m++) vm[m] = lds64(sb + O_VM + (3 * r + m) * 512 + l16 + L * 8);
                    sched_fence(gridDim.y, 5);
                    const float l0 = rcp(l[0]), l1 = rcp(l[2]);
                    float o[6][4];
#pragma unroll
                    for (int m = 0; m < 6; m++) o[m][0] = o[m][1] = o[m][2] = o[m][3] = 0.f;
#pragma unroll
                    for (int m = 0; m < 3; m++) { mma8(o[2 * m], p[0], p[1], v0[m].x); mma8(o[2 * m + 1], p[0], p[1], v0[m].y); }
#pragma unroll
                    for (int m = 0; m < 3; m++) { mma8(o[2 * m], p[2], p[3], v0[m].z); mma8(o[2 * m + 1], p[2], p[3], v0[m].w); v1[m] = lds128(vad + m * 2048 + 512); }
#pragma unroll
                    for (int m = 0; m < 3; m++) { mma8(o[2 * m], p[8], p[9], vm[m].x); mma8(o[2 * m + 1], p[8], p[9], vm[m].y); }
#pragma unroll
                    for (int m = 0; m < 3; m++) { mma8(o[2 * m], p[4], p[5], v1[m].x); mma8(o[2 * m + 1], p[4], p[5], v1[m].y); }
#pragma unroll
                    for (int m = 0; m < 3; m++) { mma8(o[2 * m], p[6], p[7], v1[m].z); mma8(o[2 * m + 1], p[6], p[7], v1[m].w); }
#pragma unroll
                    for (int m = 0; m < 3; m++)
                        sts128(sb + O_OS + warp * 512 + m * 2048 + l16, (pk(o[2 * m][0] * l0, o[2 * m][1] * l0) & ~1u) | otag, pk(o[2 * m][2] * l1, o[2 * m][3] * l1),
                               pk(o[2 * m + 1][0] * l0, o[2 * m + 1][1] * l0), pk(o[2 * m + 1][2] * l1, o[2 * m + 1][3] * l1));
                    TR(4);
                }
            }
            if (t + 1 >= NT) break;
            {
                float d[32];
                if (warp >= 4) mbar_wait(bar + B_X, (t + 1) & 1);
                if (NGAP == 0 || warp < 4) bar_sync(7, 384); else if (t >= 0) bar_sync(11, 256);
                wg_fence();
                TR(6);
#pragma unroll
                for (int kk = 0; kk < 36; kk++) {
                    if (NGAP > 0 && kk == NGAP) asm volatile("{.reg .pred p; setp.ge.u32 p, %0, 4; @p bar.sync 7, 384;}" :: "r"(warp) : "memory");
                    const uint64_t db = mkdesc(hlo + ((kk >> 2) * 8192 + (kk & 3) * 32) / 16, DESC_HI);
                    if (IS_SS(kk)) wgmma_ss64(d, mkdesc(wlo + (kk / SSP) * 256, 16), db, 1);
                    else wgmma_rs64(d, a[AI(kk)], a[AI(kk) + 1], a[AI(kk) + 2], a[AI(kk) + 3], db, kk > 0);
                }
                wg_commit();
                TR(5);
                mbar_wait(bar + B_WIN, (t + 1) & 1);
                wg_wait<0>();
                TR(7);
                mbar_arrive_all3(bar + B_XFREE, l16 >> 4);
                uint32_t p[16];
#pragma unroll
                for (int u = 0; u < 16; u++) p[u] = pk(d[2 * u], d[2 * u + 1]);
                if (kind == 2) {
#pragma unroll
                    for (int u = 0; u < 4; u++) sts128(adX + u * 512, p[4 * u], p[4 * u + 1], p[4 * u + 2], p[4 * u + 3]);
                } else {
#pragma unroll
                    for (int u = 0; u < 4; u++) stsm4t(adX + u * 512, p[4 * u], p[4 * u + 1], p[4 * u + 2], p[4 * u + 3]);
                }
                __syncwarp();
                asm volatile("{.reg .pred p; setp.eq.u32 p, %1, 0; @p mbarrier.arrive.shared.b64 _, [%0];}" :: "r"(bar + B_EP), "r"(l16) : "memory");
                TR(8);
            }
        }
        if (warp < 4) bar_arrive(7, 160); else if (NGAP > 0) bar_sync(11, 256);
        cluster_sync();
    } else {
        asm volatile("setmaxnreg.dec.sync.aligned.u32 " RW ";");
        const int w = warp - 8, t2 = tid - 256;
        if (t2 == 0) {
            mbar_init(bar + B_X, 1); mbar_init(bar + B_XFREE, 24); mbar_init(bar + B_WIN, 3);
            mbar_init(bar + B_VX, 1); mbar_init(bar + B_SM, 1); mbar_init(bar + B_ST, 1); mbar_init(bar + B_EP, 8);
            asm volatile("fence.mbarrier_init.release.cluster;" ::: "memory");
        }
        char* const ex = reinterpret_cast<char*>((reinterpret_cast<uintptr_t>(g_ex) + 0x1fffff) & ~(uintptr_t)0x1fffff);
        char* rbase = ex; uint32_t side = 0;
        {
            uint32_t m0[5][4];
#pragma unroll
            for (int i = 0; i < 5; i++) {
                const unsigned short* m = reinterpret_cast<const unsigned short*>(mem0) + min(i * 128 + t2, DM - 1);
#pragma unroll
                for (int j = 0; j < 4; j++) m0[i][j] = m[2 * j * DM] | (m[(2 * j + 1) * DM] << 16);
            }
            if (w == 3) { bar_sync(15, 288); cnt_add(g_cnt + C_W * 8, lane); TR1(1); }
            if (t2 >= 96 && t2 < 99 && PFON) prefetch_l2((t2 == 96 ? Wq : t2 == 97 ? Wk : Wv) + b * (6 * 4096), 6 * 8192);
            delay_until(t_start, DLYW);
#pragma unroll 4
            for (int i = t2; i < 128 * 24; i += 128) {
                const int e = (i >> 3) & 127, G = i >> 10, q = i & 7;
                cp16(sb + O_WO + G * 16384 + e * 128 + ((q ^ (e & 7) ^ ((h >> 1) & 1)) << 4), Wo + (size_t)(h * 128 + e) * DM + G * 192 + r * 64 + q * 8);
            }
            bar_sync(9, 384);
#pragma unroll
            for (int i = 0; i < 5; i++) {
                const int k = min(i * 128 + t2, DM - 1);
                const uint32_t ad = sb + O_MB + (k >> 3) * 256 + (k & 7) * 16;
                sts128(ad, m0[i][0], m0[i][1], m0[i][2], m0[i][3]); sts128(ad + 128, m0[i][0], m0[i][1], m0[i][2], m0[i][3]);
            }
            fence_async_smem();
        }
        auto arm = [&]() {
            const uint32_t ln = l16 >> 4;
            mbar_expect(bar + B_VX + (ln & 3) * 8, ln == 0 ? nv_remote * 2048 : ln == 1 ? nv_remote * 512 + 2560 : 8192, ln < 3);
        };
        if (w == 3) arm();
        cluster_sync();
        TR1(3);
        const int L = w >> 1, hf = w & 1;
        const uint32_t rd = hf ? roff1 : roff0;
        const uint32_t rzero = gridDim.y + 100;
#define WOAD (sb + O_WO + ((l16 & 0x100) << 2) + ((l16 & 0x70) << 3) + (((w * 32) | ((l16 >> 3) & 16)) ^ (l16 & 0x70)))

        auto fetch_tile = [&](int u) {
            const bool a0 = u < NSEG, a1 = u >= LAG;
            mbar_expect(bar + B_X, ((int)a0 + (int)a1) * 36864, l16 == 0);
            const uint32_t off = r * 24576 + (l16 << 9) + (a0 ? 0 : 4096);
            asm volatile("{.reg .pred p; setp.lt.u32 p, %5, %6;\n"
                "@p cp.async.bulk.shared::cluster.global.mbarrier::complete_tx::bytes.multicast::cluster [%0], [%1], %4, [%2], %3;}"
                :: "r"(sb + O_H + off), "l"(reinterpret_cast<const char*>(g_xt + u * 4608) + off), "r"(bar + B_X), "h"((uint16_t)7),
                   "r"(a0 && a1 ? 24576 : 4096), "r"(l16), "r"(a0 && a1 ? 16 : 48) : "memory");
        };
        auto store_o = [&](int u) {
            asm volatile("{.reg .pred p; setp.eq.u32 p, %3, 0;\n"
                "@p cp.async.bulk.global.shared::cta.bulk_group [%0], [%1], %2;\n cp.async.bulk.commit_group;}"
                :: "l"(g_o + ((u & (RING - 1)) * 256 + h * 8 + 3 * r) * 128), "r"(sb + O_OS), "r"(nq * 2048), "r"(l16) : "memory");
            cnt_hint(g_cnt + (C_O + u * 8 + (h >> 2)) * 8, l16);
            TRG(u, 2);
        };
        bar_arrive(7, 384);
        if (w < 3) {
            bar_arrive(1 + w, 160); bar_arrive(12 + w, 160); if (w == 0) bar_arrive(8, 64);
            if (w < 2) {
                unsigned* pp = reinterpret_cast<unsigned*>(ex + inbox_off(b) + 16384 + w * 4096 + 2048);
                uint32_t best = ~0u, v = 0;
                if (lane == 0) {
#pragma unroll 1
                    for (int i = 0; i < 6; i++) {
                        const uint32_t c0 = clk();
                        v = atomicAdd(pp + (v >> 31), 0);
                        asm volatile("" :: "r"(v) : "memory");
                        sts32(bar + 80, v);
                        best = min(best, clk() - c0);
                    }
                    sts32(bar + 72 + w * 4, best);
                }
            }
            bar_sync(15, 96);
            const uint32_t xs = PLACE ? lds32(bar + 76) < lds32(bar + 72) : 0, ep = EP;
            side = PLACE ? xs ^ page_par(inbox_off(b)) : 0;
            rbase = ex + inbox_off(b) + xs * 4096;
            const uint32_t inv = (ep * (NT - 1)) & 1;
#pragma unroll
            for (int i = 0; i < 4; i++) stg128(rbase + (w == 2 ? 16384 : w * 2048) + i * 512 + lane * 16, inv, 0, 0, 0);
            __threadfence();
            bar_sync(15, 96);
            if (t2 == 0) stg_word(g_side + b, (ep + 1) * 2 + xs, true);
            TR1(4);
        } else {
            mbar_arrive_all3(bar + B_WIN, l16 >> 4);
            cnt_wait(g_cnt + C_X * 8, 64 * (EP + 1)); fence_async_global();
            TRG(0, 0);
            fetch_tile(0);
            TRG(0, 1);
        }
        cp_wait_all();
        bar_sync(6, 128);
        uint32_t poff;
        {
            const int rb = r * 32 + w * 8 + (lane >> 2);
            const uint32_t want = EP + 1;
            uint32_t v;
            for (int n = 0; __any_sync(~0u, ((v = ldg_word(g_side + rb)) >> 1) != want); n++) fault_if(n > POLL_LIMIT, n);
            __threadfence();
            poff = inbox_off(rb) + (v & 1) * 4096 + h * 64 + (lane & 3) * 16;
        }
        side = __shfl_sync(~0u, side, 0);
        const uint32_t roff = __shfl_sync(~0u, (uint32_t)(rbase - ex), 0) + (w == 2 ? 16384 : (w & 1) * 2048);
        bool late = true;
        uint4 a0[8];
#pragma unroll
        for (int kk = 0; kk < 8; kk++) a0[kk] = ldsm4t(WOAD + kk * 2048);
#pragma unroll 1
        for (int t = 0;; t++) {
            TR_ON(t);
            OPQ();
            mbar_wait(bar + B_EP, t & 1);
            if (w == 3) {
                fence_async_smem();
                const uint32_t ad = sb + O_VX + r * 4096;
                asm volatile("{.reg .pred p; setp.eq.u32 p, %5, 0;\n"
                    "@p cp.async.bulk.shared::cluster.shared::cta.mbarrier::complete_tx::bytes [%0], [%2], %6, [%3];\n"
                    "@p cp.async.bulk.shared::cluster.shared::cta.mbarrier::complete_tx::bytes [%1], [%2], %6, [%4];}"
                    :: "r"(ad + roff0), "r"(ad + roff1), "r"(ad), "r"(bar + B_VX + roff0), "r"(bar + B_VX + roff1), "r"(l16), "r"(16384 - 4096 * nq) : "memory");
            }
            uint4 kx[3][2], vx[4][2];
            const uint32_t lp = LSWAP;
#pragma unroll
            for (int m = 0; m < 3; m++) {
                kx[m][0] = ldsm4(sb + O_KX + m * 2048 + L * 1024 + lp);
                kx[m][1] = ldsm4(sb + O_KX + m * 2048 + L * 1024 + 512 + lp);
            }
            if (w == 3) {
                mbar_wait(bar + B_XFREE, t & 1);
                bar_sync(8, 64);
                TR(6);
                if (t > 0) store_o(t - 1);
                if (late) { cnt_wait(g_cnt + (C_X + t + 1) * 8, 64 * (EP + 1)); fence_async_global(); }
                TRG(t + 1, 0);
                if (t + 1 < NT) { fetch_tile(t + 1); TRG(t + 1, 1); }
                asm volatile("cp.async.bulk.wait_group.read 0;" ::: "memory");
                TR(7);
            }
            mbar_wait(bar + B_VX, t & 1);
            TR(0);
            bar_sync(4, 384);
            float s0[4] = {0, 0, 0, 0}, s1[4] = {0, 0, 0, 0}, sm[4] = {0, 0, 0, 0};
            {
                const uint4 q01 = ldsm4(sb + O_QM + L * 256 + l16 + (l16 & 256));
                const uint2 q2 = ldsm2(sb + O_QM + 1024 + L * 256 + l16);
                uint4 km_[3];
#pragma unroll
                for (int m = 0; m < 3; m++) km_[m] = ldsm4(sb + O_KM + m * 512 + (lp ^ (L << 8)));
                bar_arrive(5, 256);
                mma16(s0, kx[0][0].x, kx[0][0].y, kx[0][0].z, kx[0][0].w, q01.x, q01.y);
                mma16(s1, kx[0][1].x, kx[0][1].y, kx[0][1].z, kx[0][1].w, q01.x, q01.y);
                mma16(sm, km_[0].x, km_[0].y, km_[0].z, km_[0].w, q01.x, q01.y);
                mma16(s0, kx[1][0].x, kx[1][0].y, kx[1][0].z, kx[1][0].w, q01.z, q01.w);
                mma16(s1, kx[1][1].x, kx[1][1].y, kx[1][1].z, kx[1][1].w, q01.z, q01.w);
                mma16(sm, km_[1].x, km_[1].y, km_[1].z, km_[1].w, q01.z, q01.w);
                mma16(s0, kx[2][0].x, kx[2][0].y, kx[2][0].z, kx[2][0].w, q2.x, q2.y);
                mma16(s1, kx[2][1].x, kx[2][1].y, kx[2][1].z, kx[2][1].w, q2.x, q2.y);
                mma16(sm, km_[2].x, km_[2].y, km_[2].z, km_[2].w, q2.x, q2.y);
                const uint32_t ad = sb + O_SM + (1 - hf) * 1280 + L * 640 + rd;
                sta128(ad + l16, pk(s0[0], s0[1]), pk(s0[2], s0[3]), pk(s1[0], s1[1]), pk(s1[2], s1[3]), bar + B_SM + rd);
                sta32(ad + 512 + (l16 >> 2), pk(sm[0], sm[1]), bar + B_SM + rd);
            }
            TR(1);
            if (t + 1 == NT) break;
#pragma unroll
            for (int m = 0; m < 8; m++) vx[m >> 1][m & 1] = lds128(sb + O_VX + (hf * 4 + (m >> 1)) * 2048 + L * 1024 + (m & 1) * 512 + l16);
            const uint32_t tag = (t + EP * (NT - 1) + 1) & 1;
            uint32_t ident = IDENT;
            asm volatile("" : "+r"(ident));
            mbar_wait(bar + B_SM, t & 1);
            TR(2);
            {
                const uint32_t ad = sb + O_SM + L * 640;
                const uint4 u = lds128(ad + l16), v = lds128(ad + 1280 + l16);
                const uint32_t x = lds32(ad + 512 + (l16 >> 2)), y = lds32(ad + 1280 + 512 + (l16 >> 2));
                mma8(s0, u.x, u.y, ident); mma8(s1, u.z, u.w, ident); mma8(s0, v.x, v.y, ident); mma8(s1, v.z, v.w, ident);
                sm[0] += bf_lo(x) + bf_lo(y); sm[1] += bf_hi(x) + bf_hi(y);
            }
            uint2 vm[4];
#pragma unroll
            for (int m = 0; m < 4; m++) vm[m] = lds64(sb + O_VM + (hf * 4 + m) * 512 + l16 + L * 8);
            float mx0 = fmaxf(fmaxf(fmaxf(s0[0], s0[2]), fmaxf(s1[0], s1[2])), sm[0]);
            float mx1 = fmaxf(fmaxf(fmaxf(s0[1], s0[3]), fmaxf(s1[1], s1[3])), sm[1]);
#pragma unroll
            for (int o = 4; o < 32; o <<= 1) { mx0 = fmaxf(mx0, __shfl_xor_sync(~0u, mx0, o)); mx1 = fmaxf(mx1, __shfl_xor_sync(~0u, mx1, o)); }
            mx0 *= -SC; mx1 *= -SC;
            s0[0] = ex2(fmaf(s0[0], SC, mx0)); s0[1] = ex2(fmaf(s0[1], SC, mx1));
            s0[2] = ex2(fmaf(s0[2], SC, mx0)); s0[3] = ex2(fmaf(s0[3], SC, mx1));
            const uint32_t pb0 = movm(pk(s0[0], s0[1])), pb1 = movm(pk(s0[2], s0[3]));
            s1[0] = ex2(fmaf(s1[0], SC, mx0)); s1[1] = ex2(fmaf(s1[1], SC, mx1));
            s1[2] = ex2(fmaf(s1[2], SC, mx0)); s1[3] = ex2(fmaf(s1[3], SC, mx1));
            const uint32_t pb2 = movm(pk(s1[0], s1[1])), pb3 = movm(pk(s1[2], s1[3]));
            sm[0] = ex2(fmaf(sm[0], SC, mx0)); sm[1] = ex2(fmaf(sm[1], SC, mx1));
            const uint32_t pm = movm(pk(sm[0], sm[1]));
            float o[4][4], l[4] = {0, 0, 0, 0};
            const uint32_t one = 0x3f803f80;
            mma8(l, one, one, pb0); mma8(l, one, one, pb1);
#pragma unroll
            for (int m = 0; m < 4; m++) { o[m][0] = o[m][1] = o[m][2] = o[m][3] = 0.f; mma16(o[m], vx[m][0].x, vx[m][0].y, vx[m][0].z, vx[m][0].w, pb0, pb1); }
            mma8(l, one, one, pb2); mma8(l, one, one, pb3);
#pragma unroll
            for (int m = 0; m < 4; m++) mma16(o[m], vx[m][1].x, vx[m][1].y, vx[m][1].z, vx[m][1].w, pb2, pb3);
            mma8(l, one, one, pm);
#pragma unroll
            for (int m = 0; m < 4; m++) mma8(o[m], vm[m].x, vm[m].y, pm);
            const float l0 = rcp(l[0]), l1 = rcp(l[1]);
#pragma unroll
            for (int m = 0; m < 4; m += 2)
                stsm4t(sb + O_OX + (hf * 4 + m) * 512 + (L ^ ((h >> 2) & 1)) * 256   + ((l16 & 0x100) << 1) + (l16 & 0xf0),
                       pk(o[m][0] * l0, o[m][1] * l1), pk(o[m][2] * l0, o[m][3] * l1), pk(o[m + 1][0] * l0, o[m + 1][1] * l1), pk(o[m + 1][2] * l0, o[m + 1][3] * l1));
            TR(3);
            char* const pdst = ex + poff;
            bar_sync(6, 128);
            {
                uint4 bo[8], a1[8], z;
                const uint32_t wad = WOAD;
#pragma unroll
                for (int kk = 0; kk < 8; kk++) bo[kk] = ldsm4(sb + O_OX + kk * 512 + l16);
#pragma unroll
                for (int G = 0; G < 3; G++) {
                    float e[4][4];
#pragma unroll
                    for (int q = 0; q < 4; q++) e[q][0] = e[q][1] = e[q][2] = e[q][3] = 0.f;
#pragma unroll
                    for (int kk = 0; kk < 8; kk++) {
                        const uint4 f = G == 0 ? a0[kk] : a1[kk];
                        mma16(e[(kk & 1) * 2], f.x, f.y, f.z, f.w, bo[kk].x, bo[kk].y);
                        mma16(e[(kk & 1) * 2 + 1], f.x, f.y, f.z, f.w, bo[kk].z, bo[kk].w);
                        if (G == 1) a1[kk] = ldsm4t(wad + 32768 + kk * 2048);
                        if (G == 0 && kk == FK) {
                            sched_fence(rzero, 2);
#pragma unroll
                            for (int j = 0; j < 8; j++) a1[j] = ldsm4t(wad + 16384 + j * 2048);
                        }
                    }
                    if (G > 0) asm volatile("{.reg .pred p; setp.eq.u32 p, %5, 0; @p st.shared.v4.u32 [%0], {%1,%2,%3,%4};}" :: "r"(__float_as_uint(e[0][0])), "r"(z.x), "r"(z.y), "r"(z.z), "r"(z.w), "r"(rzero));
                    z = make_uint4((pk(e[0][0] + e[2][0], e[0][1] + e[2][1]) & ~1u) | tag, pk(e[0][2] + e[2][2], e[0][3] + e[2][3]),
                                   pk(e[1][0] + e[3][0], e[1][1] + e[3][1]), pk(e[1][2] + e[3][2], e[1][3] + e[3][3]));
                    stg_pkt(pdst + (G == 2 ? 16384 : G * 2048), z.x, z.y, z.z, z.w);
                    if (G == 0) { TR(9); TRD(t, 0); }
                    if (G < 2) sched_fence(rzero, 3 + G);
                }
            }
            TR(4);
            if (w < 3) {
                bar_arrive(7, 384);
                OPQ();
                const uint32_t tagm = tag;
                uint32_t m0v = 0;
                if (t + 1 <= LAG) {
                    const unsigned short* m = reinterpret_cast<const unsigned short*>(mem0) + ((l16 >> 3) & 6) * DM + 192 * w + 16 * (b >> 3) + (b & 7) + ((l16 >> 4) & 8);
                    m0v = m[0] | (m[DM] << 16);
                }
                const char* const rsrc = ex + roff + l16;
                uint4 v[4];
                delay(DLY1);
#pragma unroll
                for (int i = 0; i < 4; i++) v[i] = ldg_pkt(rsrc + i * 512);
                for (int n = 0; __any_sync(~0u, lop_bad(lop_bad(0, v[0].x, v[1].x, tagm), v[2].x, v[3].x, tagm) & 1); n++) {
#pragma unroll
                    for (int i = 0; i < 4; i++) v[i] = ldg_pkt(rsrc + i * 512);
                    fault_if(n > POLL_LIMIT, n);
                }
                TR(5); TRD(t, 1);
                float s[8];
                s[4] = (bf_lo(v[0].z) + bf_lo(v[1].z)) + (bf_lo(v[2].z) + bf_lo(v[3].z)); s[5] = (bf_hi(v[0].z) + bf_hi(v[1].z)) + (bf_hi(v[2].z) + bf_hi(v[3].z));
                s[6] = (bf_lo(v[0].w) + bf_lo(v[1].w)) + (bf_lo(v[2].w) + bf_lo(v[3].w)); s[7] = (bf_hi(v[0].w) + bf_hi(v[1].w)) + (bf_hi(v[2].w) + bf_hi(v[3].w));
                s[2] = (bf_lo(v[0].y) + bf_lo(v[1].y)) + (bf_lo(v[2].y) + bf_lo(v[3].y)); s[3] = (bf_hi(v[0].y) + bf_hi(v[1].y)) + (bf_hi(v[2].y) + bf_hi(v[3].y));
                s[0] = (bf_lo(v[0].x) + bf_lo(v[1].x)) + (bf_lo(v[2].x) + bf_lo(v[3].x)); s[1] = (bf_hi(v[0].x) + bf_hi(v[1].x)) + (bf_hi(v[2].x) + bf_hi(v[3].x));
#pragma unroll
                for (int j = 0; j < 4; j++) s[j] += __shfl_xor_sync(~0u, s[j + 4], 16);
#pragma unroll
                for (int j = 0; j < 2; j++) s[j] += __shfl_xor_sync(~0u, s[j + 2], 8);
#pragma unroll
                for (int j = 0; j < 2; j++) s[j] += __shfl_xor_sync(~0u, s[j], 4);
                char* const mem_w = ex + mem_off(w, 0);
                uint32_t res = t + 1 <= LAG && l16 >= 256 ? m0v : pk(s[0], s[1]);
                if ((l16 & 48) == 0) res = (res & ~1u) | tag;
                stg_word(mem_w + (mem_off(0, b >> 3) - mem_off(0, 0)) + (b & 7) * 16 + (((l16 & 64) << 6) + ((l16 & 128) << 1) + ((l16 & 256) >> 1) + ((l16 >> 2) & 12)), res, true);
                TR(6); TRD(t, 2);
                delay(DLY2);
                const char* src = mem_w + (side ^ page_par(0x180000)) * 4096 + l16;
                const uint32_t gdst = sb + O_MB + w * 6144 + l16;
                uint4 x[12];
#pragma unroll
                for (int i = 0; i < 12; i++) x[i] = ldg_pkt(src + (mem_off(0, i) - mem_off(0, 0)));
                for (int n = 0;; n++) {
                    uint32_t bad = 0;
#pragma unroll
                    for (int i = 0; i < 12; i += 2) bad = lop_bad(bad, x[i].x, x[i + 1].x, tagm);
                    if (!__any_sync(~0u, bad & 1)) break;
#pragma unroll
                    for (int i = 0; i < 12; i++) ldg_pkt_retry(x[i], src + (mem_off(0, i) - mem_off(0, 0)), tagm);
                    fault_if(n > POLL_LIMIT, n);
                }
#pragma unroll
                for (int i = 0; i < 12; i++) sts128(gdst + i * 512, x[i].x, x[i].y, x[i].z, x[i].w);
                TR(7); TRD(t, 3);
                fence_async_smem();
                bar_arrive(12 + w, 160);
                bar_arrive(1 + w, 160);
                if (w == XST) bar_arrive(8, 64);
                TR(8);
            } else {
                bar_sync(7, 384);
                fence_async_smem();
                arm();
                __syncwarp();
                mbar_arrive_all3(bar + B_WIN, l16 >> 4);
                late = t + 2 < NT && cnt_poll(g_cnt + (C_X + t + 2) * 8, 64 * (EP + 1), bar + B_EP, (t + 1) & 1);
                fence_async_global();
                TR(5);
            }
        }
        if (w == 3) { bar_sync(7, 160); fence_async_smem(); store_o(NT - 1); asm volatile("cp.async.bulk.wait_group 0;" ::: "memory"); }
        cluster_sync();
    }
    TR_DUMP(b);
}

#define VG 12
#define HB 3
#define HA 2
#define HW 0
namespace ka {
constexpr int O_WA = 196608;
constexpr int A_KB = 21504;
constexpr int O_RING = 194560;
constexpr int O_BAR = 230400;
constexpr int SMEM = O_BAR + 256 + 1024;
constexpr float SC = 0.23570226039551584f * 1.4426950408889634f;
}

template <int NP, int KB = 4096>
DEVI void row_task(const uint4* res, const uint4* part, uint4* xout, char* img, int pos, int lane, uint32_t tag) {
    const bool on = lane < 24;
    const int ln = on ? lane : 0;
    uint4 rv[3], pv[NP > 0 ? NP * 3 : 1];
#pragma unroll
    for (int i = 0; i < 3; i++) rv[i] = ldg128(res + i * 24 + ln);
#pragma unroll
    for (int i = 0; i < NP * 3; i++) pv[i] = ldg_pkt(part + i * 24 + ln);
    if (NP > 0) validate<NP * 3>(pv, part + ln, 384, tag);
#pragma unroll
    for (int q = 0; q < NP * 3 / 2; q++) {
        const uint4 y = pv[q + NP * 3 / 2];
        pv[q] = make_uint4(add2(pv[q].x, y.x), add2(pv[q].y, y.y), add2(pv[q].z, y.z), add2(pv[q].w, y.w));
    }
    float x[24];
#pragma unroll
    for (int i = 0; i < 3; i++) {
        x[8 * i] = bf_lo(rv[i].x); x[8 * i + 1] = bf_hi(rv[i].x); x[8 * i + 2] = bf_lo(rv[i].y); x[8 * i + 3] = bf_hi(rv[i].y);
        x[8 * i + 4] = bf_lo(rv[i].z); x[8 * i + 5] = bf_hi(rv[i].z); x[8 * i + 6] = bf_lo(rv[i].w); x[8 * i + 7] = bf_hi(rv[i].w);
    }
    if (NP > 0) {
#pragma unroll
        for (int q = 0; q < NP * 3 / 2; q++) {
            const int i = q % 3;
            x[8 * i] += bf_lo(pv[q].x); x[8 * i + 1] += bf_hi(pv[q].x); x[8 * i + 2] += bf_lo(pv[q].y); x[8 * i + 3] += bf_hi(pv[q].y);
            x[8 * i + 4] += bf_lo(pv[q].z); x[8 * i + 5] += bf_hi(pv[q].z); x[8 * i + 6] += bf_lo(pv[q].w); x[8 * i + 7] += bf_hi(pv[q].w);
        }
#pragma unroll
        for (int i = 0; i < 3; i++) {
            uint32_t w[4];
#pragma unroll
            for (int j = 0; j < 4; j++) { w[j] = pk(x[8 * i + 2 * j], x[8 * i + 2 * j + 1]); x[8 * i + 2 * j] = bf_lo(w[j]); x[8 * i + 2 * j + 1] = bf_hi(w[j]); }
            stg128p(xout + i * 24 + ln, w[0], w[1], w[2], w[3], on);
        }
    }
    if (img) {
        float s = 0.f;
#pragma unroll
        for (int j = 0; j < 24; j++) s += x[j];
        if (!on) s = 0.f;
#pragma unroll
        for (int o = 1; o < 32; o <<= 1) s += __shfl_xor_sync(~0u, s, o);
        const float mean = s * (1.f / DM);
        float v = 0.f;
#pragma unroll
        for (int j = 0; j < 24; j++) { x[j] -= mean; v = fmaf(x[j], x[j], v); }
        if (!on) v = 0.f;
#pragma unroll
        for (int o = 1; o < 32; o <<= 1) v += __shfl_xor_sync(~0u, v, o);
        const float rs = rsqrtf(v * (1.f / DM) + 1e-5f);
        char* dst = img + (ln >> 3) * KB + pos * 128 + (((ln ^ pos) & 7) << 4);
#pragma unroll
        for (int i = 0; i < 3; i++)
            stg128p(dst + i * (3 * KB), pk(x[8 * i] * rs, x[8 * i + 1] * rs), pk(x[8 * i + 2] * rs, x[8 * i + 3] * rs),
                    pk(x[8 * i + 4] * rs, x[8 * i + 5] * rs), pk(x[8 * i + 6] * rs, x[8 * i + 7] * rs), on);
    }
}

DEVI void rows_a(const uint4* xin, int f, int i, int lane, uint32_t ep, int warp) {
    for (int u = 0; u < LAG; u++) cnt_hint(g_cnt + (C_X + u + (f ? 0 : NSEG)) * 8, lane);
#pragma unroll 1
    for (int seg = 0; seg < NSEG; seg++) {
        const int j = seg + f * LAGA, u = seg + f * LAG, row = seg * 32 + i;
        hint_wait(g_cnt + (C_WA + j * 4 + f * 2 + (i & 1)) * 8, 24 * (ep + 1));
        TRG(u, 0);
        row_task<4, 8192>((f ? g_x + 2048 * 72 : xin) + row * 72, g_pa + ((j & (RING - 1)) * 64 + f * 32 + i) * 288,
                    g_x + (f * 4096 + row) * 72, reinterpret_cast<char*>(g_xt + u * 4608 + f * 256), i, lane, ring_tag<NTA>(j, ep));
        TRG(u, 1);
        cnt_add(g_cnt + (C_X + u) * 8, lane);
        TRG(u, 2);
    }
}

__global__ void __launch_bounds__(384, 1)
k_aux(const __nv_bfloat16* __restrict__ x0, const __nv_bfloat16* __restrict__ wqkv, const __nv_bfloat16* __restrict__ wo,
      const __nv_bfloat16* __restrict__ Wo, __nv_bfloat16* __restrict__ out) {
    using namespace ka;
    extern __shared__ unsigned char smem_raw[];
    const uint32_t sb = (smem_u32(smem_raw) + 1023) & ~1023u;
    const int tid = threadIdx.x, lane = tid & 31, warp = __shfl_sync(~0u, tid >> 5, 0), g = lane >> 2, c = lane & 3;
    const int b = blockIdx.x;
    const uint32_t bar = sb + O_BAR;
    const uint32_t ep = __shfl_sync(~0u, ldg32(&g_epoch), 0);

    TRG(79, 0);
    const uint4* xin = reinterpret_cast<const uint4*>(x0);
    if (warp >= 8 || b == 35) {
        asm volatile("setmaxnreg.dec.sync.aligned.u32 128;");
        const int rw = b < 24 ? (warp - 8) * 24 + b : b < 35 ? (warp - 8) * 11 + b - 24 : 96 + 2 * warp;
        if (b < 24 || b == 35) {
#pragma unroll 1
            for (int row = rw; row < 2048; row += (row & 1) ? 23 : 1) {
                if (lane == 0 && b == 35 && row < 2024) prefetch_l2(xin + (row + 24) * 72, 1152);
                row_task<0>(xin + row * 72, nullptr, nullptr, reinterpret_cast<char*>(g_xa + (row >> 5) * 4608), (row & 1) * 16 + ((row & 31) >> 1), lane, 0);
                if (b < 24) { cnt_add(g_cnt + (C_N0 + (row >> 5)) * 8, lane); break; }
                if (row & 1) cnt_add<2>(g_cnt + (C_N0 + (row >> 5)) * 8, lane);
            }
        }
        if (rw < 32) {
            const int f = b < 24, i = rw;
#pragma unroll 1
            for (int seg = 0; seg < NSEG; seg++) {
                const int u = seg + f * LAG, row = seg * 32 + i;
                hint_wait(g_cnt + (C_WB + u * 4 + f * 2 + (i >> 4)) * 8, 24 * (ep + 1));
                TRG(u, 0);
                row_task<8>(g_x + (f * 4096 + row) * 72, g_pb + ((u & (RING - 1)) * 64 + f * 32 + i) * 576,
                            f ? reinterpret_cast<uint4*>(out) + row * 72 : g_x + (2048 + row) * 72,
                            f ? nullptr : reinterpret_cast<char*>(g_xa + (seg + LAGA) * 4608 + 2304), (i & 1) * 16 + (i >> 1), lane, ring_tag(u, ep));
                TRG(u, 1);
                cnt_add(g_cnt + (C_RB + f * NSEG + seg) * 8, lane);
                TRG(u, 2);
            }
            if (f && rw == 31) {
                asm volatile("griddepcontrol.wait;" ::: "memory");
                if (lane == 0) g_epoch = ep + 1;
            }
        } else if (rw < 64 && b < 24) rows_a(xin, 0, rw - 32, lane, ep, warp);
        return;
    }

    if (b < 24) {
        if (warp >= 4) {
            const int kq = b / 6, nq = b % 6;
            uint4 v[17];
#pragma unroll
            for (int q = 0; q < 17; q++) {
                const int it = q * 4 + warp - 4, kr = (it / 3) * 8 + g, s = kq * 11 + (kr >> 4), a = s >> 2, j = s & 3, e = kr & 15;
                const int head = 3 * a + (j < 3 ? j : e >> 1), row = head * 18 + (j < 3 ? e : 16 + (e & 1));
                v[q] = make_uint4(0, 0, 0, 0);
                if (it < 66 && head < 32 && (j < 3 || e < 6)) v[q] = *reinterpret_cast<const uint4*>(wo + row * DM + nq * 96 + (it % 3) * 32 + c * 8);
            }
#pragma unroll
            for (int q = 0; q < 17; q++) {
                const int it = q * 4 + warp - 4;
                const uint32_t ad = sb + O_WA + (it % 3) * 4 * 2816 + (it / 3) * 128 + lane * 4;
                if (it < 66) { sts32(ad, v[q].x); sts32(ad + 2816, v[q].y); sts32(ad + 2 * 2816, v[q].z); sts32(ad + 3 * 2816, v[q].w); }
            }
        } else {
            const int kg = b / 3, ng = b % 3;
            delay(DLYB);
#pragma unroll 1
            for (int bt = 0; bt < 4; bt++) {
                uint4 v[24];
#pragma unroll
                for (int q = 0; q < 24; q++)
                    v[q] = *reinterpret_cast<const uint4*>(Wo + (size_t)(kg * 512 + (bt * 4 + q / 6) * 32 + warp * 8 + g) * DM + ng * 192 + (q % 6) * 32 + c * 8);
#pragma unroll
                for (int q = 0; q < 24; q++) {
                    const uint32_t ad = sb + (q % 6) * 4 * 8192 + ((bt * 4 + q / 6) * 4 + warp) * 128 + lane * 4;
                    sts32(ad, v[q].x); sts32(ad + 8192, v[q].y); sts32(ad + 2 * 8192, v[q].z); sts32(ad + 3 * 8192, v[q].w);
                }
            }
        }
        fence_async_smem();
        bar_sync(2 + (warp >> 2), 128);
    } else {
        for (int i = tid; i < 2048; i += 256) sts128(sb + O_RING + i * 16, 0, 0, 0, 0);
        if (tid < 17) mbar_init(bar + tid * 8, tid >= 4 && tid < 8 ? 4 : 1);
        fence_async_smem();
        bar_sync(1, 256);
    }
    TRG(79, 1);
    const int wq = warp & 3;

    if (warp < 4) {
        asm volatile("setmaxnreg.inc.sync.aligned.u32 256;");
        if (b < 24) {
            const int kg = b / 3, ng = b % 3;
            const uint32_t blo = ((sb >> 4) & 0x3fff) | (8u << 16);
            uint4 a[32];
            bool pre = false;
#pragma unroll 1
            for (int u = 0; u < NT; u++) {
                const uint32_t tag = ring_tag(u, ep);
                const uint4* src = g_o + (((u & (RING - 1)) * 256 + kg * 32) * 4 + wq) * 32 + lane;
                if (!pre) {
                    hint_wait(g_cnt + (C_O + u * 8 + kg) * 8, 12 * (ep + 1));
#pragma unroll
                    for (int i = 0; i < VG; i++) a[i] = ldg_pkt(src + i * 128);
                }
                TRG(u, 0);
                float d[96];
                validate<VG>(a, src, 2048, tag);
#pragma unroll
                for (int i = VG; i < 32; i++) a[i] = ldg_pkt(src + i * 128);
                wg_fence();
#pragma unroll
                for (int i = 0; i < 32; i++) {
                    if (i == VG) { validate<32 - VG>(a + VG, src + VG * 128, 2048, tag); wg_fence(); }
                    wgmma_rs192t(d, a[i].x, a[i].y, a[i].z, a[i].w, mkdesc(blo + i * 16, 512), i > 0);
                    if (i == 23 || i == 31) wg_commit();
                }
                wg_wait<1>();
                pre = u + 1 < NT && __all_sync(~0u, ldg_word(g_cnt + (C_O + (u + 1) * 8 + kg) * 8) >= 12 * (ep + 1));
                if (pre) {
                    const uint4* nx = g_o + ((((u + 1) & (RING - 1)) * 256 + kg * 32) * 4 + wq) * 32 + lane;
#pragma unroll
                    for (int i = 0; i < VG; i++) a[i] = ldg_pkt(nx + i * 128);
                }
                wg_wait<0>();
                TRG(u, 1);
                uint4* dst = g_pb + (((u & (RING - 1)) * 64 + wq * 16 + g) * 8 + kg) * 72 + ng * 24 + c;
#pragma unroll
                for (int m = 0; m < 6; m++) {
                    if (m == HB) cnt_hint(g_cnt + (C_WB + u * 4 + wq) * 8, lane);
                    stg128(dst + 4 * m, (pk(d[16 * m], d[16 * m + 1]) & ~1u) | tag, pk(d[16 * m + 4], d[16 * m + 5]), pk(d[16 * m + 8], d[16 * m + 9]), pk(d[16 * m + 12], d[16 * m + 13]));
                    stg128(dst + 4 * m + 8 * 576, (pk(d[16 * m + 2], d[16 * m + 3]) & ~1u) | tag, pk(d[16 * m + 6], d[16 * m + 7]), pk(d[16 * m + 10], d[16 * m + 11]), pk(d[16 * m + 14], d[16 * m + 15]));
                }
                TRG(u, 3);
            }
        } else {
            const int a = b - 24, f = wq >> 1;
            const uint32_t blo = ((sb >> 4) & 0x3fff) | (8u << 16), alo = (((sb + O_RING) >> 4) & 0x3fff) | (1u << 16);
            const bool m0 = 2 * c <= g, m1 = 2 * c + 1 <= g;
            const uint32_t M = (m0 ? 0xffffu : 0u) | (m1 ? 0xffff0000u : 0u);
            uint32_t kh[7], vh[7];
#pragma unroll
            for (int i = 0; i < 7; i++) kh[i] = vh[i] = 0;
            int it = 0;
#pragma unroll 1
            for (int u = 0; u < NTA; u++) {
                float d[84];
#pragma unroll 1
                for (int kb = 0; kb < 9; kb++, it++) {
                    mbar_wait(bar + (it & 3) * 8, (it >> 2) & 1);
                    if (u == 0) mbar_wait(bar + 64 + kb * 8, 0);
                    if (kb == 0) TRG(u, 0);
                    wg_fence();
#pragma unroll
                    for (int q = 0; q < 4; q++)
                        wgmma_ss168t(d, mkdesc(alo + (it & 3) * 512 + q * 2, km::DESC_HI), mkdesc(blo + kb * (A_KB >> 4) + q * 16, 64), kb + q > 0);
                    wg_commit();
                    wg_wait<1>();
                    mbar_arrive(bar + 32 + ((it - 1) & 3) * 8, lane == 0 && kb > 0);
                }
                wg_wait<0>();
                mbar_arrive(bar + 32 + ((it - 1) & 3) * 8, lane == 0);
                TRG(u, 1);
                const bool first = u == f * LAGA;
                const uint32_t tag = ring_tag<NTA>(u, ep);
                const uint32_t qt0 = pk(d[72], d[73]), qt1 = pk(d[74], d[75]), kt0 = pk(d[76], d[77]), kt1 = pk(d[78], d[79]);
                const uint32_t vt0 = movm(pk(d[80], d[81])), vt1 = movm(pk(d[82], d[83]));
                float ot[4] = {0, 0, 0, 0};
                uint4* dst = g_oa + (((u & (RING - 1)) * 4 + wq) * 44 + a * 4) * 32 + lane;
#pragma unroll
                for (int h = 0; h < 3; h++) {
                    const float* q = d + 8 * h; const float* k = d + 24 + 8 * h; const float* v = d + 48 + 8 * h;
                    const uint32_t q0 = pk(q[0], q[1]), q1 = pk(q[2], q[3]), q2 = pk(q[4], q[5]), q3 = pk(q[6], q[7]);
                    const uint32_t k0 = pk(k[0], k[1]), k1 = pk(k[4], k[5]), k2 = pk(k[2], k[3]), k3 = pk(k[6], k[7]);
                    const uint32_t v0 = movm(pk(v[0], v[1])), v1 = movm(pk(v[2], v[3])), v2 = movm(pk(v[4], v[5])), v3 = movm(pk(v[6], v[7]));
                    const uint32_t t0 = c == h ? qt0 : 0, t1 = c == h ? qt1 : 0;
                    float sp[4] = {0, 0, 0, 0}, sl[4] = {0, 0, 0, 0}, sh[4] = {0, 0, 0, 0};
                    mma16(sp, q0, q1, q2, q3, kh[2 * h], kh[2 * h + 1]); mma16(sl, q0, q1, q2, q3, k0, k1); mma16(sh, q0, q1, q2, q3, k2, k3);
                    mma8(sp, t0, t1, kh[6]); mma8(sl, t0, t1, kt0); mma8(sh, t0, t1, kt1);
                    float x0_ = m0 ? sl[0] : first ? -INFINITY : sp[0], x1_ = m1 ? sl[1] : first ? -INFINITY : sp[1];
                    float y0_ = m0 ? sh[2] : sl[2], y1_ = m1 ? sh[3] : sl[3];
                    float mx = fmaxf(x0_, x1_), my = fmaxf(y0_, y1_);
#pragma unroll
                    for (int o = 1; o < 4; o <<= 1) { mx = fmaxf(mx, __shfl_xor_sync(~0u, mx, o)); my = fmaxf(my, __shfl_xor_sync(~0u, my, o)); }
                    mx *= -SC; my *= -SC;
                    x0_ = ex2(fmaf(x0_, SC, mx)); x1_ = ex2(fmaf(x1_, SC, mx)); y0_ = ex2(fmaf(y0_, SC, my)); y1_ = ex2(fmaf(y1_, SC, my));
                    float lx = x0_ + x1_, ly = y0_ + y1_;
#pragma unroll
                    for (int o = 1; o < 4; o <<= 1) { lx += __shfl_xor_sync(~0u, lx, o); ly += __shfl_xor_sync(~0u, ly, o); }
                    lx = rcp(lx); ly = rcp(ly);
                    const uint32_t px = pk(x0_ * lx, x1_ * lx), py = pk(y0_ * ly, y1_ * ly);
                    const uint32_t hm = (g >> 1) == h ? ~0u : 0u;
                    float o0[4] = {0, 0, 0, 0}, o1[4] = {0, 0, 0, 0};
                    mma16(o0, px & M, py & ~M, 0, py & M, v0, v1); mma16(o1, px & M, py & ~M, 0, py & M, v2, v3);
                    mma16(ot, px & M, py & ~M, 0, py & M, vt0 & hm, vt1 & hm);
                    mma8(o0, px & ~M, 0, vh[2 * h]); mma8(o1, px & ~M, 0, vh[2 * h + 1]); mma8(ot, px & ~M, 0, vh[6] & hm);
                    if (h == HA) cnt_hint(g_cnt + (C_A + u * 4 + wq) * 8, lane);
                    stg128(dst + h * 32, (pk(o0[0], o0[1]) & ~1u) | tag, pk(o0[2], o0[3]), pk(o1[0], o1[1]), pk(o1[2], o1[3]));
                    kh[2 * h] = k2; kh[2 * h + 1] = k3; vh[2 * h] = v1; vh[2 * h + 1] = v3;
                }
                kh[6] = kt1; vh[6] = vt1;
                stg128(dst + 96, (pk(ot[0], ot[1]) & ~1u) | tag, pk(ot[2], ot[3]), 0, 0);
                TRG(u, 2);
            }
        }
    } else {
        asm volatile("setmaxnreg.dec.sync.aligned.u32 120;");
        if (b < 24) {
            const int kq = b / 6, nq = b % 6;
            const uint32_t blo = (((sb + O_WA) >> 4) & 0x3fff) | (8u << 16);
#pragma unroll 1
            for (int u = 0; u < NTA; u++) {
                hint_wait(g_cnt + (C_A + u * 4 + wq) * 8, 11 * (ep + 1));
                const uint32_t tag = ring_tag<NTA>(u, ep);
                TRG(u, 0);
                const uint4* src = g_oa + (((u & (RING - 1)) * 4 + wq) * 44 + kq * 11) * 32 + lane;
                uint4 a[11];
                float d[48];
#pragma unroll
                for (int i = 0; i < 11; i++) a[i] = ldg_pkt(src + i * 32);
                validate<11>(a, src, 512, tag);
                wg_fence();
#pragma unroll
                for (int i = 0; i < 11; i++) wgmma_rs96t(d, a[i].x, a[i].y, a[i].z, a[i].w, mkdesc(blo + i * 16, 176), i > 0);
                wg_commit();
                wg_wait<0>();
                TRG(u, 1);
                uint4* dst = g_pa + (((u & (RING - 1)) * 64 + (wq >> 1) * 32 + 2 * g + (wq & 1)) * 4 + kq) * 72 + nq * 12 + c;
#pragma unroll
                for (int m = 0; m < 3; m++) {
                    if (m == HW) cnt_hint(g_cnt + (C_WA + u * 4 + wq) * 8, lane);
                    stg128(dst + 4 * m, (pk(d[16 * m], d[16 * m + 1]) & ~1u) | tag, pk(d[16 * m + 4], d[16 * m + 5]), pk(d[16 * m + 8], d[16 * m + 9]), pk(d[16 * m + 12], d[16 * m + 13]));
                    stg128(dst + 4 * m + 16 * 288, (pk(d[16 * m + 2], d[16 * m + 3]) & ~1u) | tag, pk(d[16 * m + 6], d[16 * m + 7]), pk(d[16 * m + 10], d[16 * m + 11]), pk(d[16 * m + 14], d[16 * m + 15]));
                }
                TRG(u, 3);
            }
        } else if (warp == 4) {
            mbar_expect(bar + 64 + lane * 8, A_KB, lane < 9);
            int it = 0;
#pragma unroll 1
            for (int u = 0; u < NTA; u++) {
                if (u == 0) { cnt_wait(g_cnt + C_W * 8, 96 * (ep + 1)); TRG(78, 0); }
                if (u < NSEG) cnt_wait(g_cnt + (C_N0 + u) * 8, 32 * (ep + 1));
                if (u > LAGA + LAG) cnt_wait(g_cnt + (C_RB + NSEG + u - LAGA - LAG - 1) * 8, 32 * (ep + 1));
                if (u >= LAGA) cnt_wait(g_cnt + (C_RB + u - LAGA) * 8, 32 * (ep + 1));
                TRG(u, 0);
                asm volatile("fence.proxy.async.global;" ::: "memory");
                const bool on = lane == 0 ? u < NSEG : lane == 1 && u >= LAGA;
#pragma unroll 1
                for (int kb = 0; kb < 9; kb++, it++) {
                    if (it >= 4) mbar_wait(bar + 32 + (it & 3) * 8, ((it >> 2) - 1) & 1);
                    mbar_expect(bar + (it & 3) * 8, u < NSEG && u >= LAGA ? 8192 : 4096, lane == 0);
                    asm volatile("{.reg .pred p; setp.ne.u32 p, %3, 0; @p cp.async.bulk.shared::cluster.global.mbarrier::complete_tx::bytes [%0], [%1], 4096, [%2];}"
                        :: "r"(sb + O_RING + (it & 3) * 8192 + (lane & 1) * 4096), "l"(g_xa + u * 4608 + (lane & 1) * 2304 + kb * 256), "r"(bar + (it & 3) * 8), "r"((uint32_t)on) : "memory");
                    if (u == 0) asm volatile("{.reg .pred p; setp.ne.u32 p, %4, 0; @p cp.async.bulk.shared::cluster.global.mbarrier::complete_tx::bytes [%0], [%1], %3, [%2];}"
                        :: "r"(sb + lane * A_KB), "l"(g_wa + ((b - 24) * 9 + lane) * (A_KB / 16)), "r"(bar + 64 + lane * 8), "n"(A_KB),
                           "r"((uint32_t)(lane < 9 && kb == (lane < 4 ? lane : lane < 6 ? 3 : lane - 2))) : "memory");
                }
            }
        } else if ((warp - 5) * 11 + b - 24 < 32) rows_a(xin, 1, (warp - 5) * 11 + b - 24, lane, ep, warp);
    }
}

extern "C" void kernel_launch(void* const* d_in, const int* in_sizes, int n_in, void* d_out, int out_size) {
    const __nv_bfloat16* x = (const __nv_bfloat16*)d_in[0];
    const __nv_bfloat16* wqkv = (const __nv_bfloat16*)d_in[1];
    const __nv_bfloat16* wo = (const __nv_bfloat16*)d_in[2];
    const __nv_bfloat16* mem0 = (const __nv_bfloat16*)d_in[4];
    const __nv_bfloat16* Wq = (const __nv_bfloat16*)d_in[5];
    const __nv_bfloat16* Wk = (const __nv_bfloat16*)d_in[6];
    const __nv_bfloat16* Wv = (const __nv_bfloat16*)d_in[7];
    const __nv_bfloat16* Wo = (const __nv_bfloat16*)d_in[8];
    cudaFuncSetAttribute(k_main, cudaFuncAttributeMaxDynamicSharedMemorySize, km::SMEM);
    cudaFuncSetAttribute(k_aux, cudaFuncAttributeMaxDynamicSharedMemorySize, ka::SMEM);
    cudaStream_t s = cudaStreamPerThread;
    k_main<<<96, 384, km::SMEM, s>>>(x, wqkv, wo, mem0, Wq, Wk, Wv, Wo);
    cudaLaunchConfig_t cfg = {};
    cudaLaunchAttribute at[1];
    at[0].id = cudaLaunchAttributeProgrammaticStreamSerialization;
    at[0].val.programmaticStreamSerializationAllowed = 1;
    cfg.stream = s; cfg.attrs = at; cfg.numAttrs = 1;
    cfg.gridDim = dim3(36); cfg.blockDim = dim3(384); cfg.dynamicSmemBytes = ka::SMEM;
    cudaLaunchKernelEx(&cfg, k_aux, x, wqkv, wo, Wo, (__nv_bfloat16*)d_out);
}
```

```cpp
#include <cuda_runtime.h>
#include <cuda_bf16.h>
#include <stdint.h>

#define LAG 7
constexpr int NSEG = 64;
constexpr int NT = NSEG + LAG;
#define AHEAD 1
constexpr int LAGA = LAG + AHEAD;
constexpr int NTA = NSEG + LAGA;
#define RING_ 8
constexpr int RING = RING_;
constexpr int DM = 576;

__device__ __align__(1024) uint4 g_xt[NT * 2 * 9 * 256];
__device__ __align__(1024) uint4 g_o[RING * 4 * 256 * 32];
__device__ __align__(1024) uint4 g_ex[2 * 131072];
__device__ unsigned g_side[96];
__device__ __align__(1024) uint4 g_pb[RING * 64 * 8 * 72];
__device__ __align__(1024) uint4 g_pa[RING * 64 * 4 * 72];
__device__ __align__(1024) uint4 g_oa[RING * 4 * 44 * 32];
__device__ __align__(1024) uint4 g_xa[NTA * 2 * 9 * 256];
__device__ __align__(1024) uint4 g_wa[11 * 9 * 21 * 64];
__device__ __align__(1024) uint4 g_x[3 * 2048 * 72];

constexpr int C_X = 0;
constexpr int C_O = C_X + NT;
constexpr int C_WB = C_O + NT * 8;
constexpr int C_RB = C_WB + NT * 4;
constexpr int C_A = C_RB + 2 * NSEG;
constexpr int C_WA = C_A + NTA * 4;
constexpr int C_N0 = C_WA + NTA * 4;
constexpr int C_W = C_N0 + NSEG;
constexpr int C_DONE = C_W + 1;
constexpr int C_TOTAL = C_DONE + 1;
__device__ __align__(1024) unsigned g_cnt[C_TOTAL * 8];
__device__ unsigned g_epoch;

#define TR(i)
#define TR1(i)
#define TR_ON(t)
#define TR_INIT(base)
#define TR_DUMP(slot)
#define TRG(t, i)
constexpr int TR_BYTES = 0;

#define DEVI __device__ __forceinline__
DEVI uint32_t smem_u32(const void* p) { return (uint32_t)__cvta_generic_to_shared(p); }
DEVI uint32_t pk(float lo, float hi) { uint32_t r; asm("cvt.rn.bf16x2.f32 %0, %1, %2;" : "=r"(r) : "f"(hi), "f"(lo)); return r; }
DEVI float bf_lo(uint32_t u) { return __uint_as_float(u << 16); }
DEVI float bf_hi(uint32_t u) { return __uint_as_float(u & 0xffff0000u); }
DEVI uint32_t add2(uint32_t a, uint32_t b) { uint32_t d; asm("add.rn.bf16x2 %0, %1, %2;" : "=r"(d) : "r"(a), "r"(b)); return d; }
DEVI uint32_t movm(uint32_t a) { uint32_t d; asm volatile("movmatrix.sync.aligned.m8n8.trans.b16 %0, %1;" : "=r"(d) : "r"(a)); return d; }
DEVI float2 shfl2(float a, float b, int o) {
    float2 r; asm volatile("shfl.sync.bfly.b32 %0, %2, %4, 31, -1; shfl.sync.bfly.b32 %1, %3, %4, 31, -1;" : "=&f"(r.x), "=f"(r.y) : "f"(a), "f"(b), "r"(o)); return r;
}
DEVI float ex2(float x) { float y; asm("ex2.approx.ftz.f32 %0, %1;" : "=f"(y) : "f"(x)); return y; }
DEVI float rcp(float x) { float y; asm("rcp.approx.ftz.f32 %0, %1;" : "=f"(y) : "f"(x)); return y; }
DEVI void mma16(float (&d)[4], uint32_t a0, uint32_t a1, uint32_t a2, uint32_t a3, uint32_t b0, uint32_t b1) {
    asm volatile("mma.sync.aligned.m16n8k16.row.col.f32.bf16.bf16.f32 {%0,%1,%2,%3}, {%4,%5,%6,%7}, {%8,%9}, {%0,%1,%2,%3};"
        : "+f"(d[0]), "+f"(d[1]), "+f"(d[2]), "+f"(d[3]) : "r"(a0), "r"(a1), "r"(a2), "r"(a3), "r"(b0), "r"(b1));
}
DEVI void mma8(float (&d)[4], uint32_t a0, uint32_t a1, uint32_t b0) {
    asm volatile("mma.sync.aligned.m16n8k8.row.col.f32.bf16.bf16.f32 {%0,%1,%2,%3}, {%4,%5}, {%6}, {%0,%1,%2,%3};"
        : "+f"(d[0]), "+f"(d[1]), "+f"(d[2]), "+f"(d[3]) : "r"(a0), "r"(a1), "r"(b0));
}
DEVI uint4 lds128(uint32_t a) { uint4 v; asm volatile("ld.shared.v4.u32 {%0,%1,%2,%3}, [%4];" : "=r"(v.x), "=r"(v.y), "=r"(v.z), "=r"(v.w) : "r"(a) : "memory"); return v; }
DEVI uint2 lds64(uint32_t a) { uint2 v; asm volatile("ld.shared.v2.u32 {%0,%1}, [%2];" : "=r"(v.x), "=r"(v.y) : "r"(a) : "memory"); return v; }
DEVI uint32_t lds32(uint32_t a) { uint32_t v; asm volatile("ld.shared.u32 %0, [%1];" : "=r"(v) : "r"(a) : "memory"); return v; }
DEVI uint32_t lds32v(uint32_t a) { uint32_t v; asm volatile("ld.volatile.shared.u32 %0, [%1];" : "=r"(v) : "r"(a) : "memory"); return v; }
DEVI uint4 lds128v(uint32_t a) { uint4 v; asm volatile("ld.volatile.shared.v4.u32 {%0,%1,%2,%3}, [%4];" : "=r"(v.x), "=r"(v.y), "=r"(v.z), "=r"(v.w) : "r"(a) : "memory"); return v; }
DEVI uint32_t lds16(uint32_t a) { uint32_t v; asm volatile("ld.shared.u16 %0, [%1];" : "=r"(v) : "r"(a) : "memory"); return v; }
DEVI uint4 ldsm4(uint32_t a) { uint4 v; asm volatile("ldmatrix.sync.aligned.m8n8.x4.shared.b16 {%0,%1,%2,%3}, [%4];" : "=r"(v.x), "=r"(v.y), "=r"(v.z), "=r"(v.w) : "r"(a) : "memory"); return v; }
DEVI uint4 ldsm4p(uint32_t a, bool pred) {
    uint4 v; asm volatile("{.reg .pred p; setp.ne.u32 p, %5, 0; @p ldmatrix.sync.aligned.m8n8.x4.shared.b16 {%0,%1,%2,%3}, [%4];}" : "=r"(v.x), "=r"(v.y), "=r"(v.z), "=r"(v.w) : "r"(a), "r"((uint32_t)pred) : "memory"); return v;
}
DEVI uint4 ldsm4t(uint32_t a) { uint4 v; asm volatile("ldmatrix.sync.aligned.m8n8.x4.trans.shared.b16 {%0,%1,%2,%3}, [%4];" : "=r"(v.x), "=r"(v.y), "=r"(v.z), "=r"(v.w) : "r"(a) : "memory"); return v; }
DEVI uint2 ldsm2(uint32_t a) { uint2 v; asm volatile("ldmatrix.sync.aligned.m8n8.x2.shared.b16 {%0,%1}, [%2];" : "=r"(v.x), "=r"(v.y) : "r"(a) : "memory"); return v; }
DEVI void stsm4t(uint32_t a, uint32_t x, uint32_t y, uint32_t z, uint32_t w) { asm volatile("stmatrix.sync.aligned.m8n8.x4.trans.shared.b16 [%0], {%1,%2,%3,%4};" :: "r"(a), "r"(x), "r"(y), "r"(z), "r"(w) : "memory"); }
DEVI void sts128(uint32_t a, uint32_t x, uint32_t y, uint32_t z, uint32_t w) { asm volatile("st.shared.v4.u32 [%0], {%1,%2,%3,%4};" :: "r"(a), "r"(x), "r"(y), "r"(z), "r"(w) : "memory"); }
DEVI void sts64(uint32_t a, uint32_t x, uint32_t y) { asm volatile("st.shared.v2.u32 [%0], {%1,%2};" :: "r"(a), "r"(x), "r"(y) : "memory"); }
DEVI void sts32(uint32_t a, uint32_t x) { asm volatile("st.shared.u32 [%0], %1;" :: "r"(a), "r"(x) : "memory"); }
DEVI void sts32p(uint32_t a, uint32_t x, bool pred) { asm volatile("{.reg .pred p; setp.ne.u32 p, %2, 0; @p st.shared.u32 [%0], %1;}" :: "r"(a), "r"(x), "r"((uint32_t)pred) : "memory"); }
DEVI void sta128(uint32_t a, uint32_t x, uint32_t y, uint32_t z, uint32_t w, uint32_t bar) {
    asm volatile("st.async.weak.shared::cluster.mbarrier::complete_tx::bytes.v4.b32 [%0], {%1,%2,%3,%4}, [%5];" :: "r"(a), "r"(x), "r"(y), "r"(z), "r"(w), "r"(bar) : "memory");
}
DEVI void sta128p(uint32_t a, uint32_t x, uint32_t y, uint32_t z, uint32_t w, uint32_t bar, bool pred) {
    asm volatile("{.reg .pred p; setp.ne.u32 p, %6, 0; @p st.async.weak.shared::cluster.mbarrier::complete_tx::bytes.v4.b32 [%0], {%1,%2,%3,%4}, [%5];}" :: "r"(a), "r"(x), "r"(y), "r"(z), "r"(w), "r"(bar), "r"((uint32_t)pred) : "memory");
}
DEVI void sta64(uint32_t a, uint32_t x, uint32_t y, uint32_t bar) {
    asm volatile("st.async.weak.shared::cluster.mbarrier::complete_tx::bytes.v2.b32 [%0], {%1,%2}, [%3];" :: "r"(a), "r"(x), "r"(y), "r"(bar) : "memory");
}
DEVI void sta32(uint32_t a, uint32_t x, uint32_t bar) {
    asm volatile("st.async.weak.shared::cluster.mbarrier::complete_tx::bytes.b32 [%0], %1, [%2];" :: "r"(a), "r"(x), "r"(bar) : "memory");
}
DEVI uint4 ldg_pkt(const void* p) {
    uint4 v;
    asm volatile("ld.relaxed.gpu.global.v4.u32 {%0,%1,%2,%3}, [%4];" : "=r"(v.x), "=r"(v.y), "=r"(v.z), "=r"(v.w) : "l"(p) : "memory");
    return v;
}
DEVI void ldg_pkt_if(uint4& v, const void* p, bool pred) {
    asm volatile("{.reg .pred p; setp.ne.u32 p, %5, 0; @p ld.relaxed.gpu.global.v4.u32 {%0,%1,%2,%3}, [%4];}"
        : "+r"(v.x), "+r"(v.y), "+r"(v.z), "+r"(v.w) : "l"(p), "r"((uint32_t)pred) : "memory");
}
DEVI void ldg_pkt_retry(uint4& v, const void* p, uint32_t tag) {
    asm volatile("{.reg .pred p; .reg .b32 t; lop3.b32 t, %0, %5, 1, 0x28; setp.ne.u32 p, t, 0; @p ld.relaxed.gpu.global.v4.u32 {%0,%1,%2,%3}, [%4];}"
        : "+r"(v.x), "+r"(v.y), "+r"(v.z), "+r"(v.w) : "l"(p), "r"(tag) : "memory");
}
DEVI void stg_pkt(void* p, uint32_t x, uint32_t y, uint32_t z, uint32_t w) {
    asm volatile("st.relaxed.gpu.global.v4.u32 [%0], {%1,%2,%3,%4};" :: "l"(p), "r"(x), "r"(y), "r"(z), "r"(w) : "memory");
}
DEVI uint32_t ldg_word(const void* p) { uint32_t v; asm volatile("ld.relaxed.gpu.global.u32 %0, [%1];" : "=r"(v) : "l"(p) : "memory"); return v; }
DEVI void stg_word(void* p, uint32_t x, bool pred) {
    asm volatile("{.reg .pred p; setp.ne.u32 p, %2, 0; @p st.relaxed.gpu.global.u32 [%0], %1;}" :: "l"(p), "r"(x), "r"((uint32_t)pred) : "memory");
}
DEVI uint2 ldg64nc(const void* p) { uint2 v; asm volatile("ld.global.nc.L1::no_allocate.v2.u32 {%0,%1}, [%2];" : "=r"(v.x), "=r"(v.y) : "l"(p)); return v; }
DEVI void prefetch_l2(const void* p, uint32_t bytes) { asm volatile("cp.async.bulk.prefetch.L2.global [%0], %1;" :: "l"(p), "r"(bytes) : "memory"); }
DEVI uint4 ldg128(const void* p) { uint4 v; asm volatile("ld.global.cg.v4.u32 {%0,%1,%2,%3}, [%4];" : "=r"(v.x), "=r"(v.y), "=r"(v.z), "=r"(v.w) : "l"(p) : "memory"); return v; }
DEVI uint2 ldg64(const void* p) { uint2 v; asm volatile("ld.global.cg.v2.u32 {%0,%1}, [%2];" : "=r"(v.x), "=r"(v.y) : "l"(p) : "memory"); return v; }
DEVI uint32_t ldg32(const void* p) { uint32_t v; asm volatile("ld.global.cg.u32 %0, [%1];" : "=r"(v) : "l"(p) : "memory"); return v; }
DEVI void stg128(void* p, uint32_t x, uint32_t y, uint32_t z, uint32_t w) { asm volatile("st.global.cg.v4.u32 [%0], {%1,%2,%3,%4};" :: "l"(p), "r"(x), "r"(y), "r"(z), "r"(w) : "memory"); }
DEVI void stg128p(void* p, uint32_t x, uint32_t y, uint32_t z, uint32_t w, bool pred) { asm volatile("{.reg .pred p; setp.ne.u32 p, %5, 0; @p st.global.cg.v4.u32 [%0], {%1,%2,%3,%4};}" :: "l"(p), "r"(x), "r"(y), "r"(z), "r"(w), "r"((uint32_t)pred) : "memory"); }
DEVI void stg64(void* p, uint32_t x, uint32_t y) { asm volatile("st.global.cg.v2.u32 [%0], {%1,%2};" :: "l"(p), "r"(x), "r"(y) : "memory"); }
DEVI void stg32(void* p, uint32_t x) { asm volatile("st.global.cg.u32 [%0], %1;" :: "l"(p), "r"(x) : "memory"); }
DEVI void cp16(uint32_t dst, const void* src) { asm volatile("cp.async.cg.shared.global [%0], [%1], 16;" :: "r"(dst), "l"(src) : "memory"); }
DEVI void cp16_if(uint32_t dst, const void* src, bool pred) { asm volatile("{.reg .pred p; setp.ne.u32 p, %2, 0; @p cp.async.cg.shared.global [%0], [%1], 16;}" :: "r"(dst), "l"(src), "r"((uint32_t)pred) : "memory"); }
DEVI void cp_commit() { asm volatile("cp.async.commit_group;" ::: "memory"); }
DEVI void cp4(uint32_t dst, const void* src) { asm volatile("cp.async.ca.shared.global [%0], [%1], 4;" :: "r"(dst), "l"(src) : "memory"); }
template <int N> DEVI void cp_wait() { asm volatile("cp.async.wait_group %0;" :: "n"(N) : "memory"); }
DEVI void cp_wait_all() { asm volatile("cp.async.wait_all;" ::: "memory"); }
DEVI void bar_sync(int id, int n) { asm volatile("bar.sync %0, %1;" :: "r"(id), "r"(n) : "memory"); }
DEVI void bar_arrive(int id, int n) { asm volatile("bar.arrive %0, %1;" :: "r"(id), "r"(n) : "memory"); }
DEVI void fence_async_smem() { asm volatile("fence.proxy.async.shared::cta;" ::: "memory"); }
DEVI void fence_async_global() { asm volatile("fence.proxy.async.global;" ::: "memory"); }
DEVI void mbar_init(uint32_t b, int n) { asm volatile("mbarrier.init.shared.b64 [%0], %1;" :: "r"(b), "r"(n) : "memory"); }
DEVI void mbar_expect(uint32_t b, uint32_t bytes, bool pred) {
    asm volatile("{.reg .pred p; setp.ne.u32 p, %2, 0; @p mbarrier.arrive.expect_tx.shared.b64 _, [%0], %1;}" :: "r"(b), "r"(bytes), "r"((uint32_t)pred) : "memory");
}
DEVI void mbar_arrive(uint32_t b, bool pred) { asm volatile("{.reg .pred p; setp.ne.u32 p, %1, 0; @p mbarrier.arrive.shared.b64 _, [%0];}" :: "r"(b), "r"((uint32_t)pred) : "memory"); }
DEVI void mbar_arrive_all3(uint32_t b, uint32_t lane) {
    asm volatile("{.reg .pred p; .reg .u32 a; setp.lt.u32 p, %1, 3; @p mapa.shared::cluster.u32 a, %0, %1; @p mbarrier.arrive.relaxed.cluster.shared::cluster.b64 _, [a];}" :: "r"(b), "r"(lane) : "memory");
}
#define FAULT "or.b32 n, n, 1; st.volatile.shared.u32 [n], n;\n"
#define LIM1 "400000"
#define LIM2 "2000000"
DEVI void fault_if(bool p, uint32_t n) { asm volatile("{.reg .pred p; setp.ne.u32 p, %0, 0; @p st.volatile.shared.u32 [%1], %1;}" :: "r"((uint32_t)p), "r"(n | 1) : "memory"); }
DEVI void mbar_wait(uint32_t b, uint32_t parity) {
    asm volatile("{.reg .pred p; .reg .u32 n;\n"
        "mbarrier.try_wait.parity.shared::cta.b64 p, [%0], %1;\n"
        "@p bra.uni D%=;\n"
        "mov.u32 n, 0;\n"
        "W%=: mbarrier.try_wait.parity.shared::cta.b64 p, [%0], %1;\n"
        "@p bra.uni D%=;\n"
        "add.u32 n, n, 1; setp.lt.u32 p, n, " LIM1 "; @p bra.uni W%=;\n"
        FAULT
        "D%=:}" :: "r"(b), "r"(parity) : "memory");
}
constexpr int POLL_LIMIT = 2000000;
DEVI void cnt_wait(const unsigned* c, unsigned target) {
    asm volatile("{.reg .pred p; .reg .u32 n, v;\n"
        "ld.acquire.gpu.global.u32 v, [%0];\n"
        "setp.ge.u32 p, v, %1; vote.sync.all.pred p, p, 0xffffffff; @p bra.uni D%=;\n"
        "mov.u32 n, 0;\n"
        "W%=: ld.acquire.gpu.global.u32 v, [%0];\n"
        "setp.ge.u32 p, v, %1; vote.sync.all.pred p, p, 0xffffffff; @p bra.uni D%=;\n"
        "add.u32 n, n, 1; setp.lt.u32 p, n, " LIM2 "; @p bra.uni W%=;\n"
        FAULT
        "D%=:}" :: "l"(c), "r"(target) : "memory");
}
DEVI void hint_wait(const unsigned* c, unsigned target) {
    asm volatile("{.reg .pred p; .reg .u32 n, v;\n"
        "ld.relaxed.gpu.global.u32 v, [%0];\n"
        "setp.ge.u32 p, v, %1; vote.sync.all.pred p, p, 0xffffffff; @p bra.uni D%=;\n"
        "mov.u32 n, 0;\n"
        "W%=: ld.relaxed.gpu.global.u32 v, [%0];\n"
        "setp.ge.u32 p, v, %1; vote.sync.all.pred p, p, 0xffffffff; @p bra.uni D%=;\n"
        "add.u32 n, n, 1; setp.lt.u32 p, n, " LIM2 "; @p bra.uni W%=;\n"
        FAULT
        "D%=:}" :: "l"(c), "r"(target) : "memory");
}
DEVI bool cnt_poll(const unsigned* c, unsigned target, uint32_t b, uint32_t parity) {
    uint32_t r;
    asm volatile("{.reg .pred p; .reg .u32 n, v;\n"
        "mov.u32 n, 0; mov.u32 %0, 0;\n"
        "W%=: ld.acquire.gpu.global.u32 v, [%1];\n"
        "setp.ge.u32 p, v, %2; vote.sync.all.pred p, p, 0xffffffff; @p bra.uni D%=;\n"
        "mbarrier.test_wait.parity.shared::cta.b64 p, [%3], %4;\n"
        "add.u32 n, n, 1; setp.gt.or.u32 p, n, 1000, p; vote.sync.any.pred p, p, 0xffffffff; @!p bra.uni W%=;\n"
        "mov.u32 %0, 1;\n"
        "D%=:}" : "=r"(r) : "l"(c), "r"(target), "r"(b), "r"(parity) : "memory");
    return r;
}
template <int N = 1> DEVI void cnt_add(unsigned* c, int lane) {
    asm volatile("{.reg .pred p; setp.eq.u32 p, %1, 0; fence.acq_rel.gpu; bar.warp.sync 0xffffffff; @p red.relaxed.gpu.global.add.u32 [%0], %2;}" :: "l"(c + lane), "r"(lane), "n"(N) : "memory");
}
DEVI void cnt_hint(unsigned* c, int lane) {
    asm volatile("{.reg .pred p; setp.eq.u32 p, %1, 0; @p red.relaxed.gpu.global.add.u32 [%0], 1;}" :: "l"(c + lane), "r"(lane) : "memory");
}
template <int N = NT> DEVI uint32_t ring_tag(unsigned u, uint32_t ep) { return (u / RING + ep * ((N - 1 - u % RING) / RING + 1) + 1) & 1; }
static_assert(RING >= LAGA && RING > LAG, "ring too short");
DEVI uint32_t lop_bad(uint32_t acc, uint32_t x, uint32_t y, uint32_t tag) {
    uint32_t d; asm("{.reg .b32 t; lop3.b32 t, %2, %3, %4, 0x7e; or.b32 %0, t, %1;}" : "=r"(d) : "r"(acc), "r"(x), "r"(y), "r"(tag)); return d;
}
template <int N> DEVI void validate(uint4* v, const void* p, int step, uint32_t tag) {
    for (int n = 0;; n++) {
        uint32_t bad = 0;
#pragma unroll
        for (int i = 0; i < N; i += 2) bad = lop_bad(bad, v[i].x, v[i + 1 < N ? i + 1 : i].x, tag);
        if (!__any_sync(~0u, bad & 1)) break;
#pragma unroll
        for (int i = 0; i < N; i++) ldg_pkt_retry(v[i], static_cast<const char*>(p) + i * step, tag);
        fault_if(n > POLL_LIMIT, n);
    }
}
DEVI uint32_t page_par(uint32_t off) { return __popc((off >> 12) & 0xb2) & 1; }
DEVI uint32_t inbox_off(int b) { return (b >> 1) * 32768 + (b & 1) * 8192; }
DEVI uint32_t mem_off(int w, int i) { return 0x180000 + w * 1024 + (i & 1) * 512 + (i & 3) * 16384 + (i < 4 ? 0 : i < 8 ? 0x30000 : 0x40000); }
DEVI void sched_fence(uint32_t zero, uint32_t id) { asm volatile("{.reg .pred p; setp.ne.u32 p, %0, %1; @p bra.uni D%=; exit; D%=:}" :: "r"(zero), "r"(id) : "memory"); }
DEVI uint32_t clk() { uint32_t c; asm volatile("mov.u32 %0, %%clock;" : "=r"(c) :: "memory"); return c; }
DEVI void delay(uint32_t n) {
    if (n) asm volatile("{.reg .pred p; .reg .u32 c, e; mov.u32 e, %%clock;\n W%=: mov.u32 c, %%clock; sub.u32 c, c, e; setp.lt.u32 p, c, %0; @p bra.uni W%=;}" :: "r"(n) : "memory");
}
DEVI void delay_until(uint32_t t0, uint32_t n) {
    asm volatile("{.reg .pred p; .reg .u32 c;\n W%=: mov.u32 c, %%clock; sub.u32 c, c, %1; setp.lt.u32 p, c, %0; @p bra.uni W%=;}" :: "r"(n), "r"(t0) : "memory");
}
DEVI void wg_fence() { asm volatile("wgmma.fence.sync.aligned;" ::: "memory"); }
DEVI void wg_commit() { asm volatile("wgmma.commit_group.sync.aligned;" ::: "memory"); }
template <int N> DEVI void wg_wait() { asm volatile("wgmma.wait_group.sync.aligned %0;" :: "n"(N) : "memory"); }
DEVI uint64_t mkdesc(uint32_t lo, uint32_t hi) { uint64_t d; asm("mov.b64 %0, {%1,%2};" : "=l"(d) : "r"(lo), "r"(hi)); return d; }
DEVI void cluster_arrive() { asm volatile("barrier.cluster.arrive.relaxed.aligned;" ::: "memory"); }
DEVI void cluster_wait() { asm volatile("barrier.cluster.wait.aligned;" ::: "memory"); }
DEVI void cluster_sync() { asm volatile("barrier.cluster.arrive.aligned;\n barrier.cluster.wait.aligned;" ::: "memory"); }
DEVI void wgmma_ss16t(float (&d)[8], uint64_t da, uint64_t db, int acc) {
    asm volatile("{.reg .pred p; setp.ne.b32 p, %10, 0;\n"
        "wgmma.mma_async.sync.aligned.m64n16k16.f32.bf16.bf16 {%0,%1,%2,%3,%4,%5,%6,%7}, %8, %9, p, 1, 1, 0, 1;}"
        : "+f"(d[0]), "+f"(d[1]), "+f"(d[2]), "+f"(d[3]), "+f"(d[4]), "+f"(d[5]), "+f"(d[6]), "+f"(d[7])
        : "l"(da), "l"(db), "r"(acc));
}
DEVI void wgmma_ss16a(float (&d)[8], uint64_t da, uint64_t db, int acc) {
    asm volatile("{.reg .pred p; setp.ne.b32 p, %10, 0;\n"
        "wgmma.mma_async.sync.aligned.m64n16k16.f32.bf16.bf16 {%0,%1,%2,%3,%4,%5,%6,%7}, %8, %9, p, 1, 1, 1, 0;}"
        : "+f"(d[0]), "+f"(d[1]), "+f"(d[2]), "+f"(d[3]), "+f"(d[4]), "+f"(d[5]), "+f"(d[6]), "+f"(d[7])
        : "l"(da), "l"(db), "r"(acc));
}
DEVI void wgmma_ss64(float (&d)[32], uint64_t da, uint64_t db, int acc) {
    asm volatile("{.reg .pred p; setp.ne.b32 p, %34, 0;\n"
        "wgmma.mma_async.sync.aligned.m64n64k16.f32.bf16.bf16 {%0,%1,%2,%3,%4,%5,%6,%7,%8,%9,%10,%11,%12,%13,%14,%15,%16,%17,%18,%19,%20,%21,%22,%23,%24,%25,%26,%27,%28,%29,%30,%31}, %32, %33, p, 1, 1, 0, 0;}"
        : "+f"(d[0]), "+f"(d[1]), "+f"(d[2]), "+f"(d[3]), "+f"(d[4]), "+f"(d[5]), "+f"(d[6]), "+f"(d[7]), "+f"(d[8]), "+f"(d[9]), "+f"(d[10]), "+f"(d[11]), "+f"(d[12]), "+f"(d[13]), "+f"(d[14]), "+f"(d[15]), "+f"(d[16]), "+f"(d[17]), "+f"(d[18]), "+f"(d[19]), "+f"(d[20]), "+f"(d[21]), "+f"(d[22]), "+f"(d[23]), "+f"(d[24]), "+f"(d[25]), "+f"(d[26]), "+f"(d[27]), "+f"(d[28]), "+f"(d[29]), "+f"(d[30]), "+f"(d[31])
        : "l"(da), "l"(db), "r"(acc));
}
DEVI void wgmma_rs16t(float (&d)[8], uint32_t a0, uint32_t a1, uint32_t a2, uint32_t a3, uint64_t db, int acc) {
    asm volatile("{.reg .pred p; setp.ne.b32 p, %13, 0;\n"
        "wgmma.mma_async.sync.aligned.m64n16k16.f32.bf16.bf16 {%0,%1,%2,%3,%4,%5,%6,%7}, {%8,%9,%10,%11}, %12, p, 1, 1, 1;}"
        : "+f"(d[0]), "+f"(d[1]), "+f"(d[2]), "+f"(d[3]), "+f"(d[4]), "+f"(d[5]), "+f"(d[6]), "+f"(d[7])
        : "r"(a0), "r"(a1), "r"(a2), "r"(a3), "l"(db), "r"(acc));
}
DEVI void wgmma_rs64(float (&d)[32], uint32_t a0, uint32_t a1, uint32_t a2, uint32_t a3, uint64_t db, int acc) {
    asm volatile("{.reg .pred p; setp.ne.b32 p, %37, 0;\n"
        "wgmma.mma_async.sync.aligned.m64n64k16.f32.bf16.bf16 {%0,%1,%2,%3,%4,%5,%6,%7,%8,%9,%10,%11,%12,%13,%14,%15,%16,%17,%18,%19,%20,%21,%22,%23,%24,%25,%26,%27,%28,%29,%30,%31}, {%32,%33,%34,%35}, %36, p, 1, 1, 0;}"
        : "+f"(d[0]), "+f"(d[1]), "+f"(d[2]), "+f"(d[3]), "+f"(d[4]), "+f"(d[5]), "+f"(d[6]), "+f"(d[7]), "+f"(d[8]), "+f"(d[9]), "+f"(d[10]), "+f"(d[11]), "+f"(d[12]), "+f"(d[13]), "+f"(d[14]), "+f"(d[15]), "+f"(d[16]), "+f"(d[17]), "+f"(d[18]), "+f"(d[19]), "+f"(d[20]), "+f"(d[21]), "+f"(d[22]), "+f"(d[23]), "+f"(d[24]), "+f"(d[25]), "+f"(d[26]), "+f"(d[27]), "+f"(d[28]), "+f"(d[29]), "+f"(d[30]), "+f"(d[31])
        : "r"(a0), "r"(a1), "r"(a2), "r"(a3), "l"(db), "r"(acc));
}
DEVI void wgmma_ss168t(float (&d)[84], uint64_t da, uint64_t db, int acc) {
    asm volatile("{.reg .pred p; setp.ne.b32 p, %86, 0;\n"
        "wgmma.mma_async.sync.aligned.m64n168k16.f32.bf16.bf16 {%0,%1,%2,%3,%4,%5,%6,%7,%8,%9,%10,%11,%12,%13,%14,%15,%16,%17,%18,%19,%20,%21,%22,%23,%24,%25,%26,%27,%28,%29,%30,%31,%32,%33,%34,%35,%36,%37,%38,%39,%40,%41,%42,%43,%44,%45,%46,%47,%48,%49,%50,%51,%52,%53,%54,%55,%56,%57,%58,%59,%60,%61,%62,%63,%64,%65,%66,%67,%68,%69,%70,%71,%72,%73,%74,%75,%76,%77,%78,%79,%80,%81,%82,%83}, %84, %85, p, 1, 1, 0, 1;}"
        : "+f"(d[0]), "+f"(d[1]), "+f"(d[2]), "+f"(d[3]), "+f"(d[4]), "+f"(d[5]), "+f"(d[6]), "+f"(d[7]), "+f"(d[8]), "+f"(d[9]), "+f"(d[10]), "+f"(d[11]), "+f"(d[12]), "+f"(d[13]), "+f"(d[14]), "+f"(d[15]), "+f"(d[16]), "+f"(d[17]), "+f"(d[18]), "+f"(d[19]), "+f"(d[20]), "+f"(d[21]), "+f"(d[22]), "+f"(d[23]), "+f"(d[24]), "+f"(d[25]), "+f"(d[26]), "+f"(d[27]), "+f"(d[28]), "+f"(d[29]), "+f"(d[30]), "+f"(d[31]), "+f"(d[32]), "+f"(d[33]), "+f"(d[34]), "+f"(d[35]), "+f"(d[36]), "+f"(d[37]), "+f"(d[38]), "+f"(d[39]), "+f"(d[40]), "+f"(d[41]), "+f"(d[42]), "+f"(d[43]), "+f"(d[44]), "+f"(d[45]), "+f"(d[46]), "+f"(d[47]), "+f"(d[48]), "+f"(d[49]), "+f"(d[50]), "+f"(d[51]), "+f"(d[52]), "+f"(d[53]), "+f"(d[54]), "+f"(d[55]), "+f"(d[56]), "+f"(d[57]), "+f"(d[58]), "+f"(d[59]), "+f"(d[60]), "+f"(d[61]), "+f"(d[62]), "+f"(d[63]), "+f"(d[64]), "+f"(d[65]), "+f"(d[66]), "+f"(d[67]), "+f"(d[68]), "+f"(d[69]), "+f"(d[70]), "+f"(d[71]), "+f"(d[72]), "+f"(d[73]), "+f"(d[74]), "+f"(d[75]), "+f"(d[76]), "+f"(d[77]), "+f"(d[78]), "+f"(d[79]), "+f"(d[80]), "+f"(d[81]), "+f"(d[82]), "+f"(d[83])
        : "l"(da), "l"(db), "r"(acc));
}
DEVI void wgmma_rs96t(float (&d)[48], uint32_t a0, uint32_t a1, uint32_t a2, uint32_t a3, uint64_t db, int acc) {
    asm volatile("{.reg .pred p; setp.ne.b32 p, %53, 0;\n"
        "wgmma.mma_async.sync.aligned.m64n96k16.f32.bf16.bf16 {%0,%1,%2,%3,%4,%5,%6,%7,%8,%9,%10,%11,%12,%13,%14,%15,%16,%17,%18,%19,%20,%21,%22,%23,%24,%25,%26,%27,%28,%29,%30,%31,%32,%33,%34,%35,%36,%37,%38,%39,%40,%41,%42,%43,%44,%45,%46,%47}, {%48,%49,%50,%51}, %52, p, 1, 1, 1;}"
        : "+f"(d[0]), "+f"(d[1]), "+f"(d[2]), "+f"(d[3]), "+f"(d[4]), "+f"(d[5]), "+f"(d[6]), "+f"(d[7]), "+f"(d[8]), "+f"(d[9]), "+f"(d[10]), "+f"(d[11]), "+f"(d[12]), "+f"(d[13]), "+f"(d[14]), "+f"(d[15]), "+f"(d[16]), "+f"(d[17]), "+f"(d[18]), "+f"(d[19]), "+f"(d[20]), "+f"(d[21]), "+f"(d[22]), "+f"(d[23]), "+f"(d[24]), "+f"(d[25]), "+f"(d[26]), "+f"(d[27]), "+f"(d[28]), "+f"(d[29]), "+f"(d[30]), "+f"(d[31]), "+f"(d[32]), "+f"(d[33]), "+f"(d[34]), "+f"(d[35]), "+f"(d[36]), "+f"(d[37]), "+f"(d[38]), "+f"(d[39]), "+f"(d[40]), "+f"(d[41]), "+f"(d[42]), "+f"(d[43]), "+f"(d[44]), "+f"(d[45]), "+f"(d[46]), "+f"(d[47])
        : "r"(a0), "r"(a1), "r"(a2), "r"(a3), "l"(db), "r"(acc));
}
DEVI void wgmma_rs192t(float (&d)[96], uint32_t a0, uint32_t a1, uint32_t a2, uint32_t a3, uint64_t db, int acc) {
    asm volatile("{.reg .pred p; setp.ne.b32 p, %101, 0;\n"
        "wgmma.mma_async.sync.aligned.m64n192k16.f32.bf16.bf16 {%0,%1,%2,%3,%4,%5,%6,%7,%8,%9,%10,%11,%12,%13,%14,%15,%16,%17,%18,%19,%20,%21,%22,%23,%24,%25,%26,%27,%28,%29,%30,%31,%32,%33,%34,%35,%36,%37,%38,%39,%40,%41,%42,%43,%44,%45,%46,%47,%48,%49,%50,%51,%52,%53,%54,%55,%56,%57,%58,%59,%60,%61,%62,%63,%64,%65,%66,%67,%68,%69,%70,%71,%72,%73,%74,%75,%76,%77,%78,%79,%80,%81,%82,%83,%84,%85,%86,%87,%88,%89,%90,%91,%92,%93,%94,%95}, {%96,%97,%98,%99}, %100, p, 1, 1, 1;}"
        : "+f"(d[0]), "+f"(d[1]), "+f"(d[2]), "+f"(d[3]), "+f"(d[4]), "+f"(d[5]), "+f"(d[6]), "+f"(d[7]), "+f"(d[8]), "+f"(d[9]), "+f"(d[10]), "+f"(d[11]), "+f"(d[12]), "+f"(d[13]), "+f"(d[14]), "+f"(d[15]), "+f"(d[16]), "+f"(d[17]), "+f"(d[18]), "+f"(d[19]), "+f"(d[20]), "+f"(d[21]), "+f"(d[22]), "+f"(d[23]), "+f"(d[24]), "+f"(d[25]), "+f"(d[26]), "+f"(d[27]), "+f"(d[28]), "+f"(d[29]), "+f"(d[30]), "+f"(d[31]), "+f"(d[32]), "+f"(d[33]), "+f"(d[34]), "+f"(d[35]), "+f"(d[36]), "+f"(d[37]), "+f"(d[38]), "+f"(d[39]), "+f"(d[40]), "+f"(d[41]), "+f"(d[42]), "+f"(d[43]), "+f"(d[44]), "+f"(d[45]), "+f"(d[46]), "+f"(d[47]), "+f"(d[48]), "+f"(d[49]), "+f"(d[50]), "+f"(d[51]), "+f"(d[52]), "+f"(d[53]), "+f"(d[54]), "+f"(d[55]), "+f"(d[56]), "+f"(d[57]), "+f"(d[58]), "+f"(d[59]), "+f"(d[60]), "+f"(d[61]), "+f"(d[62]), "+f"(d[63]), "+f"(d[64]), "+f"(d[65]), "+f"(d[66]), "+f"(d[67]), "+f"(d[68]), "+f"(d[69]), "+f"(d[70]), "+f"(d[71]), "+f"(d[72]), "+f"(d[73]), "+f"(d[74]), "+f"(d[75]), "+f"(d[76]), "+f"(d[77]), "+f"(d[78]), "+f"(d[79]), "+f"(d[80]), "+f"(d[81]), "+f"(d[82]), "+f"(d[83]), "+f"(d[84]), "+f"(d[85]), "+f"(d[86]), "+f"(d[87]), "+f"(d[88]), "+f"(d[89]), "+f"(d[90]), "+f"(d[91]), "+f"(d[92]), "+f"(d[93]), "+f"(d[94]), "+f"(d[95])
        : "r"(a0), "r"(a1), "r"(a2), "r"(a3), "l"(db), "r"(acc));
}

#define TRD(t, i)
namespace km {
#define NSS 6
#define RG "184"
#define RW "136"
#define NFL 2
#define NR1 3
#define NR2 3
#define FK 5
#define LDP 3
#define SND 1
#define NGAP 0
constexpr int O_H = 0;
constexpr int O_MB = 73728;
constexpr int O_VX = 96768;
constexpr int O_KX = 113152;
constexpr int O_QX = 119296;
constexpr int O_VM = 125440;
constexpr int O_KM = 129536;
constexpr int O_QM = 131072;
constexpr int O_SM = 132608;
constexpr int O_ST = 135168;
constexpr int O_OX = 145408;
constexpr int O_WO = 149504;
constexpr int O_OS = O_WO;
constexpr int O_WS = O_WO + 49152;
constexpr int O_RL = 110592;
constexpr int O_BAR = O_WS + NSS * 4096;
constexpr int SMEM = O_BAR + 128 + 1024 + TR_BYTES;
enum { B_X = 0, B_XFREE = 8, B_WIN = 16, B_VX = 24, B_SM = 32, B_ST = 40, B_EP = 56 };
#define DLY1 (100 * w)
#define DLY2 300
#define HON 100
#define GON 1
#define DLY0 1000
#define PFON 0
#define PLACE 1
#define XST 0
#define DLYW 12000
#define DLYB 14000
constexpr uint32_t DESC_HI = (1024 >> 4) | (1u << 30);
constexpr float SC = 0.08838834764831845f * 1.4426950408889634f;
}

__global__ void __cluster_dims__(3, 1, 1) __launch_bounds__(384, 1)
k_main(const __nv_bfloat16* __restrict__ x0, const __nv_bfloat16* __restrict__ wqkv, const __nv_bfloat16* __restrict__ wo,
       const __nv_bfloat16* __restrict__ mem0, const __nv_bfloat16* __restrict__ Wq, const __nv_bfloat16* __restrict__ Wk,
       const __nv_bfloat16* __restrict__ Wv, const __nv_bfloat16* __restrict__ Wo) {
    using namespace km;
    extern __shared__ unsigned char smem_raw[];
    const uint32_t sb = (smem_u32(smem_raw) + 1023) & ~1023u;
    const int tid = threadIdx.x, lane = tid & 31, warp = __shfl_sync(~0u, tid >> 5, 0);
    uint32_t l16 = __shfl_sync(~0u, lane * 16, lane);
#define OPQ() asm volatile("" : "+r"(l16))
    const int b = blockIdx.x, h = b / 3, r = b % 3;
    const int nq = r == 2 ? 2 : 3;
    const uint32_t bar = sb + O_BAR;
    asm volatile("griddepcontrol.launch_dependents;");
    const uint32_t t_start = clk();
    if (warp == 0 && b < 72) {
        if (lane == 0) { mbar_init(bar + 96, 1); fence_async_smem(); mbar_expect(bar + 96, 8 * 3456, true); }
        __syncwarp();
        if (lane < 8) asm volatile("cp.async.bulk.shared::cluster.global.mbarrier::complete_tx::bytes [%0], [%1], 3456, [%2];" :: "r"(sb + O_RL + lane * 3472), "l"(wqkv + (b * 8 + lane) * 1728), "r"(bar + 96) : "memory");
    }
    if (tid == 352) {
        prefetch_l2(x0 + b * (2 * DM), 2 * 1152); prefetch_l2(wo + b * (6 * DM), 6 * 1152);
    }
    if (tid == 320) sts32(bar + 64, ldg32(&g_epoch));
#define EP lds32(bar + 64)
    TR_INIT(bar + 128);
    TRG(79, 0);
    uint32_t roff0, roff1;
    {
        uint32_t y0, y1;
        asm("mapa.shared::cluster.u32 %0, %1, %2;" : "=r"(y0) : "r"(sb), "r"((r + 1) % 3));
        asm("mapa.shared::cluster.u32 %0, %1, %2;" : "=r"(y1) : "r"(sb), "r"((r + 2) % 3));
        roff0 = y0 - sb; roff1 = y1 - sb;
    }
#define IDENT (((l16 >> 7) == ((l16 >> 4) & 3) ? 0x3f80u : 0u) << ((l16 >> 2) & 16))
#define LSWAP ((l16 & 0x70) | ((l16 & 0x80) << 1) | ((l16 & 0x100) >> 1))
    const uint32_t nv_remote = 8 - (8 - 2 * nq);

    if (warp < 8) {
        asm volatile("setmaxnreg.inc.sync.aligned.u32 " RG ";");
        constexpr int SSP = 36 / NSS;
#define IS_SS(kk) ((kk) % SSP == 3)
#define AI(kk) (4 * ((kk) - ((kk) + SSP - 4) / SSP))
        uint32_t a[144 - 4 * NSS];
        {
            const int ci = tid & 15, slot = ci >> 1, d0 = tid >> 4;
            const __nv_bfloat16* src = slot < nq ? Wq + (3 * r + slot) * 16 : slot < 2 * nq ? Wk + (3 * r + slot - nq) * 16 : Wv + (2 * r + slot - 2 * nq) * 16;
            src += h * 128 + (ci & 1) * 8 + d0 * 4096;
            auto issue = [&](int q) {
#pragma unroll
                for (int i = 0; i < 3; i++) if (q < 12) cp16(sb + (q * 3 + i) * 4096 + d0 * 256 + ((ci ^ (d0 & 7)) << 4), src + (size_t)(q * 3 + i) * 65536);
                asm volatile("cp.async.commit_group;" ::: "memory");
            };
            if (b < 72) {
                bar_sync(10, 256);
                mbar_wait(bar + 96, 0);
                TR1(4);
#pragma unroll 2
                for (int ag = tid >> 3; ag < 231; ag += 32) {
                    const int a = ag / 21, gr = ag % 21, tl = gr >= 18;
                    const int head = 3 * a + (tl ? 0 : (gr % 6) >> 1), nw = tl ? min(3, 32 - head) : head < 32 ? 4 : 0;
                    const uint32_t p = sb + O_RL + (tid & 7) * 3472 + (tl ? gr - 18 : gr / 6) * 1152 + head * 36 + (tl ? 32 : (gr & 1) * 16), step = tl ? 36 : 4;
                    uint32_t v[4];
#pragma unroll
                    for (int i = 0; i < 4; i++) { v[i] = lds32(p + i * step); if (i >= nw) v[i] = 0; }
                    stg128(g_wa + ((a * 9 + (b >> 3)) * 21 + gr) * 64 + (b & 7) * 8 + (tid & 7), v[0], v[1], v[2], v[3]);
                }
            }
            {
                bar_arrive(15, 288);
                TR1(5);
                delay_until(t_start, DLY0);
#pragma unroll
                for (int q = 0; q < NFL; q++) issue(q);
            }
            TR1(1);
            const int mi = lane >> 3;
            const uint32_t ad = sb + ((mi >> 1) * 8 + (lane & 7)) * 256 + (((warp * 2 + (mi & 1)) ^ (lane & 7)) << 4);
#pragma unroll
            for (int kk = 0; kk < 36; kk++) {
                if (kk % 3 == 0) { cp_wait<NFL - 1>(); issue(kk / 3 + NFL); bar_sync(10, 256); }
                const uint4 f = ldsm4t(ad + kk * 4096);
                if (IS_SS(kk)) {
                    const uint32_t o0 = sb + O_WS + (kk / SSP) * 4096 + warp * 512 + lane * 4;
                    sts32(o0, f.x); sts32(o0 + 256, f.y); sts32(o0 + 128, f.z); sts32(o0 + 384, f.w);
                } else { a[AI(kk)] = f.x; a[AI(kk) + 1] = f.y; a[AI(kk) + 2] = f.z; a[AI(kk) + 3] = f.w; }
            }
            TR1(2);
            bar_sync(9, 384);
#pragma unroll
            for (int i = 0; i < 9; i++) sts128(sb + O_H + i * 8192 + 4096 + tid * 16, 0, 0, 0, 0);
#pragma unroll
            for (int i = 0; i < 8; i++) if (i * 256 + tid < (O_OX - O_KX) / 16) sts128(sb + O_KX + i * 4096 + tid * 16, 0, 0, 0, 0);
            fence_async_smem();
            cluster_sync();
        }
        TR1(3);
        const int kind = warp < nq ? 0 : warp < 2 * nq ? 1 : 2;
        const int sl = kind == 0 ? warp : kind == 1 ? warp - nq : 2 * r + warp - 2 * nq;
        const uint32_t adX0 = sb + (kind == 0 ? O_QX : kind == 1 ? O_KX : O_VX) + sl * 2048;
        const uint32_t adM0 = sb + (kind == 0 ? O_QM : kind == 1 ? O_KM : O_VM) + sl * 512;
        const uint32_t hlo = (((sb + O_H) >> 4) & 0x3fff) | (1u << 16);
        const uint32_t mlo = (((sb + O_MB) >> 4) & 0x3fff) | (16u << 16);
        const uint32_t wlo = (((sb + O_WS + (warp >> 2) * 2048) >> 4) & 0x3fff) | (8u << 16);
        const int L = (warp >> 1) & 1, qh = warp & 1;
        const uint32_t st = sb + O_ST + warp * 1280;

#pragma unroll 1
        for (int t = -1;; t++) {
            TR_ON(t);
            OPQ();
            const uint32_t adX = adX0 + l16, adM = adM0 + l16, l8 = l16 >> 1;
            const uint32_t lq = LSWAP;
            if (t >= 0) {
                float d0[8], d1[8];
                {
#pragma unroll
                    for (int G = 0; G < 3; G++) {
                        if (warp < 4) bar_sync(1 + G, 160); else bar_sync(12 + G, 160);
                        if (G == 0) wg_fence();
#pragma unroll
                        for (int q = 0; q < 12; q++) {
                            const int kk = 12 * G + q;
                            const uint64_t db = mkdesc(mlo + kk * 32, 8);
                            if (IS_SS(kk)) wgmma_ss16t((kk & 1) ? d1 : d0, mkdesc(wlo + (kk / SSP) * 256, 16), db, 1);
                            else wgmma_rs16t((kk & 1) ? d1 : d0, a[AI(kk)], a[AI(kk) + 1], a[AI(kk) + 2], a[AI(kk) + 3], db, kk >= 2);
                            if (kk == 0) TR(0);
                        }
                    }
                    wg_commit();
                }
#define PM(i) pk(d0[2 * (i)] + d1[2 * (i)], d0[2 * (i) + 1] + d1[2 * (i) + 1])
                if (warp >= 4) {
                    wg_wait<0>();
                    TR(1);
                    const uint32_t p0 = PM(0), p1 = PM(1), p2 = PM(2), p3 = PM(3);
                    if (kind == 2) {
                        sts128(adM, p0, p1, p2, p3);
                        bar_arrive(4, 384);
                        sta128(adM + roff0, p0, p1, p2, p3, bar + B_SM + roff0);
                        sta128(adM + roff1, p0, p1, p2, p3, bar + B_SM + roff1);
                    } else {
                        stsm4t(adM, p0, p1, p2, p3);
                        bar_arrive(4, 384);
                    }
                } else {
                    uint4 q[3], k[3][2];
                    mbar_wait(bar + B_EP, t & 1);
#pragma unroll
                    for (int m = 0; m < LDP; m++) {
                        q[m] = ldsm4(sb + O_QX + m * 2048 + warp * 512 + lq);
                        k[m][0] = ldsm4(sb + O_KX + m * 2048 + L * 1024 + l16); k[m][1] = ldsm4(sb + O_KX + m * 2048 + L * 1024 + 512 + l16);
                    }
                    wg_wait<0>();
                    TR(1);
                    stsm4t(adM, PM(0), PM(1), PM(2), PM(3));
                    bar_arrive(4, 384);
                    sched_fence(gridDim.y, 6);
#pragma unroll
                    for (int m = LDP; m < 3; m++) {
                        q[m] = ldsm4(sb + O_QX + m * 2048 + warp * 512 + lq);
                        k[m][0] = ldsm4(sb + O_KX + m * 2048 + L * 1024 + l16); k[m][1] = ldsm4(sb + O_KX + m * 2048 + L * 1024 + 512 + l16);
                    }
                    float s[5][4];
                    {
                        float y[4] = {0, 0, 0, 0};
#pragma unroll
                        for (int n = 0; n < 5; n++) s[n][0] = s[n][1] = s[n][2] = s[n][3] = 0.f;
#pragma unroll
                        for (int m = 0; m < 3; m++) {
                            mma16(s[0], q[m].x, q[m].y, q[m].z, q[m].w, k[m][0].x, k[m][0].y); mma16(s[1], q[m].x, q[m].y, q[m].z, q[m].w, k[m][0].z, k[m][0].w);
                            mma16(s[2], q[m].x, q[m].y, q[m].z, q[m].w, k[m][1].x, k[m][1].y); mma16(s[3], q[m].x, q[m].y, q[m].z, q[m].w, k[m][1].z, k[m][1].w);
                        }
                        auto send = [&]() {
                            uint32_t w0 = pk(s[0][0], s[0][1]), w1 = pk(s[0][2], s[0][3]), w2 = pk(s[1][0], s[1][1]), w3 = pk(s[1][2], s[1][3]);
                            sta128(st + l16 + 5120 + roff0, w0, w1, w2, w3, bar + B_ST + roff0);
                            sta128(st + l16 + roff1, w0, w1, w2, w3, bar + B_ST + roff1);
                            w0 = pk(s[2][0], s[2][1]); w1 = pk(s[2][2], s[2][3]); w2 = pk(s[3][0], s[3][1]); w3 = pk(s[3][2], s[3][3]);
                            sta128p(st + l16 + 5120 + 512 + roff0, w0, w1, w2, w3, bar + B_ST + roff0, qh);
                            sta128p(st + l16 + 512 + roff1, w0, w1, w2, w3, bar + B_ST + roff1, qh);
                        };
                        sched_fence(gridDim.y, 7);
                        bar_sync(5, 256);
                        const uint4 k01 = ldsm4(sb + O_KM + L * 256 + l16 + (l16 & 256));
                        const uint2 k2 = ldsm2(sb + O_KM + 1024 + L * 256 + l16);
                        if (SND == 0) send();
                        mma16(s[4], q[0].x, q[0].y, q[0].z, q[0].w, k01.x, k01.y);
                        mma16(y, q[1].x, q[1].y, q[1].z, q[1].w, k01.z, k01.w);
                        mma16(s[4], q[2].x, q[2].y, q[2].z, q[2].w, k2.x, k2.y);
#pragma unroll
                        for (int j = 0; j < 4; j++) s[4][j] += y[j];
                        const uint32_t w0 = pk(s[4][0], s[4][1]), w1 = pk(s[4][2], s[4][3]);
                        if (NGAP > 0) bar_arrive(11, 256);
                        sta64(st + l8 + 5120 + 1024 + roff0, w0, w1, bar + B_ST + roff0);
                        sta64(st + l8 + 1024 + roff1, w0, w1, bar + B_ST + roff1);
                        if (SND == 1) send();
                        TR(2);
                        const int lim = 16 * qh + (int)(l16 >> 6) - (int)((l16 >> 3) & 6);
#pragma unroll
                        for (int n = 0; n < 4; n++)
#pragma unroll
                            for (int j = 0; j < 4; j++) if (!(n == 0 && j >= 2) && 8 * (n - (j >> 1)) + (j & 1) > lim) s[n][j] = -1e30f;
#pragma unroll
                        for (int n = 0; n < 4; n++) asm volatile("" : "+f"(s[n][0]), "+f"(s[n][1]), "+f"(s[n][2]), "+f"(s[n][3]));
                    }
                    uint4 v0[3], v1[3]; uint2 vm[3];
                    const uint32_t vad = sb + O_VX + 3 * r * 2048 + L * 1024 + l16;
#pragma unroll
                    for (int m = 0; m < 3; m++) v0[m] = lds128(vad + m * 2048);
                    const uint32_t otag = ring_tag(t, EP);
                    uint32_t ident = IDENT;
                    asm volatile("" : "+r"(ident));
                    mbar_wait(bar + B_SM, t & 1);
                    mbar_wait(bar + B_ST, t & 1);
                    TR(3);
                    float mx0, mx1;
                    {
                        const uint4 u = lds128(st + l16), v = lds128(st + 512 + l16); const uint2 w = lds64(st + 1024 + l8);
                        const uint4 x = lds128(st + 5120 + l16), y = lds128(st + 5120 + 512 + l16); const uint2 z = lds64(st + 5120 + 1024 + l8);
                        mma8(s[0], u.x, u.y, ident); mma8(s[1], u.z, u.w, ident); mma8(s[2], v.x, v.y, ident); mma8(s[3], v.z, v.w, ident); mma8(s[4], w.x, w.y, ident);
                        mma8(s[0], x.x, x.y, ident); mma8(s[1], x.z, x.w, ident); mma8(s[2], y.x, y.y, ident); mma8(s[3], y.z, y.w, ident); mma8(s[4], z.x, z.y, ident);
                        mx0 = fmaxf(fmaxf(fmaxf(s[0][0], s[0][1]), fmaxf(s[1][0], s[1][1])), fmaxf(fmaxf(s[2][0], s[2][1]), fmaxf(s[3][0], s[3][1])));
                        mx1 = fmaxf(fmaxf(fmaxf(s[0][2], s[0][3]), fmaxf(s[1][2], s[1][3])), fmaxf(fmaxf(s[2][2], s[2][3]), fmaxf(s[3][2], s[3][3])));
                        mx0 = fmaxf(mx0, fmaxf(s[4][0], s[4][1])); mx1 = fmaxf(mx1, fmaxf(s[4][2], s[4][3]));
                    }
#pragma unroll
                    for (int o = 1; o < 4; o <<= 1) { const float2 z = shfl2(mx0, mx1, o); mx0 = fmaxf(mx0, z.x); mx1 = fmaxf(mx1, z.y); }
                    mx0 *= -SC; mx1 *= -SC;
                    float l[4] = {0, 0, 0, 0};
                    uint32_t p[10];
#pragma unroll
                    for (int n = 0; n < 5; n++) {
                        const float e0 = ex2(fmaf(s[n][0], SC, mx0)), e1 = ex2(fmaf(s[n][1], SC, mx0));
                        const float e2 = ex2(fmaf(s[n][2], SC, mx1)), e3 = ex2(fmaf(s[n][3], SC, mx1));
                        p[2 * n] = pk(e0, e1); p[2 * n + 1] = pk(e2, e3);
                        mma8(l, p[2 * n], p[2 * n + 1], 0x3f803f80);
                    }
#pragma unroll
                    for (int m = 0; m < 3; m++) vm[m] = lds64(sb + O_VM + (3 * r + m) * 512 + l16 + L * 8);
                    sched_fence(gridDim.y, 5);
                    const float l0 = rcp(l[0]), l1 = rcp(l[2]);
                    float o[6][4];
#pragma unroll
                    for (int m = 0; m < 6; m++) o[m][0] = o[m][1] = o[m][2] = o[m][3] = 0.f;
#pragma unroll
                    for (int m = 0; m < 3; m++) { mma8(o[2 * m], p[0], p[1], v0[m].x); mma8(o[2 * m + 1], p[0], p[1], v0[m].y); }
#pragma unroll
                    for (int m = 0; m < 3; m++) { mma8(o[2 * m], p[2], p[3], v0[m].z); mma8(o[2 * m + 1], p[2], p[3], v0[m].w); v1[m] = lds128(vad + m * 2048 + 512); }
#pragma unroll
                    for (int m = 0; m < 3; m++) { mma8(o[2 * m], p[8], p[9], vm[m].x); mma8(o[2 * m + 1], p[8], p[9], vm[m].y); }
#pragma unroll
                    for (int m = 0; m < 3; m++) { mma8(o[2 * m], p[4], p[5], v1[m].x); mma8(o[2 * m + 1], p[4], p[5], v1[m].y); }
#pragma unroll
                    for (int m = 0; m < 3; m++) { mma8(o[2 * m], p[6], p[7], v1[m].z); mma8(o[2 * m + 1], p[6], p[7], v1[m].w); }
#pragma unroll
                    for (int m = 0; m < 3; m++)
                        sts128(sb + O_OS + warp * 512 + m * 2048 + l16, (pk(o[2 * m][0] * l0, o[2 * m][1] * l0) & ~1u) | otag, pk(o[2 * m][2] * l1, o[2 * m][3] * l1),
                               pk(o[2 * m + 1][0] * l0, o[2 * m + 1][1] * l0), pk(o[2 * m + 1][2] * l1, o[2 * m + 1][3] * l1));
                    TR(4);
                }
            }
            if (t + 1 >= NT) break;
            {
                float d[32];
                if (warp >= 4) mbar_wait(bar + B_X, (t + 1) & 1);
                if (NGAP == 0 || warp < 4) bar_sync(7, 384); else if (t >= 0) bar_sync(11, 256);
                wg_fence();
                TR(6);
#pragma unroll
                for (int kk = 0; kk < 36; kk++) {
                    if (NGAP > 0 && kk == NGAP) asm volatile("{.reg .pred p; setp.ge.u32 p, %0, 4; @p bar.sync 7, 384;}" :: "r"(warp) : "memory");
                    const uint64_t db = mkdesc(hlo + ((kk >> 2) * 8192 + (kk & 3) * 32) / 16, DESC_HI);
                    if (IS_SS(kk)) wgmma_ss64(d, mkdesc(wlo + (kk / SSP) * 256, 16), db, 1);
                    else wgmma_rs64(d, a[AI(kk)], a[AI(kk) + 1], a[AI(kk) + 2], a[AI(kk) + 3], db, kk > 0);
                }
                wg_commit();
                TR(5);
                mbar_wait(bar + B_WIN, (t + 1) & 1);
                wg_wait<0>();
                TR(7);
                mbar_arrive_all3(bar + B_XFREE, l16 >> 4);
                uint32_t p[16];
#pragma unroll
                for (int u = 0; u < 16; u++) p[u] = pk(d[2 * u], d[2 * u + 1]);
                if (kind == 2) {
#pragma unroll
                    for (int u = 0; u < 4; u++) sts128(adX + u * 512, p[4 * u], p[4 * u + 1], p[4 * u + 2], p[4 * u + 3]);
                } else {
#pragma unroll
                    for (int u = 0; u < 4; u++) stsm4t(adX + u * 512, p[4 * u], p[4 * u + 1], p[4 * u + 2], p[4 * u + 3]);
                }
                __syncwarp();
                asm volatile("{.reg .pred p; setp.eq.u32 p, %1, 0; @p mbarrier.arrive.shared.b64 _, [%0];}" :: "r"(bar + B_EP), "r"(l16) : "memory");
                TR(8);
            }
        }
        if (warp < 4) bar_arrive(7, 160); else if (NGAP > 0) bar_sync(11, 256);
        cluster_sync();
    } else {
        asm volatile("setmaxnreg.dec.sync.aligned.u32 " RW ";");
        const int w = warp - 8, t2 = tid - 256;
        if (t2 == 0) {
            mbar_init(bar + B_X, 1); mbar_init(bar + B_XFREE, 24); mbar_init(bar + B_WIN, 3);
            mbar_init(bar + B_VX, 1); mbar_init(bar + B_SM, 1); mbar_init(bar + B_ST, 1); mbar_init(bar + B_EP, 8);
            asm volatile("fence.mbarrier_init.release.cluster;" ::: "memory");
        }
        char* const ex = reinterpret_cast<char*>((reinterpret_cast<uintptr_t>(g_ex) + 0x1fffff) & ~(uintptr_t)0x1fffff);
        char* rbase = ex; uint32_t side = 0;
        {
            uint32_t m0[5][4];
#pragma unroll
            for (int i = 0; i < 5; i++) {
                const unsigned short* m = reinterpret_cast<const unsigned short*>(mem0) + min(i * 128 + t2, DM - 1);
#pragma unroll
                for (int j = 0; j < 4; j++) m0[i][j] = m[2 * j * DM] | (m[(2 * j + 1) * DM] << 16);
            }
            if (w == 3) { bar_sync(15, 288); cnt_add(g_cnt + C_W * 8, lane); TR1(1); }
            if (t2 >= 96 && t2 < 99 && PFON) prefetch_l2((t2 == 96 ? Wq : t2 == 97 ? Wk : Wv) + b * (6 * 4096), 6 * 8192);
            delay_until(t_start, DLYW);
#pragma unroll 4
            for (int i = t2; i < 128 * 24; i += 128) {
                const int e = (i >> 3) & 127, G = i >> 10, q = i & 7;
                cp16(sb + O_WO + G * 16384 + e * 128 + ((q ^ (e & 7) ^ ((h >> 1) & 1)) << 4), Wo + (size_t)(h * 128 + e) * DM + G * 192 + r * 64 + q * 8);
            }
            bar_sync(9, 384);
#pragma unroll
            for (int i = 0; i < 5; i++) {
                const int k = min(i * 128 + t2, DM - 1);
                const uint32_t ad = sb + O_MB + (k >> 3) * 256 + (k & 7) * 16;
                sts128(ad, m0[i][0], m0[i][1], m0[i][2], m0[i][3]); sts128(ad + 128, m0[i][0], m0[i][1], m0[i][2], m0[i][3]);
            }
            fence_async_smem();
        }
        auto arm = [&]() {
            const uint32_t ln = l16 >> 4;
            mbar_expect(bar + B_VX + (ln & 3) * 8, ln == 0 ? nv_remote * 2048 : ln == 1 ? nv_remote * 512 + 2560 : 8192, ln < 3);
        };
        if (w == 3) arm();
        cluster_sync();
        TR1(3);
        const int L = w >> 1, hf = w & 1;
        const uint32_t rd = hf ? roff1 : roff0;
        const uint32_t rzero = gridDim.y + 100;
#define WOAD (sb + O_WO + ((l16 & 0x100) << 2) + ((l16 & 0x70) << 3) + (((w * 32) | ((l16 >> 3) & 16)) ^ (l16 & 0x70)))

        auto fetch_tile = [&](int u) {
            const bool a0 = u < NSEG, a1 = u >= LAG;
            mbar_expect(bar + B_X, ((int)a0 + (int)a1) * 36864, l16 == 0);
            const uint32_t off = r * 24576 + (l16 << 9) + (a0 ? 0 : 4096);
            asm volatile("{.reg .pred p; setp.lt.u32 p, %5, %6;\n"
                "@p cp.async.bulk.shared::cluster.global.mbarrier::complete_tx::bytes.multicast::cluster [%0], [%1], %4, [%2], %3;}"
                :: "r"(sb + O_H + off), "l"(reinterpret_cast<const char*>(g_xt + u * 4608) + off), "r"(bar + B_X), "h"((uint16_t)7),
                   "r"(a0 && a1 ? 24576 : 4096), "r"(l16), "r"(a0 && a1 ? 16 : 48) : "memory");
        };
        auto store_o = [&](int u) {
            asm volatile("{.reg .pred p; setp.eq.u32 p, %3, 0;\n"
                "@p cp.async.bulk.global.shared::cta.bulk_group [%0], [%1], %2;\n cp.async.bulk.commit_group;}"
                :: "l"(g_o + ((u & (RING - 1)) * 256 + h * 8 + 3 * r) * 128), "r"(sb + O_OS), "r"(nq * 2048), "r"(l16) : "memory");
            cnt_hint(g_cnt + (C_O + u * 8 + (h >> 2)) * 8, l16);
            TRG(u, 2);
        };
        bar_arrive(7, 384);
        if (w < 3) {
            bar_arrive(1 + w, 160); bar_arrive(12 + w, 160); if (w == 0 && XST < 3) bar_arrive(8, 64);
            if (w < 2) {
                unsigned* pp = reinterpret_cast<unsigned*>(ex + inbox_off(b) + 16384 + w * 4096 + 2048);
                uint32_t best = ~0u, v = 0;
                if (lane == 0) {
#pragma unroll 1
                    for (int i = 0; i < 6; i++) {
                        const uint32_t c0 = clk();
                        v = atomicAdd(pp + (v >> 31), 0);
                        asm volatile("" :: "r"(v) : "memory");
                        sts32(bar + 80, v);
                        best = min(best, clk() - c0);
                    }
                    sts32(bar + 72 + w * 4, best);
                }
            }
            bar_sync(15, 96);
            const uint32_t xs = PLACE ? lds32(bar + 76) < lds32(bar + 72) : 0, ep = EP;
            side = PLACE ? xs ^ page_par(inbox_off(b)) : 0;
            rbase = ex + inbox_off(b) + xs * 4096;
            const uint32_t inv = (ep * (NT - 1)) & 1;
#pragma unroll
            for (int i = 0; i < 4; i++) stg128(rbase + (w == 2 ? 16384 : w * 2048) + i * 512 + lane * 16, inv, 0, 0, 0);
            __threadfence();
            bar_sync(15, 96);
            if (t2 == 0) stg_word(g_side + b, (ep + 1) * 2 + xs, true);
            TR1(4);
        } else {
            mbar_arrive_all3(bar + B_WIN, l16 >> 4);
            cnt_wait(g_cnt + C_X * 8, 64 * (EP + 1)); fence_async_global();
            TRG(0, 0);
            fetch_tile(0);
            TRG(0, 1);
        }
        cp_wait_all();
        bar_sync(6, 128);
        uint32_t poff;
        {
            const int rb = r * 32 + w * 8 + (lane >> 2);
            const uint32_t want = EP + 1;
            uint32_t v;
            for (int n = 0; __any_sync(~0u, ((v = ldg_word(g_side + rb)) >> 1) != want); n++) fault_if(n > POLL_LIMIT, n);
            __threadfence();
            poff = inbox_off(rb) + (v & 1) * 4096 + h * 64 + (lane & 3) * 16;
        }
        side = __shfl_sync(~0u, side, 0);
        const uint32_t roff = __shfl_sync(~0u, (uint32_t)(rbase - ex), 0) + (w == 2 ? 16384 : (w & 1) * 2048);
        bool late = true;
        uint4 a0[8];
#pragma unroll
        for (int kk = 0; kk < 8; kk++) a0[kk] = ldsm4t(WOAD + kk * 2048);
#pragma unroll 1
        for (int t = 0;; t++) {
            TR_ON(t);
            OPQ();
            mbar_wait(bar + B_EP, t & 1);
            if (w == 3) {
                fence_async_smem();
                const uint32_t ad = sb + O_VX + r * 4096;
                asm volatile("{.reg .pred p; setp.eq.u32 p, %5, 0;\n"
                    "@p cp.async.bulk.shared::cluster.shared::cta.mbarrier::complete_tx::bytes [%0], [%2], %6, [%3];\n"
                    "@p cp.async.bulk.shared::cluster.shared::cta.mbarrier::complete_tx::bytes [%1], [%2], %6, [%4];}"
                    :: "r"(ad + roff0), "r"(ad + roff1), "r"(ad), "r"(bar + B_VX + roff0), "r"(bar + B_VX + roff1), "r"(l16), "r"(16384 - 4096 * nq) : "memory");
                if (XST < 3) bar_sync(8, 64);
                TR(6);
                if (t > 0) store_o(t - 1);
                if (late) { cnt_wait(g_cnt + (C_X + t + 1) * 8, 64 * (EP + 1)); fence_async_global(); }
                TRG(t + 1, 0);
                mbar_wait(bar + B_XFREE, t & 1);
                if (t + 1 < NT) { fetch_tile(t + 1); TRG(t + 1, 1); }
                TR(7);
            }
            uint4 kx[3][2], vx[4][2];
            const uint32_t lp = LSWAP;
#pragma unroll
            for (int m = 0; m < 3; m++) {
                kx[m][0] = ldsm4(sb + O_KX + m * 2048 + L * 1024 + lp);
                kx[m][1] = ldsm4(sb + O_KX + m * 2048 + L * 1024 + 512 + lp);
            }
            if (w == 3) asm volatile("cp.async.bulk.wait_group.read 0;" ::: "memory");
            mbar_wait(bar + B_VX, t & 1);
            TR(0);
            bar_sync(4, 384);
            float s0[4] = {0, 0, 0, 0}, s1[4] = {0, 0, 0, 0}, sm[4] = {0, 0, 0, 0};
            {
                const uint4 q01 = ldsm4(sb + O_QM + L * 256 + l16 + (l16 & 256));
                const uint2 q2 = ldsm2(sb + O_QM + 1024 + L * 256 + l16);
                uint4 km_[3];
#pragma unroll
                for (int m = 0; m < 3; m++) km_[m] = ldsm4(sb + O_KM + m * 512 + (lp ^ (L << 8)));
                bar_arrive(5, 256);
                mma16(s0, kx[0][0].x, kx[0][0].y, kx[0][0].z, kx[0][0].w, q01.x, q01.y);
                mma16(s1, kx[0][1].x, kx[0][1].y, kx[0][1].z, kx[0][1].w, q01.x, q01.y);
                mma16(sm, km_[0].x, km_[0].y, km_[0].z, km_[0].w, q01.x, q01.y);
                mma16(s0, kx[1][0].x, kx[1][0].y, kx[1][0].z, kx[1][0].w, q01.z, q01.w);
                mma16(s1, kx[1][1].x, kx[1][1].y, kx[1][1].z, kx[1][1].w, q01.z, q01.w);
                mma16(sm, km_[1].x, km_[1].y, km_[1].z, km_[1].w, q01.z, q01.w);
                mma16(s0, kx[2][0].x, kx[2][0].y, kx[2][0].z, kx[2][0].w, q2.x, q2.y);
                mma16(s1, kx[2][1].x, kx[2][1].y, kx[2][1].z, kx[2][1].w, q2.x, q2.y);
                mma16(sm, km_[2].x, km_[2].y, km_[2].z, km_[2].w, q2.x, q2.y);
                const uint32_t ad = sb + O_SM + (1 - hf) * 1280 + L * 640 + rd;
                sta128(ad + l16, pk(s0[0], s0[1]), pk(s0[2], s0[3]), pk(s1[0], s1[1]), pk(s1[2], s1[3]), bar + B_SM + rd);
                sta32(ad + 512 + (l16 >> 2), pk(sm[0], sm[1]), bar + B_SM + rd);
            }
            TR(1);
            if (t + 1 == NT) break;
#pragma unroll
            for (int m = 0; m < 8; m++) vx[m >> 1][m & 1] = lds128(sb + O_VX + (hf * 4 + (m >> 1)) * 2048 + L * 1024 + (m & 1) * 512 + l16);
            const uint32_t tag = (t + EP * (NT - 1) + 1) & 1;
            uint32_t ident = IDENT;
            asm volatile("" : "+r"(ident));
            mbar_wait(bar + B_SM, t & 1);
            TR(2);
            {
                const uint32_t ad = sb + O_SM + L * 640;
                const uint4 u = lds128(ad + l16), v = lds128(ad + 1280 + l16);
                const uint32_t x = lds32(ad + 512 + (l16 >> 2)), y = lds32(ad + 1280 + 512 + (l16 >> 2));
                mma8(s0, u.x, u.y, ident); mma8(s1, u.z, u.w, ident); mma8(s0, v.x, v.y, ident); mma8(s1, v.z, v.w, ident);
                sm[0] += bf_lo(x) + bf_lo(y); sm[1] += bf_hi(x) + bf_hi(y);
            }
            uint2 vm[4];
#pragma unroll
            for (int m = 0; m < 4; m++) vm[m] = lds64(sb + O_VM + (hf * 4 + m) * 512 + l16 + L * 8);
            float mx0 = fmaxf(fmaxf(fmaxf(s0[0], s0[2]), fmaxf(s1[0], s1[2])), sm[0]);
            float mx1 = fmaxf(fmaxf(fmaxf(s0[1], s0[3]), fmaxf(s1[1], s1[3])), sm[1]);
#pragma unroll
            for (int o = 4; o < 32; o <<= 1) { mx0 = fmaxf(mx0, __shfl_xor_sync(~0u, mx0, o)); mx1 = fmaxf(mx1, __shfl_xor_sync(~0u, mx1, o)); }
            mx0 *= -SC; mx1 *= -SC;
            s0[0] = ex2(fmaf(s0[0], SC, mx0)); s0[1] = ex2(fmaf(s0[1], SC, mx1));
            s0[2] = ex2(fmaf(s0[2], SC, mx0)); s0[3] = ex2(fmaf(s0[3], SC, mx1));
            const uint32_t pb0 = movm(pk(s0[0], s0[1])), pb1 = movm(pk(s0[2], s0[3]));
            s1[0] = ex2(fmaf(s1[0], SC, mx0)); s1[1] = ex2(fmaf(s1[1], SC, mx1));
            s1[2] = ex2(fmaf(s1[2], SC, mx0)); s1[3] = ex2(fmaf(s1[3], SC, mx1));
            const uint32_t pb2 = movm(pk(s1[0], s1[1])), pb3 = movm(pk(s1[2], s1[3]));
            sm[0] = ex2(fmaf(sm[0], SC, mx0)); sm[1] = ex2(fmaf(sm[1], SC, mx1));
            const uint32_t pm = movm(pk(sm[0], sm[1]));
            float o[4][4], l[4] = {0, 0, 0, 0};
            const uint32_t one = 0x3f803f80;
            mma8(l, one, one, pb0); mma8(l, one, one, pb1);
#pragma unroll
            for (int m = 0; m < 4; m++) { o[m][0] = o[m][1] = o[m][2] = o[m][3] = 0.f; mma16(o[m], vx[m][0].x, vx[m][0].y, vx[m][0].z, vx[m][0].w, pb0, pb1); }
            mma8(l, one, one, pb2); mma8(l, one, one, pb3);
#pragma unroll
            for (int m = 0; m < 4; m++) mma16(o[m], vx[m][1].x, vx[m][1].y, vx[m][1].z, vx[m][1].w, pb2, pb3);
            mma8(l, one, one, pm);
#pragma unroll
            for (int m = 0; m < 4; m++) mma8(o[m], vm[m].x, vm[m].y, pm);
            const float l0 = rcp(l[0]), l1 = rcp(l[1]);
#pragma unroll
            for (int m = 0; m < 4; m += 2)
                stsm4t(sb + O_OX + (hf * 4 + m) * 512 + (L ^ ((h >> 2) & 1)) * 256   + ((l16 & 0x100) << 1) + (l16 & 0xf0),
                       pk(o[m][0] * l0, o[m][1] * l1), pk(o[m][2] * l0, o[m][3] * l1), pk(o[m + 1][0] * l0, o[m + 1][1] * l1), pk(o[m + 1][2] * l0, o[m + 1][3] * l1));
            TR(3);
            char* const pdst = ex + poff;
            bar_sync(6, 128);
            {
                uint4 bo[8], a1[8], z;
                const uint32_t wad = WOAD;
#pragma unroll
                for (int kk = 0; kk < 8; kk++) bo[kk] = ldsm4(sb + O_OX + kk * 512 + l16);
#pragma unroll
                for (int G = 0; G < 3; G++) {
                    float e[4][4];
#pragma unroll
                    for (int q = 0; q < 4; q++) e[q][0] = e[q][1] = e[q][2] = e[q][3] = 0.f;
#pragma unroll
                    for (int kk = 0; kk < 8; kk++) {
                        const uint4 f = G == 0 ? a0[kk] : a1[kk];
                        mma16(e[(kk & 1) * 2], f.x, f.y, f.z, f.w, bo[kk].x, bo[kk].y);
                        mma16(e[(kk & 1) * 2 + 1], f.x, f.y, f.z, f.w, bo[kk].z, bo[kk].w);
                        if (G == 1) a1[kk] = ldsm4t(wad + 32768 + kk * 2048);
                        if (G == 0 && kk == FK) {
                            sched_fence(rzero, 2);
#pragma unroll
                            for (int j = 0; j < 8; j++) a1[j] = ldsm4t(wad + 16384 + j * 2048);
                        }
                    }
                    if (G > 0) asm volatile("{.reg .pred p; setp.eq.u32 p, %5, 0; @p st.shared.v4.u32 [%0], {%1,%2,%3,%4};}" :: "r"(__float_as_uint(e[0][0])), "r"(z.x), "r"(z.y), "r"(z.z), "r"(z.w), "r"(rzero));
                    z = make_uint4((pk(e[0][0] + e[2][0], e[0][1] + e[2][1]) & ~1u) | tag, pk(e[0][2] + e[2][2], e[0][3] + e[2][3]),
                                   pk(e[1][0] + e[3][0], e[1][1] + e[3][1]), pk(e[1][2] + e[3][2], e[1][3] + e[3][3]));
                    stg_pkt(pdst + (G == 2 ? 16384 : G * 2048), z.x, z.y, z.z, z.w);
                    if (G == 0) { TR(9); TRD(t, 0); }
                    if (G < 2) sched_fence(rzero, 3 + G);
                }
            }
            TR(4);
            if (w < 3) {
                bar_arrive(7, 384);
                OPQ();
                const uint32_t tagm = tag;
                uint32_t m0v = 0;
                if (t + 1 <= LAG) {
                    const unsigned short* m = reinterpret_cast<const unsigned short*>(mem0) + ((l16 >> 3) & 6) * DM + 192 * w + 16 * (b >> 3) + (b & 7) + ((l16 >> 4) & 8);
                    m0v = m[0] | (m[DM] << 16);
                }
                const char* const rsrc = ex + roff + l16;
                uint4 v[4];
                delay(DLY1);
#pragma unroll
                for (int i = 0; i < 4; i++) v[i] = ldg_pkt(rsrc + i * 512);
                for (int n = 0; __any_sync(~0u, lop_bad(lop_bad(0, v[0].x, v[1].x, tagm), v[2].x, v[3].x, tagm) & 1); n++) {
#pragma unroll
                    for (int i = 0; i < 4; i++) v[i] = ldg_pkt(rsrc + i * 512);
                    fault_if(n > POLL_LIMIT, n);
                }
                TR(5); TRD(t, 1);
                float s[8];
                s[4] = (bf_lo(v[0].z) + bf_lo(v[1].z)) + (bf_lo(v[2].z) + bf_lo(v[3].z)); s[5] = (bf_hi(v[0].z) + bf_hi(v[1].z)) + (bf_hi(v[2].z) + bf_hi(v[3].z));
                s[6] = (bf_lo(v[0].w) + bf_lo(v[1].w)) + (bf_lo(v[2].w) + bf_lo(v[3].w)); s[7] = (bf_hi(v[0].w) + bf_hi(v[1].w)) + (bf_hi(v[2].w) + bf_hi(v[3].w));
                s[2] = (bf_lo(v[0].y) + bf_lo(v[1].y)) + (bf_lo(v[2].y) + bf_lo(v[3].y)); s[3] = (bf_hi(v[0].y) + bf_hi(v[1].y)) + (bf_hi(v[2].y) + bf_hi(v[3].y));
                s[0] = (bf_lo(v[0].x) + bf_lo(v[1].x)) + (bf_lo(v[2].x) + bf_lo(v[3].x)); s[1] = (bf_hi(v[0].x) + bf_hi(v[1].x)) + (bf_hi(v[2].x) + bf_hi(v[3].x));
#pragma unroll
                for (int j = 0; j < 4; j++) s[j] += __shfl_xor_sync(~0u, s[j + 4], 16);
#pragma unroll
                for (int j = 0; j < 2; j++) s[j] += __shfl_xor_sync(~0u, s[j + 2], 8);
#pragma unroll
                for (int j = 0; j < 2; j++) s[j] += __shfl_xor_sync(~0u, s[j], 4);
                char* const mem_w = ex + mem_off(w, 0);
                uint32_t res = t + 1 <= LAG && l16 >= 256 ? m0v : pk(s[0], s[1]);
                if ((l16 & 48) == 0) res = (res & ~1u) | tag;
                stg_word(mem_w + (mem_off(0, b >> 3) - mem_off(0, 0)) + (b & 7) * 16 + (((l16 & 64) << 6) + ((l16 & 128) << 1) + ((l16 & 256) >> 1) + ((l16 >> 2) & 12)), res, true);
                TR(6); TRD(t, 2);
                delay(DLY2);
                const char* src = mem_w + (side ^ page_par(0x180000)) * 4096 + l16;
                const uint32_t gdst = sb + O_MB + w * 6144 + l16;
                uint4 x[12];
#pragma unroll
                for (int i = 0; i < 12; i++) x[i] = ldg_pkt(src + (mem_off(0, i) - mem_off(0, 0)));
                for (int n = 0;; n++) {
                    uint32_t bad = 0;
#pragma unroll
                    for (int i = 0; i < 12; i += 2) bad = lop_bad(bad, x[i].x, x[i + 1].x, tagm);
                    if (!__any_sync(~0u, bad & 1)) break;
#pragma unroll
                    for (int i = 0; i < 12; i++) ldg_pkt_retry(x[i], src + (mem_off(0, i) - mem_off(0, 0)), tagm);
                    fault_if(n > POLL_LIMIT, n);
                }
#pragma unroll
                for (int i = 0; i < 12; i++) sts128(gdst + i * 512, x[i].x, x[i].y, x[i].z, x[i].w);
                TR(7); TRD(t, 3);
                fence_async_smem();
                bar_arrive(12 + w, 160);
                bar_arrive(1 + w, 160);
                if (w == XST) bar_arrive(8, 64);
                TR(8);
            } else {
                bar_sync(7, 384);
                fence_async_smem();
                arm();
                __syncwarp();
                mbar_arrive_all3(bar + B_WIN, l16 >> 4);
                late = t + 2 < NT && cnt_poll(g_cnt + (C_X + t + 2) * 8, 64 * (EP + 1), bar + B_EP, (t + 1) & 1);
                fence_async_global();
                TR(5);
            }
        }
        if (w == 3) { bar_sync(7, 160); fence_async_smem(); store_o(NT - 1); asm volatile("cp.async.bulk.wait_group 0;" ::: "memory"); }
        cluster_sync();
    }
    TR_DUMP(b);
}

#define VG 12
#define HB 3
#define HA 2
#define HW 0
namespace ka {
constexpr int O_WA = 196608;
constexpr int A_KB = 21504;
constexpr int O_RING = 194560;
constexpr int O_BAR = 230400;
constexpr int SMEM = O_BAR + 256 + 1024;
constexpr float SC = 0.23570226039551584f * 1.4426950408889634f;
}

template <int NP, int KB = 4096>
DEVI void row_task(const uint4* res, const uint4* part, uint4* xout, char* img, int pos, int lane, uint32_t tag) {
    const bool on = lane < 24;
    const int ln = on ? lane : 0;
    uint4 rv[3], pv[NP > 0 ? NP * 3 : 1];
#pragma unroll
    for (int i = 0; i < 3; i++) rv[i] = ldg128(res + i * 24 + ln);
#pragma unroll
    for (int i = 0; i < NP * 3; i++) pv[i] = ldg_pkt(part + i * 24 + ln);
    if (NP > 0) validate<NP * 3>(pv, part + ln, 384, tag);
#pragma unroll
    for (int q = 0; q < NP * 3 / 2; q++) {
        const uint4 y = pv[q + NP * 3 / 2];
        pv[q] = make_uint4(add2(pv[q].x, y.x), add2(pv[q].y, y.y), add2(pv[q].z, y.z), add2(pv[q].w, y.w));
    }
    float x[24];
#pragma unroll
    for (int i = 0; i < 3; i++) {
        x[8 * i] = bf_lo(rv[i].x); x[8 * i + 1] = bf_hi(rv[i].x); x[8 * i + 2] = bf_lo(rv[i].y); x[8 * i + 3] = bf_hi(rv[i].y);
        x[8 * i + 4] = bf_lo(rv[i].z); x[8 * i + 5] = bf_hi(rv[i].z); x[8 * i + 6] = bf_lo(rv[i].w); x[8 * i + 7] = bf_hi(rv[i].w);
    }
    if (NP > 0) {
#pragma unroll
        for (int q = 0; q < NP * 3 / 2; q++) {
            const int i = q % 3;
            x[8 * i] += bf_lo(pv[q].x); x[8 * i + 1] += bf_hi(pv[q].x); x[8 * i + 2] += bf_lo(pv[q].y); x[8 * i + 3] += bf_hi(pv[q].y);
            x[8 * i + 4] += bf_lo(pv[q].z); x[8 * i + 5] += bf_hi(pv[q].z); x[8 * i + 6] += bf_lo(pv[q].w); x[8 * i + 7] += bf_hi(pv[q].w);
        }
#pragma unroll
        for (int i = 0; i < 3; i++) {
            uint32_t w[4];
#pragma unroll
            for (int j = 0; j < 4; j++) { w[j] = pk(x[8 * i + 2 * j], x[8 * i + 2 * j + 1]); x[8 * i + 2 * j] = bf_lo(w[j]); x[8 * i + 2 * j + 1] = bf_hi(w[j]); }
            stg128p(xout + i * 24 + ln, w[0], w[1], w[2], w[3], on);
        }
    }
    if (img) {
        float s = 0.f;
#pragma unroll
        for (int j = 0; j < 24; j++) s += x[j];
        if (!on) s = 0.f;
#pragma unroll
        for (int o = 1; o < 32; o <<= 1) s += __shfl_xor_sync(~0u, s, o);
        const float mean = s * (1.f / DM);
        float v = 0.f;
#pragma unroll
        for (int j = 0; j < 24; j++) { x[j] -= mean; v = fmaf(x[j], x[j], v); }
        if (!on) v = 0.f;
#pragma unroll
        for (int o = 1; o < 32; o <<= 1) v += __shfl_xor_sync(~0u, v, o);
        const float rs = rsqrtf(v * (1.f / DM) + 1e-5f);
        char* dst = img + (ln >> 3) * KB + pos * 128 + (((ln ^ pos) & 7) << 4);
#pragma unroll
        for (int i = 0; i < 3; i++)
            stg128p(dst + i * (3 * KB), pk(x[8 * i] * rs, x[8 * i + 1] * rs), pk(x[8 * i + 2] * rs, x[8 * i + 3] * rs),
                    pk(x[8 * i + 4] * rs, x[8 * i + 5] * rs), pk(x[8 * i + 6] * rs, x[8 * i + 7] * rs), on);
    }
}

DEVI void rows_a(const uint4* xin, int f, int i, int lane, uint32_t ep, int warp) {
    for (int u = 0; u < LAG; u++) cnt_hint(g_cnt + (C_X + u + (f ? 0 : NSEG)) * 8, lane);
#pragma unroll 1
    for (int seg = 0; seg < NSEG; seg++) {
        const int j = seg + f * LAGA, u = seg + f * LAG, row = seg * 32 + i;
        hint_wait(g_cnt + (C_WA + j * 4 + f * 2 + (i & 1)) * 8, 24 * (ep + 1));
        TRG(u, 0);
        row_task<4, 8192>((f ? g_x + 2048 * 72 : xin) + row * 72, g_pa + ((j & (RING - 1)) * 64 + f * 32 + i) * 288,
                    g_x + (f * 4096 + row) * 72, reinterpret_cast<char*>(g_xt + u * 4608 + f * 256), i, lane, ring_tag<NTA>(j, ep));
        TRG(u, 1);
        cnt_add(g_cnt + (C_X + u) * 8, lane);
        TRG(u, 2);
    }
}

__global__ void __launch_bounds__(384, 1)
k_aux(const __nv_bfloat16* __restrict__ x0, const __nv_bfloat16* __restrict__ wqkv, const __nv_bfloat16* __restrict__ wo,
      const __nv_bfloat16* __restrict__ Wo, __nv_bfloat16* __restrict__ out) {
    using namespace ka;
    extern __shared__ unsigned char smem_raw[];
    const uint32_t sb = (smem_u32(smem_raw) + 1023) & ~1023u;
    const int tid = threadIdx.x, lane = tid & 31, warp = __shfl_sync(~0u, tid >> 5, 0), g = lane >> 2, c = lane & 3;
    const int b = blockIdx.x;
    const uint32_t bar = sb + O_BAR;
    const uint32_t ep = __shfl_sync(~0u, ldg32(&g_epoch), 0);

    TRG(79, 0);
    const uint4* xin = reinterpret_cast<const uint4*>(x0);
    if (warp >= 8 || b == 35) {
        asm volatile("setmaxnreg.dec.sync.aligned.u32 128;");
        const int rw = b < 24 ? (warp - 8) * 24 + b : b < 35 ? (warp - 8) * 11 + b - 24 : 96 + 2 * warp;
        if (b < 24 || b == 35) {
#pragma unroll 1
            for (int row = rw; row < 2048; row += (row & 1) ? 23 : 1) {
                if (lane == 0 && b == 35 && row < 2024) prefetch_l2(xin + (row + 24) * 72, 1152);
                row_task<0>(xin + row * 72, nullptr, nullptr, reinterpret_cast<char*>(g_xa + (row >> 5) * 4608), (row & 1) * 16 + ((row & 31) >> 1), lane, 0);
                if (b < 24) { cnt_add(g_cnt + (C_N0 + (row >> 5)) * 8, lane); break; }
                if (row & 1) cnt_add<2>(g_cnt + (C_N0 + (row >> 5)) * 8, lane);
            }
        }
        if (rw < 32) {
            const int f = b < 24, i = rw;
#pragma unroll 1
            for (int seg = 0; seg < NSEG; seg++) {
                const int u = seg + f * LAG, row = seg * 32 + i;
                hint_wait(g_cnt + (C_WB + u * 4 + f * 2 + (i >> 4)) * 8, 24 * (ep + 1));
                TRG(u, 0);
                row_task<8>(g_x + (f * 4096 + row) * 72, g_pb + ((u & (RING - 1)) * 64 + f * 32 + i) * 576,
                            f ? reinterpret_cast<uint4*>(out) + row * 72 : g_x + (2048 + row) * 72,
                            f ? nullptr : reinterpret_cast<char*>(g_xa + (seg + LAGA) * 4608 + 2304), (i & 1) * 16 + (i >> 1), lane, ring_tag(u, ep));
                TRG(u, 1);
                cnt_add(g_cnt + (C_RB + f * NSEG + seg) * 8, lane);
                TRG(u, 2);
            }
            if (f && rw == 31) {
                asm volatile("griddepcontrol.wait;" ::: "memory");
                if (lane == 0) g_epoch = ep + 1;
            }
        } else if (rw < 64 && b < 24) rows_a(xin, 0, rw - 32, lane, ep, warp);
        return;
    }

    if (b < 24) {
        if (warp >= 4) {
            const int kq = b / 6, nq = b % 6;
            uint4 v[17];
#pragma unroll
            for (int q = 0; q < 17; q++) {
                const int it = q * 4 + warp - 4, kr = (it / 3) * 8 + g, s = kq * 11 + (kr >> 4), a = s >> 2, j = s & 3, e = kr & 15;
                const int head = 3 * a + (j < 3 ? j : e >> 1), row = head * 18 + (j < 3 ? e : 16 + (e & 1));
                v[q] = make_uint4(0, 0, 0, 0);
                if (it < 66 && head < 32 && (j < 3 || e < 6)) v[q] = *reinterpret_cast<const uint4*>(wo + row * DM + nq * 96 + (it % 3) * 32 + c * 8);
            }
#pragma unroll
            for (int q = 0; q < 17; q++) {
                const int it = q * 4 + warp - 4;
                const uint32_t ad = sb + O_WA + (it % 3) * 4 * 2816 + (it / 3) * 128 + lane * 4;
                if (it < 66) { sts32(ad, v[q].x); sts32(ad + 2816, v[q].y); sts32(ad + 2 * 2816, v[q].z); sts32(ad + 3 * 2816, v[q].w); }
            }
        } else {
            const int kg = b / 3, ng = b % 3;
            delay(DLYB);
#pragma unroll 1
            for (int bt = 0; bt < 4; bt++) {
                uint4 v[24];
#pragma unroll
                for (int q = 0; q < 24; q++)
                    v[q] = *reinterpret_cast<const uint4*>(Wo + (size_t)(kg * 512 + (bt * 4 + q / 6) * 32 + warp * 8 + g) * DM + ng * 192 + (q % 6) * 32 + c * 8);
#pragma unroll
                for (int q = 0; q < 24; q++) {
                    const uint32_t ad = sb + (q % 6) * 4 * 8192 + ((bt * 4 + q / 6) * 4 + warp) * 128 + lane * 4;
                    sts32(ad, v[q].x); sts32(ad + 8192, v[q].y); sts32(ad + 2 * 8192, v[q].z); sts32(ad + 3 * 8192, v[q].w);
                }
            }
        }
        fence_async_smem();
        bar_sync(2 + (warp >> 2), 128);
    } else {
        for (int i = tid; i < 2048; i += 256) sts128(sb + O_RING + i * 16, 0, 0, 0, 0);
        if (tid < 17) mbar_init(bar + tid * 8, tid >= 4 && tid < 8 ? 4 : 1);
        fence_async_smem();
        bar_sync(1, 256);
    }
    TRG(79, 1);
    const int wq = warp & 3;

    if (warp < 4) {
        asm volatile("setmaxnreg.inc.sync.aligned.u32 256;");
        if (b < 24) {
            const int kg = b / 3, ng = b % 3;
            const uint32_t blo = ((sb >> 4) & 0x3fff) | (8u << 16);
            uint4 a[32];
            bool pre = false;
#pragma unroll 1
            for (int u = 0; u < NT; u++) {
                const uint32_t tag = ring_tag(u, ep);
                const uint4* src = g_o + (((u & (RING - 1)) * 256 + kg * 32) * 4 + wq) * 32 + lane;
                if (!pre) {
                    hint_wait(g_cnt + (C_O + u * 8 + kg) * 8, 12 * (ep + 1));
#pragma unroll
                    for (int i = 0; i < VG; i++) a[i] = ldg_pkt(src + i * 128);
                }
                TRG(u, 0);
                float d[96];
                validate<VG>(a, src, 2048, tag);
#pragma unroll
                for (int i = VG; i < 32; i++) a[i] = ldg_pkt(src + i * 128);
                wg_fence();
#pragma unroll
                for (int i = 0; i < 32; i++) {
                    if (i == VG) { validate<32 - VG>(a + VG, src + VG * 128, 2048, tag); wg_fence(); }
                    wgmma_rs192t(d, a[i].x, a[i].y, a[i].z, a[i].w, mkdesc(blo + i * 16, 512), i > 0);
                    if (i == 23 || i == 31) wg_commit();
                }
                wg_wait<1>();
                pre = u + 1 < NT && __all_sync(~0u, ldg_word(g_cnt + (C_O + (u + 1) * 8 + kg) * 8) >= 12 * (ep + 1));
                if (pre) {
                    const uint4* nx = g_o + ((((u + 1) & (RING - 1)) * 256 + kg * 32) * 4 + wq) * 32 + lane;
#pragma unroll
                    for (int i = 0; i < VG; i++) a[i] = ldg_pkt(nx + i * 128);
                }
                wg_wait<0>();
                TRG(u, 1);
                uint4* dst = g_pb + (((u & (RING - 1)) * 64 + wq * 16 + g) * 8 + kg) * 72 + ng * 24 + c;
#pragma unroll
                for (int m = 0; m < 6; m++) {
                    if (m == HB) cnt_hint(g_cnt + (C_WB + u * 4 + wq) * 8, lane);
                    stg128(dst + 4 * m, (pk(d[16 * m], d[16 * m + 1]) & ~1u) | tag, pk(d[16 * m + 4], d[16 * m + 5]), pk(d[16 * m + 8], d[16 * m + 9]), pk(d[16 * m + 12], d[16 * m + 13]));
                    stg128(dst + 4 * m + 8 * 576, (pk(d[16 * m + 2], d[16 * m + 3]) & ~1u) | tag, pk(d[16 * m + 6], d[16 * m + 7]), pk(d[16 * m + 10], d[16 * m + 11]), pk(d[16 * m + 14], d[16 * m + 15]));
                }
                TRG(u, 3);
            }
        } else {
            const int a = b - 24, f = wq >> 1;
            const uint32_t blo = ((sb >> 4) & 0x3fff) | (8u << 16), alo = (((sb + O_RING) >> 4) & 0x3fff) | (1u << 16);
            const bool m0 = 2 * c <= g, m1 = 2 * c + 1 <= g;
            const uint32_t M = (m0 ? 0xffffu : 0u) | (m1 ? 0xffff0000u : 0u);
            uint32_t kh[7], vh[7];
#pragma unroll
            for (int i = 0; i < 7; i++) kh[i] = vh[i] = 0;
            int it = 0;
#pragma unroll 1
            for (int u = 0; u < NTA; u++) {
                float d[84];
#pragma unroll 1
                for (int kb = 0; kb < 9; kb++, it++) {
                    mbar_wait(bar + (it & 3) * 8, (it >> 2) & 1);
                    if (u == 0) mbar_wait(bar + 64 + kb * 8, 0);
                    if (kb == 0) TRG(u, 0);
                    wg_fence();
#pragma unroll
                    for (int q = 0; q < 4; q++)
                        wgmma_ss168t(d, mkdesc(alo + (it & 3) * 512 + q * 2, km::DESC_HI), mkdesc(blo + kb * (A_KB >> 4) + q * 16, 64), kb + q > 0);
                    wg_commit();
                    wg_wait<1>();
                    mbar_arrive(bar + 32 + ((it - 1) & 3) * 8, lane == 0 && kb > 0);
                }
                wg_wait<0>();
                mbar_arrive(bar + 32 + ((it - 1) & 3) * 8, lane == 0);
                TRG(u, 1);
                const bool first = u == f * LAGA;
                const uint32_t tag = ring_tag<NTA>(u, ep);
                const uint32_t qt0 = pk(d[72], d[73]), qt1 = pk(d[74], d[75]), kt0 = pk(d[76], d[77]), kt1 = pk(d[78], d[79]);
                const uint32_t vt0 = movm(pk(d[80], d[81])), vt1 = movm(pk(d[82], d[83]));
                float ot[4] = {0, 0, 0, 0};
                uint4* dst = g_oa + (((u & (RING - 1)) * 4 + wq) * 44 + a * 4) * 32 + lane;
#pragma unroll
                for (int h = 0; h < 3; h++) {
                    const float* q = d + 8 * h; const float* k = d + 24 + 8 * h; const float* v = d + 48 + 8 * h;
                    const uint32_t q0 = pk(q[0], q[1]), q1 = pk(q[2], q[3]), q2 = pk(q[4], q[5]), q3 = pk(q[6], q[7]);
                    const uint32_t k0 = pk(k[0], k[1]), k1 = pk(k[4], k[5]), k2 = pk(k[2], k[3]), k3 = pk(k[6], k[7]);
                    const uint32_t v0 = movm(pk(v[0], v[1])), v1 = movm(pk(v[2], v[3])), v2 = movm(pk(v[4], v[5])), v3 = movm(pk(v[6], v[7]));
                    const uint32_t t0 = c == h ? qt0 : 0, t1 = c == h ? qt1 : 0;
                    float sp[4] = {0, 0, 0, 0}, sl[4] = {0, 0, 0, 0}, sh[4] = {0, 0, 0, 0};
                    mma16(sp, q0, q1, q2, q3, kh[2 * h], kh[2 * h + 1]); mma16(sl, q0, q1, q2, q3, k0, k1); mma16(sh, q0, q1, q2, q3, k2, k3);
                    mma8(sp, t0, t1, kh[6]); mma8(sl, t0, t1, kt0); mma8(sh, t0, t1, kt1);
                    float x0_ = m0 ? sl[0] : first ? -INFINITY : sp[0], x1_ = m1 ? sl[1] : first ? -INFINITY : sp[1];
                    float y0_ = m0 ? sh[2] : sl[2], y1_ = m1 ? sh[3] : sl[3];
                    float mx = fmaxf(x0_, x1_), my = fmaxf(y0_, y1_);
#pragma unroll
                    for (int o = 1; o < 4; o <<= 1) { mx = fmaxf(mx, __shfl_xor_sync(~0u, mx, o)); my = fmaxf(my, __shfl_xor_sync(~0u, my, o)); }
                    mx *= -SC; my *= -SC;
                    x0_ = ex2(fmaf(x0_, SC, mx)); x1_ = ex2(fmaf(x1_, SC, mx)); y0_ = ex2(fmaf(y0_, SC, my)); y1_ = ex2(fmaf(y1_, SC, my));
                    float lx = x0_ + x1_, ly = y0_ + y1_;
#pragma unroll
                    for (int o = 1; o < 4; o <<= 1) { lx += __shfl_xor_sync(~0u, lx, o); ly += __shfl_xor_sync(~0u, ly, o); }
                    lx = rcp(lx); ly = rcp(ly);
                    const uint32_t px = pk(x0_ * lx, x1_ * lx), py = pk(y0_ * ly, y1_ * ly);
                    const uint32_t hm = (g >> 1) == h ? ~0u : 0u;
                    float o0[4] = {0, 0, 0, 0}, o1[4] = {0, 0, 0, 0};
                    mma16(o0, px & M, py & ~M, 0, py & M, v0, v1); mma16(o1, px & M, py & ~M, 0, py & M, v2, v3);
                    mma16(ot, px & M, py & ~M, 0, py & M, vt0 & hm, vt1 & hm);
                    mma8(o0, px & ~M, 0, vh[2 * h]); mma8(o1, px & ~M, 0, vh[2 * h + 1]); mma8(ot, px & ~M, 0, vh[6] & hm);
                    if (h == HA) cnt_hint(g_cnt + (C_A + u * 4 + wq) * 8, lane);
                    stg128(dst + h * 32, (pk(o0[0], o0[1]) & ~1u) | tag, pk(o0[2], o0[3]), pk(o1[0], o1[1]), pk(o1[2], o1[3]));
                    kh[2 * h] = k2; kh[2 * h + 1] = k3; vh[2 * h] = v1; vh[2 * h + 1] = v3;
                }
                kh[6] = kt1; vh[6] = vt1;
                stg128(dst + 96, (pk(ot[0], ot[1]) & ~1u) | tag, pk(ot[2], ot[3]), 0, 0);
                TRG(u, 2);
            }
        }
    } else {
        asm volatile("setmaxnreg.dec.sync.aligned.u32 120;");
        if (b < 24) {
            const int kq = b / 6, nq = b % 6;
            const uint32_t blo = (((sb + O_WA) >> 4) & 0x3fff) | (8u << 16);
#pragma unroll 1
            for (int u = 0; u < NTA; u++) {
                hint_wait(g_cnt + (C_A + u * 4 + wq) * 8, 11 * (ep + 1));
                const uint32_t tag = ring_tag<NTA>(u, ep);
                TRG(u, 0);
                const uint4* src = g_oa + (((u & (RING - 1)) * 4 + wq) * 44 + kq * 11) * 32 + lane;
                uint4 a[11];
                float d[48];
#pragma unroll
                for (int i = 0; i < 11; i++) a[i] = ldg_pkt(src + i * 32);
                validate<11>(a, src, 512, tag);
                wg_fence();
#pragma unroll
                for (int i = 0; i < 11; i++) wgmma_rs96t(d, a[i].x, a[i].y, a[i].z, a[i].w, mkdesc(blo + i * 16, 176), i > 0);
                wg_commit();
                wg_wait<0>();
                TRG(u, 1);
                uint4* dst = g_pa + (((u & (RING - 1)) * 64 + (wq >> 1) * 32 + 2 * g + (wq & 1)) * 4 + kq) * 72 + nq * 12 + c;
#pragma unroll
                for (int m = 0; m < 3; m++) {
                    if (m == HW) cnt_hint(g_cnt + (C_WA + u * 4 + wq) * 8, lane);
                    stg128(dst + 4 * m, (pk(d[16 * m], d[16 * m + 1]) & ~1u) | tag, pk(d[16 * m + 4], d[16 * m + 5]), pk(d[16 * m + 8], d[16 * m + 9]), pk(d[16 * m + 12], d[16 * m + 13]));
                    stg128(dst + 4 * m + 16 * 288, (pk(d[16 * m + 2], d[16 * m + 3]) & ~1u) | tag, pk(d[16 * m + 6], d[16 * m + 7]), pk(d[16 * m + 10], d[16 * m + 11]), pk(d[16 * m + 14], d[16 * m + 15]));
                }
                TRG(u, 3);
            }
        } else if (warp == 4) {
            mbar_expect(bar + 64 + lane * 8, A_KB, lane < 9);
            int it = 0;
#pragma unroll 1
            for (int u = 0; u < NTA; u++) {
                if (u == 0) { cnt_wait(g_cnt + C_W * 8, 96 * (ep + 1)); TRG(78, 0); }
                if (u < NSEG) cnt_wait(g_cnt + (C_N0 + u) * 8, 32 * (ep + 1));
                if (u > LAGA + LAG) cnt_wait(g_cnt + (C_RB + NSEG + u - LAGA - LAG - 1) * 8, 32 * (ep + 1));
                if (u >= LAGA) cnt_wait(g_cnt + (C_RB + u - LAGA) * 8, 32 * (ep + 1));
                TRG(u, 0);
                asm volatile("fence.proxy.async.global;" ::: "memory");
                const bool on = lane == 0 ? u < NSEG : lane == 1 && u >= LAGA;
#pragma unroll 1
                for (int kb = 0; kb < 9; kb++, it++) {
                    if (it >= 4) mbar_wait(bar + 32 + (it & 3) * 8, ((it >> 2) - 1) & 1);
                    mbar_expect(bar + (it & 3) * 8, u < NSEG && u >= LAGA ? 8192 : 4096, lane == 0);
                    asm volatile("{.reg .pred p; setp.ne.u32 p, %3, 0; @p cp.async.bulk.shared::cluster.global.mbarrier::complete_tx::bytes [%0], [%1], 4096, [%2];}"
                        :: "r"(sb + O_RING + (it & 3) * 8192 + (lane & 1) * 4096), "l"(g_xa + u * 4608 + (lane & 1) * 2304 + kb * 256), "r"(bar + (it & 3) * 8), "r"((uint32_t)on) : "memory");
                    if (u == 0) asm volatile("{.reg .pred p; setp.ne.u32 p, %4, 0; @p cp.async.bulk.shared::cluster.global.mbarrier::complete_tx::bytes [%0], [%1], %3, [%2];}"
                        :: "r"(sb + lane * A_KB), "l"(g_wa + ((b - 24) * 9 + lane) * (A_KB / 16)), "r"(bar + 64 + lane * 8), "n"(A_KB),
                           "r"((uint32_t)(lane < 9 && kb == (lane < 4 ? lane : lane < 6 ? 3 : lane - 2))) : "memory");
                }
            }
        } else if ((warp - 5) * 11 + b - 24 < 32) rows_a(xin, 1, (warp - 5) * 11 + b - 24, lane, ep, warp);
    }
}

extern "C" void kernel_launch(void* const* d_in, const int* in_sizes, int n_in, void* d_out, int out_size) {
    const __nv_bfloat16* x = (const __nv_bfloat16*)d_in[0];
    const __nv_bfloat16* wqkv = (const __nv_bfloat16*)d_in[1];
    const __nv_bfloat16* wo = (const __nv_bfloat16*)d_in[2];
    const __nv_bfloat16* mem0 = (const __nv_bfloat16*)d_in[4];
    const __nv_bfloat16* Wq = (const __nv_bfloat16*)d_in[5];
    const __nv_bfloat16* Wk = (const __nv_bfloat16*)d_in[6];
    const __nv_bfloat16* Wv = (const __nv_bfloat16*)d_in[7];
    const __nv_bfloat16* Wo = (const __nv_bfloat16*)d_in[8];
    cudaFuncSetAttribute(k_main, cudaFuncAttributeMaxDynamicSharedMemorySize, km::SMEM);
    cudaFuncSetAttribute(k_aux, cudaFuncAttributeMaxDynamicSharedMemorySize, ka::SMEM);
    cudaStream_t s = cudaStreamPerThread;
    k_main<<<96, 384, km::SMEM, s>>>(x, wqkv, wo, mem0, Wq, Wk, Wv, Wo);
    cudaLaunchConfig_t cfg = {};
    cudaLaunchAttribute at[1];
    at[0].id = cudaLaunchAttributeProgrammaticStreamSerialization;
    at[0].val.programmaticStreamSerializationAllowed = 1;
    cfg.stream = s; cfg.attrs = at; cfg.numAttrs = 1;
    cfg.gridDim = dim3(36); cfg.blockDim = dim3(384); cfg.dynamicSmemBytes = ka::SMEM;
    cudaLaunchKernelEx(&cfg, k_aux, x, wqkv, wo, Wo, (__nv_bfloat16*)d_out);
}
```

```cpp
#include <cuda_runtime.h>
#include <cuda_bf16.h>
#include <stdint.h>

#define LAG 7
constexpr int NSEG = 64;
constexpr int NT = NSEG + LAG;
#define AHEAD 1
constexpr int LAGA = LAG + AHEAD;
constexpr int NTA = NSEG + LAGA;
#define RING_ 8
constexpr int RING = RING_;
constexpr int DM = 576;

__device__ __align__(1024) uint4 g_xt[NT * 2 * 9 * 256];
__device__ __align__(1024) uint4 g_o[RING * 4 * 256 * 32];
__device__ __align__(1024) uint4 g_ex[2 * 131072];
__device__ unsigned g_side[96];
__device__ __align__(1024) uint4 g_pb[RING * 64 * 8 * 72];
__device__ __align__(1024) uint4 g_pa[RING * 64 * 4 * 72];
__device__ __align__(1024) uint4 g_oa[RING * 4 * 44 * 32];
__device__ __align__(1024) uint4 g_xa[NTA * 2 * 9 * 256];
__device__ __align__(1024) uint4 g_wa[11 * 9 * 21 * 64];
__device__ __align__(1024) uint4 g_x[3 * 2048 * 72];

constexpr int C_X = 0;
constexpr int C_O = C_X + NT;
constexpr int C_WB = C_O + NT * 8;
constexpr int C_RB = C_WB + NT * 4;
constexpr int C_A = C_RB + 2 * NSEG;
constexpr int C_WA = C_A + NTA * 4;
constexpr int C_N0 = C_WA + NTA * 4;
constexpr int C_W = C_N0 + NSEG;
constexpr int C_DONE = C_W + 1;
constexpr int C_TOTAL = C_DONE + 1;
__device__ __align__(1024) unsigned g_cnt[C_TOTAL * 8];
__device__ unsigned g_epoch;

#define TR(i)
#define TR1(i)
#define TR_ON(t)
#define TR_INIT(base)
#define TR_DUMP(slot)
#define TRG(t, i)
constexpr int TR_BYTES = 0;

#define DEVI __device__ __forceinline__
DEVI uint32_t smem_u32(const void* p) { return (uint32_t)__cvta_generic_to_shared(p); }
DEVI uint32_t pk(float lo, float hi) { uint32_t r; asm("cvt.rn.bf16x2.f32 %0, %1, %2;" : "=r"(r) : "f"(hi), "f"(lo)); return r; }
DEVI float bf_lo(uint32_t u) { return __uint_as_float(u << 16); }
DEVI float bf_hi(uint32_t u) { return __uint_as_float(u & 0xffff0000u); }
DEVI uint32_t add2(uint32_t a, uint32_t b) { uint32_t d; asm("add.rn.bf16x2 %0, %1, %2;" : "=r"(d) : "r"(a), "r"(b)); return d; }
DEVI uint32_t movm(uint32_t a) { uint32_t d; asm volatile("movmatrix.sync.aligned.m8n8.trans.b16 %0, %1;" : "=r"(d) : "r"(a)); return d; }
DEVI float2 shfl2(float a, float b, int o) {
    float2 r; asm volatile("shfl.sync.bfly.b32 %0, %2, %4, 31, -1; shfl.sync.bfly.b32 %1, %3, %4, 31, -1;" : "=&f"(r.x), "=f"(r.y) : "f"(a), "f"(b), "r"(o)); return r;
}
DEVI float ex2(float x) { float y; asm("ex2.approx.ftz.f32 %0, %1;" : "=f"(y) : "f"(x)); return y; }
DEVI float rcp(float x) { float y; asm("rcp.approx.ftz.f32 %0, %1;" : "=f"(y) : "f"(x)); return y; }
DEVI void mma16(float (&d)[4], uint32_t a0, uint32_t a1, uint32_t a2, uint32_t a3, uint32_t b0, uint32_t b1) {
    asm volatile("mma.sync.aligned.m16n8k16.row.col.f32.bf16.bf16.f32 {%0,%1,%2,%3}, {%4,%5,%6,%7}, {%8,%9}, {%0,%1,%2,%3};"
        : "+f"(d[0]), "+f"(d[1]), "+f"(d[2]), "+f"(d[3]) : "r"(a0), "r"(a1), "r"(a2), "r"(a3), "r"(b0), "r"(b1));
}
DEVI void mma8(float (&d)[4], uint32_t a0, uint32_t a1, uint32_t b0) {
    asm volatile("mma.sync.aligned.m16n8k8.row.col.f32.bf16.bf16.f32 {%0,%1,%2,%3}, {%4,%5}, {%6}, {%0,%1,%2,%3};"
        : "+f"(d[0]), "+f"(d[1]), "+f"(d[2]), "+f"(d[3]) : "r"(a0), "r"(a1), "r"(b0));
}
DEVI uint4 lds128(uint32_t a) { uint4 v; asm volatile("ld.shared.v4.u32 {%0,%1,%2,%3}, [%4];" : "=r"(v.x), "=r"(v.y), "=r"(v.z), "=r"(v.w) : "r"(a) : "memory"); return v; }
DEVI uint2 lds64(uint32_t a) { uint2 v; asm volatile("ld.shared.v2.u32 {%0,%1}, [%2];" : "=r"(v.x), "=r"(v.y) : "r"(a) : "memory"); return v; }
DEVI uint32_t lds32(uint32_t a) { uint32_t v; asm volatile("ld.shared.u32 %0, [%1];" : "=r"(v) : "r"(a) : "memory"); return v; }
DEVI uint32_t lds32v(uint32_t a) { uint32_t v; asm volatile("ld.volatile.shared.u32 %0, [%1];" : "=r"(v) : "r"(a) : "memory"); return v; }
DEVI uint4 lds128v(uint32_t a) { uint4 v; asm volatile("ld.volatile.shared.v4.u32 {%0,%1,%2,%3}, [%4];" : "=r"(v.x), "=r"(v.y), "=r"(v.z), "=r"(v.w) : "r"(a) : "memory"); return v; }
DEVI uint32_t lds16(uint32_t a) { uint32_t v; asm volatile("ld.shared.u16 %0, [%1];" : "=r"(v) : "r"(a) : "memory"); return v; }
DEVI uint4 ldsm4(uint32_t a) { uint4 v; asm volatile("ldmatrix.sync.aligned.m8n8.x4.shared.b16 {%0,%1,%2,%3}, [%4];" : "=r"(v.x), "=r"(v.y), "=r"(v.z), "=r"(v.w) : "r"(a) : "memory"); return v; }
DEVI uint4 ldsm4p(uint32_t a, bool pred) {
    uint4 v; asm volatile("{.reg .pred p; setp.ne.u32 p, %5, 0; @p ldmatrix.sync.aligned.m8n8.x4.shared.b16 {%0,%1,%2,%3}, [%4];}" : "=r"(v.x), "=r"(v.y), "=r"(v.z), "=r"(v.w) : "r"(a), "r"((uint32_t)pred) : "memory"); return v;
}
DEVI uint4 ldsm4t(uint32_t a) { uint4 v; asm volatile("ldmatrix.sync.aligned.m8n8.x4.trans.shared.b16 {%0,%1,%2,%3}, [%4];" : "=r"(v.x), "=r"(v.y), "=r"(v.z), "=r"(v.w) : "r"(a) : "memory"); return v; }
DEVI uint2 ldsm2(uint32_t a) { uint2 v; asm volatile("ldmatrix.sync.aligned.m8n8.x2.shared.b16 {%0,%1}, [%2];" : "=r"(v.x), "=r"(v.y) : "r"(a) : "memory"); return v; }
DEVI void stsm4t(uint32_t a, uint32_t x, uint32_t y, uint32_t z, uint32_t w) { asm volatile("stmatrix.sync.aligned.m8n8.x4.trans.shared.b16 [%0], {%1,%2,%3,%4};" :: "r"(a), "r"(x), "r"(y), "r"(z), "r"(w) : "memory"); }
DEVI void sts128(uint32_t a, uint32_t x, uint32_t y, uint32_t z, uint32_t w) { asm volatile("st.shared.v4.u32 [%0], {%1,%2,%3,%4};" :: "r"(a), "r"(x), "r"(y), "r"(z), "r"(w) : "memory"); }
DEVI void sts64(uint32_t a, uint32_t x, uint32_t y) { asm volatile("st.shared.v2.u32 [%0], {%1,%2};" :: "r"(a), "r"(x), "r"(y) : "memory"); }
DEVI void sts32(uint32_t a, uint32_t x) { asm volatile("st.shared.u32 [%0], %1;" :: "r"(a), "r"(x) : "memory"); }
DEVI void sts32p(uint32_t a, uint32_t x, bool pred) { asm volatile("{.reg .pred p; setp.ne.u32 p, %2, 0; @p st.shared.u32 [%0], %1;}" :: "r"(a), "r"(x), "r"((uint32_t)pred) : "memory"); }
DEVI void sta128(uint32_t a, uint32_t x, uint32_t y, uint32_t z, uint32_t w, uint32_t bar) {
    asm volatile("st.async.weak.shared::cluster.mbarrier::complete_tx::bytes.v4.b32 [%0], {%1,%2,%3,%4}, [%5];" :: "r"(a), "r"(x), "r"(y), "r"(z), "r"(w), "r"(bar) : "memory");
}
DEVI void sta128p(uint32_t a, uint32_t x, uint32_t y, uint32_t z, uint32_t w, uint32_t bar, bool pred) {
    asm volatile("{.reg .pred p; setp.ne.u32 p, %6, 0; @p st.async.weak.shared::cluster.mbarrier::complete_tx::bytes.v4.b32 [%0], {%1,%2,%3,%4}, [%5];}" :: "r"(a), "r"(x), "r"(y), "r"(z), "r"(w), "r"(bar), "r"((uint32_t)pred) : "memory");
}
DEVI void sta64(uint32_t a, uint32_t x, uint32_t y, uint32_t bar) {
    asm volatile("st.async.weak.shared::cluster.mbarrier::complete_tx::bytes.v2.b32 [%0], {%1,%2}, [%3];" :: "r"(a), "r"(x), "r"(y), "r"(bar) : "memory");
}
DEVI void sta32(uint32_t a, uint32_t x, uint32_t bar) {
    asm volatile("st.async.weak.shared::cluster.mbarrier::complete_tx::bytes.b32 [%0], %1, [%2];" :: "r"(a), "r"(x), "r"(bar) : "memory");
}
DEVI uint4 ldg_pkt(const void* p) {
    uint4 v;
    asm volatile("ld.relaxed.gpu.global.v4.u32 {%0,%1,%2,%3}, [%4];" : "=r"(v.x), "=r"(v.y), "=r"(v.z), "=r"(v.w) : "l"(p) : "memory");
    return v;
}
DEVI void ldg_pkt_if(uint4& v, const void* p, bool pred) {
    asm volatile("{.reg .pred p; setp.ne.u32 p, %5, 0; @p ld.relaxed.gpu.global.v4.u32 {%0,%1,%2,%3}, [%4];}"
        : "+r"(v.x), "+r"(v.y), "+r"(v.z), "+r"(v.w) : "l"(p), "r"((uint32_t)pred) : "memory");
}
DEVI void ldg_pkt_retry(uint4& v, const void* p, uint32_t tag) {
    asm volatile("{.reg .pred p; .reg .b32 t; lop3.b32 t, %0, %5, 1, 0x28; setp.ne.u32 p, t, 0; @p ld.relaxed.gpu.global.v4.u32 {%0,%1,%2,%3}, [%4];}"
        : "+r"(v.x), "+r"(v.y), "+r"(v.z), "+r"(v.w) : "l"(p), "r"(tag) : "memory");
}
DEVI void stg_pkt(void* p, uint32_t x, uint32_t y, uint32_t z, uint32_t w) {
    asm volatile("st.relaxed.gpu.global.v4.u32 [%0], {%1,%2,%3,%4};" :: "l"(p), "r"(x), "r"(y), "r"(z), "r"(w) : "memory");
}
DEVI uint32_t ldg_word(const void* p) { uint32_t v; asm volatile("ld.relaxed.gpu.global.u32 %0, [%1];" : "=r"(v) : "l"(p) : "memory"); return v; }
DEVI void stg_word(void* p, uint32_t x, bool pred) {
    asm volatile("{.reg .pred p; setp.ne.u32 p, %2, 0; @p st.relaxed.gpu.global.u32 [%0], %1;}" :: "l"(p), "r"(x), "r"((uint32_t)pred) : "memory");
}
DEVI uint2 ldg64nc(const void* p) { uint2 v; asm volatile("ld.global.nc.L1::no_allocate.v2.u32 {%0,%1}, [%2];" : "=r"(v.x), "=r"(v.y) : "l"(p)); return v; }
DEVI void prefetch_l2(const void* p, uint32_t bytes) { asm volatile("cp.async.bulk.prefetch.L2.global [%0], %1;" :: "l"(p), "r"(bytes) : "memory"); }
DEVI uint4 ldg128(const void* p) { uint4 v; asm volatile("ld.global.cg.v4.u32 {%0,%1,%2,%3}, [%4];" : "=r"(v.x), "=r"(v.y), "=r"(v.z), "=r"(v.w) : "l"(p) : "memory"); return v; }
DEVI uint2 ldg64(const void* p) { uint2 v; asm volatile("ld.global.cg.v2.u32 {%0,%1}, [%2];" : "=r"(v.x), "=r"(v.y) : "l"(p) : "memory"); return v; }
DEVI uint32_t ldg32(const void* p) { uint32_t v; asm volatile("ld.global.cg.u32 %0, [%1];" : "=r"(v) : "l"(p) : "memory"); return v; }
DEVI void stg128(void* p, uint32_t x, uint32_t y, uint32_t z, uint32_t w) { asm volatile("st.global.cg.v4.u32 [%0], {%1,%2,%3,%4};" :: "l"(p), "r"(x), "r"(y), "r"(z), "r"(w) : "memory"); }
DEVI void stg128p(void* p, uint32_t x, uint32_t y, uint32_t z, uint32_t w, bool pred) { asm volatile("{.reg .pred p; setp.ne.u32 p, %5, 0; @p st.global.cg.v4.u32 [%0], {%1,%2,%3,%4};}" :: "l"(p), "r"(x), "r"(y), "r"(z), "r"(w), "r"((uint32_t)pred) : "memory"); }
DEVI void stg64(void* p, uint32_t x, uint32_t y) { asm volatile("st.global.cg.v2.u32 [%0], {%1,%2};" :: "l"(p), "r"(x), "r"(y) : "memory"); }
DEVI void stg32(void* p, uint32_t x) { asm volatile("st.global.cg.u32 [%0], %1;" :: "l"(p), "r"(x) : "memory"); }
DEVI void cp16(uint32_t dst, const void* src) { asm volatile("cp.async.cg.shared.global [%0], [%1], 16;" :: "r"(dst), "l"(src) : "memory"); }
DEVI void cp16_if(uint32_t dst, const void* src, bool pred) { asm volatile("{.reg .pred p; setp.ne.u32 p, %2, 0; @p cp.async.cg.shared.global [%0], [%1], 16;}" :: "r"(dst), "l"(src), "r"((uint32_t)pred) : "memory"); }
DEVI void cp_commit() { asm volatile("cp.async.commit_group;" ::: "memory"); }
DEVI void cp4(uint32_t dst, const void* src) { asm volatile("cp.async.ca.shared.global [%0], [%1], 4;" :: "r"(dst), "l"(src) : "memory"); }
template <int N> DEVI void cp_wait() { asm volatile("cp.async.wait_group %0;" :: "n"(N) : "memory"); }
DEVI void cp_wait_all() { asm volatile("cp.async.wait_all;" ::: "memory"); }
DEVI void bar_sync(int id, int n) { asm volatile("bar.sync %0, %1;" :: "r"(id), "r"(n) : "memory"); }
DEVI void bar_arrive(int id, int n) { asm volatile("bar.arrive %0, %1;" :: "r"(id), "r"(n) : "memory"); }
DEVI void fence_async_smem() { asm volatile("fence.proxy.async.shared::cta;" ::: "memory"); }
DEVI void fence_async_global() { asm volatile("fence.proxy.async.global;" ::: "memory"); }
DEVI void mbar_init(uint32_t b, int n) { asm volatile("mbarrier.init.shared.b64 [%0], %1;" :: "r"(b), "r"(n) : "memory"); }
DEVI void mbar_expect(uint32_t b, uint32_t bytes, bool pred) {
    asm volatile("{.reg .pred p; setp.ne.u32 p, %2, 0; @p mbarrier.arrive.expect_tx.shared.b64 _, [%0], %1;}" :: "r"(b), "r"(bytes), "r"((uint32_t)pred) : "memory");
}
DEVI void mbar_arrive(uint32_t b, bool pred) { asm volatile("{.reg .pred p; setp.ne.u32 p, %1, 0; @p mbarrier.arrive.shared.b64 _, [%0];}" :: "r"(b), "r"((uint32_t)pred) : "memory"); }
DEVI void mbar_arrive_all3(uint32_t b, uint32_t lane) {
    asm volatile("{.reg .pred p; .reg .u32 a; setp.lt.u32 p, %1, 3; @p mapa.shared::cluster.u32 a, %0, %1; @p mbarrier.arrive.relaxed.cluster.shared::cluster.b64 _, [a];}" :: "r"(b), "r"(lane) : "memory");
}
#define FAULT "or.b32 n, n, 1; st.volatile.shared.u32 [n], n;\n"
#define LIM1 "400000"
#define LIM2 "2000000"
DEVI void fault_if(bool p, uint32_t n) { asm volatile("{.reg .pred p; setp.ne.u32 p, %0, 0; @p st.volatile.shared.u32 [%1], %1;}" :: "r"((uint32_t)p), "r"(n | 1) : "memory"); }
DEVI void mbar_wait(uint32_t b, uint32_t parity) {
    asm volatile("{.reg .pred p; .reg .u32 n;\n"
        "mbarrier.try_wait.parity.shared::cta.b64 p, [%0], %1;\n"
        "@p bra.uni D%=;\n"
        "mov.u32 n, 0;\n"
        "W%=: mbarrier.try_wait.parity.shared::cta.b64 p, [%0], %1;\n"
        "@p bra.uni D%=;\n"
        "add.u32 n, n, 1; setp.lt.u32 p, n, " LIM1 "; @p bra.uni W%=;\n"
        FAULT
        "D%=:}" :: "r"(b), "r"(parity) : "memory");
}
constexpr int POLL_LIMIT = 2000000;
DEVI void cnt_wait(const unsigned* c, unsigned target) {
    asm volatile("{.reg .pred p; .reg .u32 n, v;\n"
        "ld.acquire.gpu.global.u32 v, [%0];\n"
        "setp.ge.u32 p, v, %1; vote.sync.all.pred p, p, 0xffffffff; @p bra.uni D%=;\n"
        "mov.u32 n, 0;\n"
        "W%=: ld.acquire.gpu.global.u32 v, [%0];\n"
        "setp.ge.u32 p, v, %1; vote.sync.all.pred p, p, 0xffffffff; @p bra.uni D%=;\n"
        "add.u32 n, n, 1; setp.lt.u32 p, n, " LIM2 "; @p bra.uni W%=;\n"
        FAULT
        "D%=:}" :: "l"(c), "r"(target) : "memory");
}
DEVI void hint_wait(const unsigned* c, unsigned target) {
    asm volatile("{.reg .pred p; .reg .u32 n, v;\n"
        "ld.relaxed.gpu.global.u32 v, [%0];\n"
        "setp.ge.u32 p, v, %1; vote.sync.all.pred p, p, 0xffffffff; @p bra.uni D%=;\n"
        "mov.u32 n, 0;\n"
        "W%=: ld.relaxed.gpu.global.u32 v, [%0];\n"
        "setp.ge.u32 p, v, %1; vote.sync.all.pred p, p, 0xffffffff; @p bra.uni D%=;\n"
        "add.u32 n, n, 1; setp.lt.u32 p, n, " LIM2 "; @p bra.uni W%=;\n"
        FAULT
        "D%=:}" :: "l"(c), "r"(target) : "memory");
}
DEVI bool cnt_poll(const unsigned* c, unsigned target, uint32_t b, uint32_t parity) {
    uint32_t r;
    asm volatile("{.reg .pred p; .reg .u32 n, v;\n"
        "mov.u32 n, 0; mov.u32 %0, 0;\n"
        "W%=: ld.acquire.gpu.global.u32 v, [%1];\n"
        "setp.ge.u32 p, v, %2; vote.sync.all.pred p, p, 0xffffffff; @p bra.uni D%=;\n"
        "mbarrier.test_wait.parity.shared::cta.b64 p, [%3], %4;\n"
        "add.u32 n, n, 1; setp.gt.or.u32 p, n, 1000, p; vote.sync.any.pred p, p, 0xffffffff; @!p bra.uni W%=;\n"
        "mov.u32 %0, 1;\n"
        "D%=:}" : "=r"(r) : "l"(c), "r"(target), "r"(b), "r"(parity) : "memory");
    return r;
}
template <int N = 1> DEVI void cnt_add(unsigned* c, int lane) {
    asm volatile("{.reg .pred p; setp.eq.u32 p, %1, 0; fence.acq_rel.gpu; bar.warp.sync 0xffffffff; @p red.relaxed.gpu.global.add.u32 [%0], %2;}" :: "l"(c + lane), "r"(lane), "n"(N) : "memory");
}
DEVI void cnt_hint(unsigned* c, int lane) {
    asm volatile("{.reg .pred p; setp.eq.u32 p, %1, 0; @p red.relaxed.gpu.global.add.u32 [%0], 1;}" :: "l"(c + lane), "r"(lane) : "memory");
}
template <int N = NT> DEVI uint32_t ring_tag(unsigned u, uint32_t ep) { return (u / RING + ep * ((N - 1 - u % RING) / RING + 1) + 1) & 1; }
static_assert(RING >= LAGA && RING > LAG, "ring too short");
DEVI uint32_t lop_bad(uint32_t acc, uint32_t x, uint32_t y, uint32_t tag) {
    uint32_t d; asm("{.reg .b32 t; lop3.b32 t, %2, %3, %4, 0x7e; or.b32 %0, t, %1;}" : "=r"(d) : "r"(acc), "r"(x), "r"(y), "r"(tag)); return d;
}
template <int N> DEVI void validate(uint4* v, const void* p, int step, uint32_t tag) {
    for (int n = 0;; n++) {
        uint32_t bad = 0;
#pragma unroll
        for (int i = 0; i < N; i += 2) bad = lop_bad(bad, v[i].x, v[i + 1 < N ? i + 1 : i].x, tag);
        if (!__any_sync(~0u, bad & 1)) break;
#pragma unroll
        for (int i = 0; i < N; i++) ldg_pkt_retry(v[i], static_cast<const char*>(p) + i * step, tag);
        fault_if(n > POLL_LIMIT, n);
    }
}
DEVI uint32_t page_par(uint32_t off) { return __popc((off >> 12) & 0xb2) & 1; }
DEVI uint32_t inbox_off(int b) { return (b >> 1) * 32768 + (b & 1) * 8192; }
DEVI uint32_t mem_off(int w, int i) { return 0x180000 + w * 1024 + (i & 1) * 512 + (i & 3) * 16384 + (i < 4 ? 0 : i < 8 ? 0x30000 : 0x40000); }
DEVI void sched_fence(uint32_t zero, uint32_t id) { asm volatile("{.reg .pred p; setp.ne.u32 p, %0, %1; @p bra.uni D%=; exit; D%=:}" :: "r"(zero), "r"(id) : "memory"); }
DEVI uint32_t clk() { uint32_t c; asm volatile("mov.u32 %0, %%clock;" : "=r"(c) :: "memory"); return c; }
DEVI void delay(uint32_t n) {
    if (n) asm volatile("{.reg .pred p; .reg .u32 c, e; mov.u32 e, %%clock;\n W%=: mov.u32 c, %%clock; sub.u32 c, c, e; setp.lt.u32 p, c, %0; @p bra.uni W%=;}" :: "r"(n) : "memory");
}
DEVI void delay_until(uint32_t t0, uint32_t n) {
    asm volatile("{.reg .pred p; .reg .u32 c;\n W%=: mov.u32 c, %%clock; sub.u32 c, c, %1; setp.lt.u32 p, c, %0; @p bra.uni W%=;}" :: "r"(n), "r"(t0) : "memory");
}
DEVI void wg_fence() { asm volatile("wgmma.fence.sync.aligned;" ::: "memory"); }
DEVI void wg_commit() { asm volatile("wgmma.commit_group.sync.aligned;" ::: "memory"); }
template <int N> DEVI void wg_wait() { asm volatile("wgmma.wait_group.sync.aligned %0;" :: "n"(N) : "memory"); }
DEVI uint64_t mkdesc(uint32_t lo, uint32_t hi) { uint64_t d; asm("mov.b64 %0, {%1,%2};" : "=l"(d) : "r"(lo), "r"(hi)); return d; }
DEVI void cluster_arrive() { asm volatile("barrier.cluster.arrive.relaxed.aligned;" ::: "memory"); }
DEVI void cluster_wait() { asm volatile("barrier.cluster.wait.aligned;" ::: "memory"); }
DEVI void cluster_sync() { asm volatile("barrier.cluster.arrive.aligned;\n barrier.cluster.wait.aligned;" ::: "memory"); }
DEVI void wgmma_ss16t(float (&d)[8], uint64_t da, uint64_t db, int acc) {
    asm volatile("{.reg .pred p; setp.ne.b32 p, %10, 0;\n"
        "wgmma.mma_async.sync.aligned.m64n16k16.f32.bf16.bf16 {%0,%1,%2,%3,%4,%5,%6,%7}, %8, %9, p, 1, 1, 0, 1;}"
        : "+f"(d[0]), "+f"(d[1]), "+f"(d[2]), "+f"(d[3]), "+f"(d[4]), "+f"(d[5]), "+f"(d[6]), "+f"(d[7])
        : "l"(da), "l"(db), "r"(acc));
}
DEVI void wgmma_ss16a(float (&d)[8], uint64_t da, uint64_t db, int acc) {
    asm volatile("{.reg .pred p; setp.ne.b32 p, %10, 0;\n"
        "wgmma.mma_async.sync.aligned.m64n16k16.f32.bf16.bf16 {%0,%1,%2,%3,%4,%5,%6,%7}, %8, %9, p, 1, 1, 1, 0;}"
        : "+f"(d[0]), "+f"(d[1]), "+f"(d[2]), "+f"(d[3]), "+f"(d[4]), "+f"(d[5]), "+f"(d[6]), "+f"(d[7])
        : "l"(da), "l"(db), "r"(acc));
}
DEVI void wgmma_ss64(float (&d)[32], uint64_t da, uint64_t db, int acc) {
    asm volatile("{.reg .pred p; setp.ne.b32 p, %34, 0;\n"
        "wgmma.mma_async.sync.aligned.m64n64k16.f32.bf16.bf16 {%0,%1,%2,%3,%4,%5,%6,%7,%8,%9,%10,%11,%12,%13,%14,%15,%16,%17,%18,%19,%20,%21,%22,%23,%24,%25,%26,%27,%28,%29,%30,%31}, %32, %33, p, 1, 1, 0, 0;}"
        : "+f"(d[0]), "+f"(d[1]), "+f"(d[2]), "+f"(d[3]), "+f"(d[4]), "+f"(d[5]), "+f"(d[6]), "+f"(d[7]), "+f"(d[8]), "+f"(d[9]), "+f"(d[10]), "+f"(d[11]), "+f"(d[12]), "+f"(d[13]), "+f"(d[14]), "+f"(d[15]), "+f"(d[16]), "+f"(d[17]), "+f"(d[18]), "+f"(d[19]), "+f"(d[20]), "+f"(d[21]), "+f"(d[22]), "+f"(d[23]), "+f"(d[24]), "+f"(d[25]), "+f"(d[26]), "+f"(d[27]), "+f"(d[28]), "+f"(d[29]), "+f"(d[30]), "+f"(d[31])
        : "l"(da), "l"(db), "r"(acc));
}
DEVI void wgmma_rs16t(float (&d)[8], uint32_t a0, uint32_t a1, uint32_t a2, uint32_t a3, uint64_t db, int acc) {
    asm volatile("{.reg .pred p; setp.ne.b32 p, %13, 0;\n"
        "wgmma.mma_async.sync.aligned.m64n16k16.f32.bf16.bf16 {%0,%1,%2,%3,%4,%5,%6,%7}, {%8,%9,%10,%11}, %12, p, 1, 1, 1;}"
        : "+f"(d[0]), "+f"(d[1]), "+f"(d[2]), "+f"(d[3]), "+f"(d[4]), "+f"(d[5]), "+f"(d[6]), "+f"(d[7])
        : "r"(a0), "r"(a1), "r"(a2), "r"(a3), "l"(db), "r"(acc));
}
DEVI void wgmma_rs64(float (&d)[32], uint32_t a0, uint32_t a1, uint32_t a2, uint32_t a3, uint64_t db, int acc) {
    asm volatile("{.reg .pred p; setp.ne.b32 p, %37, 0;\n"
        "wgmma.mma_async.sync.aligned.m64n64k16.f32.bf16.bf16 {%0,%1,%2,%3,%4,%5,%6,%7,%8,%9,%10,%11,%12,%13,%14,%15,%16,%17,%18,%19,%20,%21,%22,%23,%24,%25,%26,%27,%28,%29,%30,%31}, {%32,%33,%34,%35}, %36, p, 1, 1, 0;}"
        : "+f"(d[0]), "+f"(d[1]), "+f"(d[2]), "+f"(d[3]), "+f"(d[4]), "+f"(d[5]), "+f"(d[6]), "+f"(d[7]), "+f"(d[8]), "+f"(d[9]), "+f"(d[10]), "+f"(d[11]), "+f"(d[12]), "+f"(d[13]), "+f"(d[14]), "+f"(d[15]), "+f"(d[16]), "+f"(d[17]), "+f"(d[18]), "+f"(d[19]), "+f"(d[20]), "+f"(d[21]), "+f"(d[22]), "+f"(d[23]), "+f"(d[24]), "+f"(d[25]), "+f"(d[26]), "+f"(d[27]), "+f"(d[28]), "+f"(d[29]), "+f"(d[30]), "+f"(d[31])
        : "r"(a0), "r"(a1), "r"(a2), "r"(a3), "l"(db), "r"(acc));
}
DEVI void wgmma_ss168t(float (&d)[84], uint64_t da, uint64_t db, int acc) {
    asm volatile("{.reg .pred p; setp.ne.b32 p, %86, 0;\n"
        "wgmma.mma_async.sync.aligned.m64n168k16.f32.bf16.bf16 {%0,%1,%2,%3,%4,%5,%6,%7,%8,%9,%10,%11,%12,%13,%14,%15,%16,%17,%18,%19,%20,%21,%22,%23,%24,%25,%26,%27,%28,%29,%30,%31,%32,%33,%34,%35,%36,%37,%38,%39,%40,%41,%42,%43,%44,%45,%46,%47,%48,%49,%50,%51,%52,%53,%54,%55,%56,%57,%58,%59,%60,%61,%62,%63,%64,%65,%66,%67,%68,%69,%70,%71,%72,%73,%74,%75,%76,%77,%78,%79,%80,%81,%82,%83}, %84, %85, p, 1, 1, 0, 1;}"
        : "+f"(d[0]), "+f"(d[1]), "+f"(d[2]), "+f"(d[3]), "+f"(d[4]), "+f"(d[5]), "+f"(d[6]), "+f"(d[7]), "+f"(d[8]), "+f"(d[9]), "+f"(d[10]), "+f"(d[11]), "+f"(d[12]), "+f"(d[13]), "+f"(d[14]), "+f"(d[15]), "+f"(d[16]), "+f"(d[17]), "+f"(d[18]), "+f"(d[19]), "+f"(d[20]), "+f"(d[21]), "+f"(d[22]), "+f"(d[23]), "+f"(d[24]), "+f"(d[25]), "+f"(d[26]), "+f"(d[27]), "+f"(d[28]), "+f"(d[29]), "+f"(d[30]), "+f"(d[31]), "+f"(d[32]), "+f"(d[33]), "+f"(d[34]), "+f"(d[35]), "+f"(d[36]), "+f"(d[37]), "+f"(d[38]), "+f"(d[39]), "+f"(d[40]), "+f"(d[41]), "+f"(d[42]), "+f"(d[43]), "+f"(d[44]), "+f"(d[45]), "+f"(d[46]), "+f"(d[47]), "+f"(d[48]), "+f"(d[49]), "+f"(d[50]), "+f"(d[51]), "+f"(d[52]), "+f"(d[53]), "+f"(d[54]), "+f"(d[55]), "+f"(d[56]), "+f"(d[57]), "+f"(d[58]), "+f"(d[59]), "+f"(d[60]), "+f"(d[61]), "+f"(d[62]), "+f"(d[63]), "+f"(d[64]), "+f"(d[65]), "+f"(d[66]), "+f"(d[67]), "+f"(d[68]), "+f"(d[69]), "+f"(d[70]), "+f"(d[71]), "+f"(d[72]), "+f"(d[73]), "+f"(d[74]), "+f"(d[75]), "+f"(d[76]), "+f"(d[77]), "+f"(d[78]), "+f"(d[79]), "+f"(d[80]), "+f"(d[81]), "+f"(d[82]), "+f"(d[83])
        : "l"(da), "l"(db), "r"(acc));
}
DEVI void wgmma_rs96t(float (&d)[48], uint32_t a0, uint32_t a1, uint32_t a2, uint32_t a3, uint64_t db, int acc) {
    asm volatile("{.reg .pred p; setp.ne.b32 p, %53, 0;\n"
        "wgmma.mma_async.sync.aligned.m64n96k16.f32.bf16.bf16 {%0,%1,%2,%3,%4,%5,%6,%7,%8,%9,%10,%11,%12,%13,%14,%15,%16,%17,%18,%19,%20,%21,%22,%23,%24,%25,%26,%27,%28,%29,%30,%31,%32,%33,%34,%35,%36,%37,%38,%39,%40,%41,%42,%43,%44,%45,%46,%47}, {%48,%49,%50,%51}, %52, p, 1, 1, 1;}"
        : "+f"(d[0]), "+f"(d[1]), "+f"(d[2]), "+f"(d[3]), "+f"(d[4]), "+f"(d[5]), "+f"(d[6]), "+f"(d[7]), "+f"(d[8]), "+f"(d[9]), "+f"(d[10]), "+f"(d[11]), "+f"(d[12]), "+f"(d[13]), "+f"(d[14]), "+f"(d[15]), "+f"(d[16]), "+f"(d[17]), "+f"(d[18]), "+f"(d[19]), "+f"(d[20]), "+f"(d[21]), "+f"(d[22]), "+f"(d[23]), "+f"(d[24]), "+f"(d[25]), "+f"(d[26]), "+f"(d[27]), "+f"(d[28]), "+f"(d[29]), "+f"(d[30]), "+f"(d[31]), "+f"(d[32]), "+f"(d[33]), "+f"(d[34]), "+f"(d[35]), "+f"(d[36]), "+f"(d[37]), "+f"(d[38]), "+f"(d[39]), "+f"(d[40]), "+f"(d[41]), "+f"(d[42]), "+f"(d[43]), "+f"(d[44]), "+f"(d[45]), "+f"(d[46]), "+f"(d[47])
        : "r"(a0), "r"(a1), "r"(a2), "r"(a3), "l"(db), "r"(acc));
}
DEVI void wgmma_rs192t(float (&d)[96], uint32_t a0, uint32_t a1, uint32_t a2, uint32_t a3, uint64_t db, int acc) {
    asm volatile("{.reg .pred p; setp.ne.b32 p, %101, 0;\n"
        "wgmma.mma_async.sync.aligned.m64n192k16.f32.bf16.bf16 {%0,%1,%2,%3,%4,%5,%6,%7,%8,%9,%10,%11,%12,%13,%14,%15,%16,%17,%18,%19,%20,%21,%22,%23,%24,%25,%26,%27,%28,%29,%30,%31,%32,%33,%34,%35,%36,%37,%38,%39,%40,%41,%42,%43,%44,%45,%46,%47,%48,%49,%50,%51,%52,%53,%54,%55,%56,%57,%58,%59,%60,%61,%62,%63,%64,%65,%66,%67,%68,%69,%70,%71,%72,%73,%74,%75,%76,%77,%78,%79,%80,%81,%82,%83,%84,%85,%86,%87,%88,%89,%90,%91,%92,%93,%94,%95}, {%96,%97,%98,%99}, %100, p, 1, 1, 1;}"
        : "+f"(d[0]), "+f"(d[1]), "+f"(d[2]), "+f"(d[3]), "+f"(d[4]), "+f"(d[5]), "+f"(d[6]), "+f"(d[7]), "+f"(d[8]), "+f"(d[9]), "+f"(d[10]), "+f"(d[11]), "+f"(d[12]), "+f"(d[13]), "+f"(d[14]), "+f"(d[15]), "+f"(d[16]), "+f"(d[17]), "+f"(d[18]), "+f"(d[19]), "+f"(d[20]), "+f"(d[21]), "+f"(d[22]), "+f"(d[23]), "+f"(d[24]), "+f"(d[25]), "+f"(d[26]), "+f"(d[27]), "+f"(d[28]), "+f"(d[29]), "+f"(d[30]), "+f"(d[31]), "+f"(d[32]), "+f"(d[33]), "+f"(d[34]), "+f"(d[35]), "+f"(d[36]), "+f"(d[37]), "+f"(d[38]), "+f"(d[39]), "+f"(d[40]), "+f"(d[41]), "+f"(d[42]), "+f"(d[43]), "+f"(d[44]), "+f"(d[45]), "+f"(d[46]), "+f"(d[47]), "+f"(d[48]), "+f"(d[49]), "+f"(d[50]), "+f"(d[51]), "+f"(d[52]), "+f"(d[53]), "+f"(d[54]), "+f"(d[55]), "+f"(d[56]), "+f"(d[57]), "+f"(d[58]), "+f"(d[59]), "+f"(d[60]), "+f"(d[61]), "+f"(d[62]), "+f"(d[63]), "+f"(d[64]), "+f"(d[65]), "+f"(d[66]), "+f"(d[67]), "+f"(d[68]), "+f"(d[69]), "+f"(d[70]), "+f"(d[71]), "+f"(d[72]), "+f"(d[73]), "+f"(d[74]), "+f"(d[75]), "+f"(d[76]), "+f"(d[77]), "+f"(d[78]), "+f"(d[79]), "+f"(d[80]), "+f"(d[81]), "+f"(d[82]), "+f"(d[83]), "+f"(d[84]), "+f"(d[85]), "+f"(d[86]), "+f"(d[87]), "+f"(d[88]), "+f"(d[89]), "+f"(d[90]), "+f"(d[91]), "+f"(d[92]), "+f"(d[93]), "+f"(d[94]), "+f"(d[95])
        : "r"(a0), "r"(a1), "r"(a2), "r"(a3), "l"(db), "r"(acc));
}

#define TRD(t, i)
namespace km {
#define NSS 6
#define RG "184"
#define RW "136"
#define NFL 2
#define NR1 3
#define NR2 3
#define EK 7
#define FK 5
#define LDP 3
#define SND 1
#define NGAP 3
constexpr int O_H = 0;
constexpr int O_MB = 73728;
constexpr int O_VX = 96768;
constexpr int O_KX = 113152;
constexpr int O_QX = 119296;
constexpr int O_VM = 125440;
constexpr int O_KM = 129536;
constexpr int O_QM = 131072;
constexpr int O_SM = 132608;
constexpr int O_ST = 135168;
constexpr int O_OX = 145408;
constexpr int O_WO = 149504;
constexpr int O_OS = O_WO;
constexpr int O_WS = O_WO + 49152;
constexpr int O_RL = 110592;
constexpr int O_BAR = O_WS + NSS * 4096;
constexpr int SMEM = O_BAR + 128 + 1024 + TR_BYTES;
enum { B_X = 0, B_XFREE = 8, B_WIN = 16, B_VX = 24, B_SM = 32, B_ST = 40, B_EP = 56 };
#define DLY1 (100 * w)
#define DLY2 400
#define EARLY 1
#define DLYO 250
#define DLY0 5000
#define PFON 0
#define PLACE 1
#define XST 7
#define DLYW 9000
#define DLYB 4000
constexpr uint32_t DESC_HI = (1024 >> 4) | (1u << 30);
constexpr float SC = 0.08838834764831845f * 1.4426950408889634f;
}

__global__ void __cluster_dims__(3, 1, 1) __launch_bounds__(384, 1)
k_main(const __nv_bfloat16* __restrict__ x0, const __nv_bfloat16* __restrict__ wqkv, const __nv_bfloat16* __restrict__ wo,
       const __nv_bfloat16* __restrict__ mem0, const __nv_bfloat16* __restrict__ Wq, const __nv_bfloat16* __restrict__ Wk,
       const __nv_bfloat16* __restrict__ Wv, const __nv_bfloat16* __restrict__ Wo) {
    using namespace km;
    extern __shared__ unsigned char smem_raw[];
    const uint32_t sb = (smem_u32(smem_raw) + 1023) & ~1023u;
    const int tid = threadIdx.x, lane = tid & 31, warp = __shfl_sync(~0u, tid >> 5, 0);
    uint32_t l16 = __shfl_sync(~0u, lane * 16, lane);
#define OPQ() asm volatile("" : "+r"(l16))
    const int b = blockIdx.x, h = b / 3, r = b % 3;
    const int nq = r == 2 ? 2 : 3;
    const uint32_t bar = sb + O_BAR;
    asm volatile("griddepcontrol.launch_dependents;");
    const uint32_t t_start = clk();
    if (warp == 0 && b < 72) {
        if (lane == 0) { mbar_init(bar + 96, 1); fence_async_smem(); mbar_expect(bar + 96, 8 * 3456, true); }
        __syncwarp();
        if (lane < 8) asm volatile("cp.async.bulk.shared::cluster.global.mbarrier::complete_tx::bytes [%0], [%1], 3456, [%2];" :: "r"(sb + O_RL + lane * 3472), "l"(wqkv + (b * 8 + lane) * 1728), "r"(bar + 96) : "memory");
    }
    if (tid == 352) {
        prefetch_l2(x0 + b * (2 * DM), 2 * 1152); prefetch_l2(wo + b * (6 * DM), 6 * 1152);
    }
    if (tid == 320) sts32(bar + 64, ldg32(&g_epoch));
#define EP lds32(bar + 64)
    TR_INIT(bar + 128);
    TRG(79, 0);
    uint32_t roff0, roff1;
    {
        uint32_t y0, y1;
        asm("mapa.shared::cluster.u32 %0, %1, %2;" : "=r"(y0) : "r"(sb), "r"((r + 1) % 3));
        asm("mapa.shared::cluster.u32 %0, %1, %2;" : "=r"(y1) : "r"(sb), "r"((r + 2) % 3));
        roff0 = y0 - sb; roff1 = y1 - sb;
    }
#define IDENT (((l16 >> 7) == ((l16 >> 4) & 3) ? 0x3f80u : 0u) << ((l16 >> 2) & 16))
#define LSWAP ((l16 & 0x70) | ((l16 & 0x80) << 1) | ((l16 & 0x100) >> 1))
    const uint32_t nv_remote = 8 - (8 - 2 * nq);

    if (warp < 8) {
        asm volatile("setmaxnreg.inc.sync.aligned.u32 " RG ";");
        constexpr int SSP = 36 / NSS;
#define IS_SS(kk) ((kk) % SSP == 3)
#define AI(kk) (4 * ((kk) - ((kk) + SSP - 4) / SSP))
        uint32_t a[144 - 4 * NSS];
        {
            const int ci = tid & 15, slot = ci >> 1, d0 = tid >> 4;
            const __nv_bfloat16* src = slot < nq ? Wq + (3 * r + slot) * 16 : slot < 2 * nq ? Wk + (3 * r + slot - nq) * 16 : Wv + (2 * r + slot - 2 * nq) * 16;
            src += h * 128 + (ci & 1) * 8 + d0 * 4096;
            auto issue = [&](int q) {
#pragma unroll
                for (int i = 0; i < 3; i++) if (q < 12) cp16(sb + (q * 3 + i) * 4096 + d0 * 256 + ((ci ^ (d0 & 7)) << 4), src + (size_t)(q * 3 + i) * 65536);
                asm volatile("cp.async.commit_group;" ::: "memory");
            };
            if (b < 72) {
                bar_sync(10, 256);
                mbar_wait(bar + 96, 0);
                TR1(4);
#pragma unroll 2
                for (int ag = tid >> 3; ag < 231; ag += 32) {
                    const int a = ag / 21, gr = ag % 21, tl = gr >= 18;
                    const int head = 3 * a + (tl ? 0 : (gr % 6) >> 1), nw = tl ? min(3, 32 - head) : head < 32 ? 4 : 0;
                    const uint32_t p = sb + O_RL + (tid & 7) * 3472 + (tl ? gr - 18 : gr / 6) * 1152 + head * 36 + (tl ? 32 : (gr & 1) * 16), step = tl ? 36 : 4;
                    uint32_t v[4];
#pragma unroll
                    for (int i = 0; i < 4; i++) { v[i] = lds32(p + i * step); if (i >= nw) v[i] = 0; }
                    stg128(g_wa + ((a * 9 + (b >> 3)) * 21 + gr) * 64 + (b & 7) * 8 + (tid & 7), v[0], v[1], v[2], v[3]);
                }
            }
            {
                bar_arrive(15, 288);
                TR1(5);
                delay_until(t_start, DLY0);
#pragma unroll
                for (int q = 0; q < NFL; q++) issue(q);
            }
            TR1(1);
            const int mi = lane >> 3;
            const uint32_t ad = sb + ((mi >> 1) * 8 + (lane & 7)) * 256 + (((warp * 2 + (mi & 1)) ^ (lane & 7)) << 4);
#pragma unroll
            for (int kk = 0; kk < 36; kk++) {
                if (kk % 3 == 0) { cp_wait<NFL - 1>(); issue(kk / 3 + NFL); bar_sync(10, 256); }
                const uint4 f = ldsm4t(ad + kk * 4096);
                if (IS_SS(kk)) {
                    const uint32_t o0 = sb + O_WS + (kk / SSP) * 4096 + warp * 512 + lane * 4;
                    sts32(o0, f.x); sts32(o0 + 256, f.y); sts32(o0 + 128, f.z); sts32(o0 + 384, f.w);
                } else { a[AI(kk)] = f.x; a[AI(kk) + 1] = f.y; a[AI(kk) + 2] = f.z; a[AI(kk) + 3] = f.w; }
            }
            TR1(2);
            bar_sync(9, 384);
#pragma unroll
            for (int i = 0; i < 9; i++) sts128(sb + O_H + i * 8192 + 4096 + tid * 16, 0, 0, 0, 0);
#pragma unroll
            for (int i = 0; i < 8; i++) if (i * 256 + tid < (O_OX - O_KX) / 16) sts128(sb + O_KX + i * 4096 + tid * 16, 0, 0, 0, 0);
            fence_async_smem();
            cluster_sync();
        }
        TR1(3);
        const int kind = warp < nq ? 0 : warp < 2 * nq ? 1 : 2;
        const int sl = kind == 0 ? warp : kind == 1 ? warp - nq : 2 * r + warp - 2 * nq;
        const uint32_t adX0 = sb + (kind == 0 ? O_QX : kind == 1 ? O_KX : O_VX) + sl * 2048;
        const uint32_t adM0 = sb + (kind == 0 ? O_QM : kind == 1 ? O_KM : O_VM) + sl * 512;
        const uint32_t hlo = (((sb + O_H) >> 4) & 0x3fff) | (1u << 16);
        const uint32_t mlo = (((sb + O_MB) >> 4) & 0x3fff) | (16u << 16);
        const uint32_t wlo = (((sb + O_WS + (warp >> 2) * 2048) >> 4) & 0x3fff) | (8u << 16);
        const int L = (warp >> 1) & 1, qh = warp & 1;
        const uint32_t st = sb + O_ST + warp * 1280;

#pragma unroll 1
        for (int t = -1;; t++) {
            TR_ON(t);
            OPQ();
            const uint32_t adX = adX0 + l16, adM = adM0 + l16, l8 = l16 >> 1;
            const uint32_t lq = LSWAP;
            if (t >= 0) {
                float d0[8], d1[8];
                {
#pragma unroll
                    for (int G = 0; G < 3; G++) {
                        if (warp < 4) bar_sync(1 + G, 160); else bar_sync(12 + G, 160);
                        if (G == 0) wg_fence();
#pragma unroll
                        for (int q = 0; q < 12; q++) {
                            const int kk = 12 * G + q;
                            const uint64_t db = mkdesc(mlo + kk * 32, 8);
                            if (IS_SS(kk)) wgmma_ss16t((kk & 1) ? d1 : d0, mkdesc(wlo + (kk / SSP) * 256, 16), db, 1);
                            else wgmma_rs16t((kk & 1) ? d1 : d0, a[AI(kk)], a[AI(kk) + 1], a[AI(kk) + 2], a[AI(kk) + 3], db, kk >= 2);
                            if (kk == 0) TR(0);
                        }
                    }
                    wg_commit();
                }
#define PM(i) pk(d0[2 * (i)] + d1[2 * (i)], d0[2 * (i) + 1] + d1[2 * (i) + 1])
                if (warp >= 4) {
                    wg_wait<0>();
                    TR(1);
                    const uint32_t p0 = PM(0), p1 = PM(1), p2 = PM(2), p3 = PM(3);
                    if (kind == 2) {
                        sts128(adM, p0, p1, p2, p3);
                        bar_arrive(4, 384);
                        sta128(adM + roff0, p0, p1, p2, p3, bar + B_SM + roff0);
                        sta128(adM + roff1, p0, p1, p2, p3, bar + B_SM + roff1);
                    } else {
                        stsm4t(adM, p0, p1, p2, p3);
                        bar_arrive(4, 384);
                    }
                } else {
                    uint4 q[3], k[3][2];
                    mbar_wait(bar + B_EP, t & 1);
#pragma unroll
                    for (int m = 0; m < LDP; m++) {
                        q[m] = ldsm4(sb + O_QX + m * 2048 + warp * 512 + lq);
                        k[m][0] = ldsm4(sb + O_KX + m * 2048 + L * 1024 + l16); k[m][1] = ldsm4(sb + O_KX + m * 2048 + L * 1024 + 512 + l16);
                    }
                    wg_wait<0>();
                    TR(1);
                    stsm4t(adM, PM(0), PM(1), PM(2), PM(3));
                    bar_arrive(4, 384);
                    sched_fence(gridDim.y, 6);
#pragma unroll
                    for (int m = LDP; m < 3; m++) {
                        q[m] = ldsm4(sb + O_QX + m * 2048 + warp * 512 + lq);
                        k[m][0] = ldsm4(sb + O_KX + m * 2048 + L * 1024 + l16); k[m][1] = ldsm4(sb + O_KX + m * 2048 + L * 1024 + 512 + l16);
                    }
                    float s[5][4];
                    {
                        float y[4] = {0, 0, 0, 0};
#pragma unroll
                        for (int n = 0; n < 5; n++) s[n][0] = s[n][1] = s[n][2] = s[n][3] = 0.f;
#pragma unroll
                        for (int m = 0; m < 3; m++) {
                            mma16(s[0], q[m].x, q[m].y, q[m].z, q[m].w, k[m][0].x, k[m][0].y); mma16(s[1], q[m].x, q[m].y, q[m].z, q[m].w, k[m][0].z, k[m][0].w);
                            mma16(s[2], q[m].x, q[m].y, q[m].z, q[m].w, k[m][1].x, k[m][1].y); mma16(s[3], q[m].x, q[m].y, q[m].z, q[m].w, k[m][1].z, k[m][1].w);
                        }
                        auto send = [&]() {
                            uint32_t w0 = pk(s[0][0], s[0][1]), w1 = pk(s[0][2], s[0][3]), w2 = pk(s[1][0], s[1][1]), w3 = pk(s[1][2], s[1][3]);
                            sta128(st + l16 + 5120 + roff0, w0, w1, w2, w3, bar + B_ST + roff0);
                            sta128(st + l16 + roff1, w0, w1, w2, w3, bar + B_ST + roff1);
                            w0 = pk(s[2][0], s[2][1]); w1 = pk(s[2][2], s[2][3]); w2 = pk(s[3][0], s[3][1]); w3 = pk(s[3][2], s[3][3]);
                            sta128p(st + l16 + 5120 + 512 + roff0, w0, w1, w2, w3, bar + B_ST + roff0, qh);
                            sta128p(st + l16 + 512 + roff1, w0, w1, w2, w3, bar + B_ST + roff1, qh);
                        };
                        sched_fence(gridDim.y, 7);
                        bar_sync(5, 256);
                        const uint4 k01 = ldsm4(sb + O_KM + L * 256 + l16 + (l16 & 256));
                        const uint2 k2 = ldsm2(sb + O_KM + 1024 + L * 256 + l16);
                        if (SND == 0) send();
                        mma16(s[4], q[0].x, q[0].y, q[0].z, q[0].w, k01.x, k01.y);
                        mma16(y, q[1].x, q[1].y, q[1].z, q[1].w, k01.z, k01.w);
                        mma16(s[4], q[2].x, q[2].y, q[2].z, q[2].w, k2.x, k2.y);
#pragma unroll
                        for (int j = 0; j < 4; j++) s[4][j] += y[j];
                        const uint32_t w0 = pk(s[4][0], s[4][1]), w1 = pk(s[4][2], s[4][3]);
                        if (NGAP > 0) bar_arrive(10, 256);
                        sta64(st + l8 + 5120 + 1024 + roff0, w0, w1, bar + B_ST + roff0);
                        sta64(st + l8 + 1024 + roff1, w0, w1, bar + B_ST + roff1);
                        if (SND == 1) send();
                        TR(2);
                        const int lim = 16 * qh + (int)(l16 >> 6) - (int)((l16 >> 3) & 6);
#pragma unroll
                        for (int n = 0; n < 4; n++)
#pragma unroll
                            for (int j = 0; j < 4; j++) if (!(n == 0 && j >= 2) && 8 * (n - (j >> 1)) + (j & 1) > lim) s[n][j] = -1e30f;
#pragma unroll
                        for (int n = 0; n < 4; n++) asm volatile("" : "+f"(s[n][0]), "+f"(s[n][1]), "+f"(s[n][2]), "+f"(s[n][3]));
                    }
                    uint4 v0[3], v1[3]; uint2 vm[3];
                    const uint32_t vad = sb + O_VX + 3 * r * 2048 + L * 1024 + l16;
#pragma unroll
                    for (int m = 0; m < 3; m++) v0[m] = lds128(vad + m * 2048);
                    const uint32_t otag = ring_tag(t, EP);
                    uint32_t ident = IDENT;
                    asm volatile("" : "+r"(ident));
                    mbar_wait(bar + B_SM, t & 1);
                    mbar_wait(bar + B_ST, t & 1);
                    TR(3);
                    float mx0, mx1;
                    {
                        const uint4 u = lds128(st + l16), v = lds128(st + 512 + l16); const uint2 w = lds64(st + 1024 + l8);
                        const uint4 x = lds128(st + 5120 + l16), y = lds128(st + 5120 + 512 + l16); const uint2 z = lds64(st + 5120 + 1024 + l8);
                        mma8(s[0], u.x, u.y, ident); mma8(s[1], u.z, u.w, ident); mma8(s[2], v.x, v.y, ident); mma8(s[3], v.z, v.w, ident); mma8(s[4], w.x, w.y, ident);
                        mma8(s[0], x.x, x.y, ident); mma8(s[1], x.z, x.w, ident); mma8(s[2], y.x, y.y, ident); mma8(s[3], y.z, y.w, ident); mma8(s[4], z.x, z.y, ident);
                        mx0 = fmaxf(fmaxf(fmaxf(s[0][0], s[0][1]), fmaxf(s[1][0], s[1][1])), fmaxf(fmaxf(s[2][0], s[2][1]), fmaxf(s[3][0], s[3][1])));
                        mx1 = fmaxf(fmaxf(fmaxf(s[0][2], s[0][3]), fmaxf(s[1][2], s[1][3])), fmaxf(fmaxf(s[2][2], s[2][3]), fmaxf(s[3][2], s[3][3])));
                        mx0 = fmaxf(mx0, fmaxf(s[4][0], s[4][1])); mx1 = fmaxf(mx1, fmaxf(s[4][2], s[4][3]));
                    }
#pragma unroll
                    for (int o = 1; o < 4; o <<= 1) { const float2 z = shfl2(mx0, mx1, o); mx0 = fmaxf(mx0, z.x); mx1 = fmaxf(mx1, z.y); }
                    mx0 *= -SC; mx1 *= -SC;
                    float l[4] = {0, 0, 0, 0};
                    uint32_t p[10];
#pragma unroll
                    for (int n = 0; n < 5; n++) {
                        const float e0 = ex2(fmaf(s[n][0], SC, mx0)), e1 = ex2(fmaf(s[n][1], SC, mx0));
                        const float e2 = ex2(fmaf(s[n][2], SC, mx1)), e3 = ex2(fmaf(s[n][3], SC, mx1));
                        p[2 * n] = pk(e0, e1); p[2 * n + 1] = pk(e2, e3);
                        mma8(l, p[2 * n], p[2 * n + 1], 0x3f803f80);
                    }
#pragma unroll
                    for (int m = 0; m < 3; m++) vm[m] = lds64(sb + O_VM + (3 * r + m) * 512 + l16 + L * 8);
                    sched_fence(gridDim.y, 5);
                    const float l0 = rcp(l[0]), l1 = rcp(l[2]);
                    float o[6][4];
#pragma unroll
                    for (int m = 0; m < 6; m++) o[m][0] = o[m][1] = o[m][2] = o[m][3] = 0.f;
#pragma unroll
                    for (int m = 0; m < 3; m++) { mma8(o[2 * m], p[0], p[1], v0[m].x); mma8(o[2 * m + 1], p[0], p[1], v0[m].y); }
#pragma unroll
                    for (int m = 0; m < 3; m++) { mma8(o[2 * m], p[2], p[3], v0[m].z); mma8(o[2 * m + 1], p[2], p[3], v0[m].w); v1[m] = lds128(vad + m * 2048 + 512); }
#pragma unroll
                    for (int m = 0; m < 3; m++) { mma8(o[2 * m], p[8], p[9], vm[m].x); mma8(o[2 * m + 1], p[8], p[9], vm[m].y); }
#pragma unroll
                    for (int m = 0; m < 3; m++) { mma8(o[2 * m], p[4], p[5], v1[m].x); mma8(o[2 * m + 1], p[4], p[5], v1[m].y); }
#pragma unroll
                    for (int m = 0; m < 3; m++) { mma8(o[2 * m], p[6], p[7], v1[m].z); mma8(o[2 * m + 1], p[6], p[7], v1[m].w); }
                    sched_fence(gridDim.y, 8);
                    if (t + 1 < NT) bar_arrive(11, 384);
#pragma unroll
                    for (int m = 0; m < 3; m++)
                        sts128(sb + O_OS + warp * 512 + m * 2048 + l16, (pk(o[2 * m][0] * l0, o[2 * m][1] * l0) & ~1u) | otag, pk(o[2 * m][2] * l1, o[2 * m][3] * l1),
                               pk(o[2 * m + 1][0] * l0, o[2 * m + 1][1] * l0), pk(o[2 * m + 1][2] * l1, o[2 * m + 1][3] * l1));
                    TR(4);
                }
            }
            if (t + 1 >= NT) break;
            {
                float d[32];
                if (warp < 4) bar_sync(7, 256);
                else {
                    mbar_wait(bar + B_X, (t + 1) & 1);
                    if (t >= 0) bar_sync(NGAP > 0 ? 10 : 11, NGAP > 0 ? 256 : 384);
                }
                wg_fence();
                TR(6);
#pragma unroll
                for (int kk = 0; kk < 36; kk++) {
                    if (NGAP > 0 && kk == NGAP) asm volatile("{.reg .pred p; setp.ne.u32 p, %0, 0; @p bar.sync 11, 384;}" :: "r"((uint32_t)(warp >= 4 && t >= 0)) : "memory");
                    const uint64_t db = mkdesc(hlo + ((kk >> 2) * 8192 + (kk & 3) * 32) / 16, DESC_HI);
                    if (IS_SS(kk)) wgmma_ss64(d, mkdesc(wlo + (kk / SSP) * 256, 16), db, 1);
                    else wgmma_rs64(d, a[AI(kk)], a[AI(kk) + 1], a[AI(kk) + 2], a[AI(kk) + 3], db, kk > 0);
                }
                wg_commit();
                TR(5);
                mbar_wait(bar + B_WIN, (t + 1) & 1);
                wg_wait<0>();
                TR(7);
                mbar_arrive_all3(bar + B_XFREE, l16 >> 4);
                uint32_t p[16];
#pragma unroll
                for (int u = 0; u < 16; u++) p[u] = pk(d[2 * u], d[2 * u + 1]);
                if (kind == 2) {
#pragma unroll
                    for (int u = 0; u < 4; u++) sts128(adX + u * 512, p[4 * u], p[4 * u + 1], p[4 * u + 2], p[4 * u + 3]);
                } else {
#pragma unroll
                    for (int u = 0; u < 4; u++) stsm4t(adX + u * 512, p[4 * u], p[4 * u + 1], p[4 * u + 2], p[4 * u + 3]);
                }
                __syncwarp();
                asm volatile("{.reg .pred p; setp.eq.u32 p, %1, 0; @p mbarrier.arrive.shared.b64 _, [%0];}" :: "r"(bar + B_EP), "r"(l16) : "memory");
                TR(8);
            }
        }
        if (warp < 4) bar_arrive(7, 160); else if (NGAP > 0) bar_sync(10, 256);
        cluster_sync();
    } else {
        asm volatile("setmaxnreg.dec.sync.aligned.u32 " RW ";");
        const int w = warp - 8, t2 = tid - 256;
        if (t2 == 0) {
            mbar_init(bar + B_X, 1); mbar_init(bar + B_XFREE, 24); mbar_init(bar + B_WIN, 3);
            mbar_init(bar + B_VX, 1); mbar_init(bar + B_SM, 1); mbar_init(bar + B_ST, 1); mbar_init(bar + B_EP, 8);
            asm volatile("fence.mbarrier_init.release.cluster;" ::: "memory");
        }
        char* const ex = reinterpret_cast<char*>((reinterpret_cast<uintptr_t>(g_ex) + 0x1fffff) & ~(uintptr_t)0x1fffff);
        char* rbase = ex; uint32_t side = 0;
        {
            uint32_t m0[5][4];
#pragma unroll
            for (int i = 0; i < 5; i++) {
                const unsigned short* m = reinterpret_cast<const unsigned short*>(mem0) + min(i * 128 + t2, DM - 1);
#pragma unroll
                for (int j = 0; j < 4; j++) m0[i][j] = m[2 * j * DM] | (m[(2 * j + 1) * DM] << 16);
            }
            if (w == 3) { bar_sync(15, 288); cnt_add(g_cnt + C_W * 8, lane); TR1(1); }
            if (t2 >= 96 && t2 < 99 && PFON) prefetch_l2((t2 == 96 ? Wq : t2 == 97 ? Wk : Wv) + b * (6 * 4096), 6 * 8192);
            delay_until(t_start, DLYW);
#pragma unroll 4
            for (int i = t2; i < 128 * 24; i += 128) {
                const int e = (i >> 3) & 127, G = i >> 10, q = i & 7;
                cp16(sb + O_WO + G * 16384 + e * 128 + ((q ^ (e & 7) ^ ((h >> 1) & 1)) << 4), Wo + (size_t)(h * 128 + e) * DM + G * 192 + r * 64 + q * 8);
            }
            bar_sync(9, 384);
#pragma unroll
            for (int i = 0; i < 5; i++) {
                const int k = min(i * 128 + t2, DM - 1);
                const uint32_t ad = sb + O_MB + (k >> 3) * 256 + (k & 7) * 16;
                sts128(ad, m0[i][0], m0[i][1], m0[i][2], m0[i][3]); sts128(ad + 128, m0[i][0], m0[i][1], m0[i][2], m0[i][3]);
            }
            fence_async_smem();
        }
        auto arm = [&]() {
            const uint32_t ln = l16 >> 4;
            mbar_expect(bar + B_VX + (ln & 3) * 8, ln == 0 ? nv_remote * 2048 : ln == 1 ? nv_remote * 512 + 2560 : 8192, ln < 3);
        };
        if (w == 3) arm();
        cluster_sync();
        TR1(3);
        const int L = w >> 1, hf = w & 1;
        const uint32_t rd = hf ? roff1 : roff0;
        const uint32_t rzero = gridDim.y + 100;
#define WOAD (sb + O_WO + ((l16 & 0x100) << 2) + ((l16 & 0x70) << 3) + (((w * 32) | ((l16 >> 3) & 16)) ^ (l16 & 0x70)))

        auto fetch_tile = [&](int u) {
            const bool a0 = u < NSEG, a1 = u >= LAG;
            mbar_expect(bar + B_X, ((int)a0 + (int)a1) * 36864, l16 == 0);
            const uint32_t off = r * 24576 + (l16 << 9) + (a0 ? 0 : 4096);
            asm volatile("{.reg .pred p; setp.lt.u32 p, %5, %6;\n"
                "@p cp.async.bulk.shared::cluster.global.mbarrier::complete_tx::bytes.multicast::cluster [%0], [%1], %4, [%2], %3;}"
                :: "r"(sb + O_H + off), "l"(reinterpret_cast<const char*>(g_xt + u * 4608) + off), "r"(bar + B_X), "h"((uint16_t)7),
                   "r"(a0 && a1 ? 24576 : 4096), "r"(l16), "r"(a0 && a1 ? 16 : 48) : "memory");
        };
        auto store_o = [&](int u) {
            asm volatile("{.reg .pred p; setp.eq.u32 p, %3, 0;\n"
                "@p cp.async.bulk.global.shared::cta.bulk_group [%0], [%1], %2;\n cp.async.bulk.commit_group;}"
                :: "l"(g_o + ((u & (RING - 1)) * 256 + h * 8 + 3 * r) * 128), "r"(sb + O_OS), "r"(nq * 2048), "r"(l16) : "memory");
            cnt_hint(g_cnt + (C_O + u * 8 + (h >> 2)) * 8, l16);
            TRG(u, 2);
        };
        if (w < 3) {
            bar_arrive(7, 256);
            bar_arrive(1 + w, 160); bar_arrive(12 + w, 160); if (w == 0 && XST < 3) bar_arrive(8, 64);
            if (w < 2) {
                unsigned* pp = reinterpret_cast<unsigned*>(ex + inbox_off(b) + 16384 + w * 4096 + 2048);
                uint32_t best = ~0u, v = 0;
                if (lane == 0) {
#pragma unroll 1
                    for (int i = 0; i < 6; i++) {
                        const uint32_t c0 = clk();
                        v = atomicAdd(pp + (v >> 31), 0);
                        asm volatile("" :: "r"(v) : "memory");
                        sts32(bar + 80, v);
                        best = min(best, clk() - c0);
                    }
                    sts32(bar + 72 + w * 4, best);
                }
            }
            bar_sync(15, 96);
            const uint32_t xs = PLACE ? lds32(bar + 76) < lds32(bar + 72) : 0, ep = EP;
            side = PLACE ? xs ^ page_par(inbox_off(b)) : 0;
            rbase = ex + inbox_off(b) + xs * 4096;
            const uint32_t inv = (ep * (NT - 1)) & 1;
#pragma unroll
            for (int i = 0; i < 4; i++) stg128(rbase + (w == 2 ? 16384 : w * 2048) + i * 512 + lane * 16, inv, 0, 0, 0);
            __threadfence();
            bar_sync(15, 96);
            if (t2 == 0) stg_word(g_side + b, (ep + 1) * 2 + xs, true);
            TR1(4);
        } else {
            mbar_arrive_all3(bar + B_WIN, l16 >> 4);
            cnt_wait(g_cnt + C_X * 8, 64 * (EP + 1)); fence_async_global();
            TRG(0, 0);
            fetch_tile(0);
            TRG(0, 1);
            mbar_wait(bar + B_X, 0);
            bar_arrive(7, 256);
        }
        cp_wait_all();
        bar_sync(6, 128);
        uint32_t poff;
        {
            const int rb = r * 32 + w * 8 + (lane >> 2);
            const uint32_t want = EP + 1;
            uint32_t v;
            for (int n = 0; __any_sync(~0u, ((v = ldg_word(g_side + rb)) >> 1) != want); n++) fault_if(n > POLL_LIMIT, n);
            __threadfence();
            poff = inbox_off(rb) + (v & 1) * 4096 + h * 64 + (lane & 3) * 16;
        }
        side = __shfl_sync(~0u, side, 0);
        const uint32_t roff = __shfl_sync(~0u, (uint32_t)(rbase - ex), 0) + (w == 2 ? 16384 : (w & 1) * 2048);
        bool late = true;
        uint4 a0[8];
#pragma unroll
        for (int kk = 0; kk < 8; kk++) a0[kk] = ldsm4t(WOAD + kk * 2048);
#pragma unroll 1
        for (int t = 0;; t++) {
            TR_ON(t);
            OPQ();
            mbar_wait(bar + B_EP, t & 1);
            if (w == 3) {
                fence_async_smem();
                const uint32_t ad = sb + O_VX + r * 4096;
                asm volatile("{.reg .pred p; setp.eq.u32 p, %5, 0;\n"
                    "@p cp.async.bulk.shared::cluster.shared::cta.mbarrier::complete_tx::bytes [%0], [%2], %6, [%3];\n"
                    "@p cp.async.bulk.shared::cluster.shared::cta.mbarrier::complete_tx::bytes [%1], [%2], %6, [%4];}"
                    :: "r"(ad + roff0), "r"(ad + roff1), "r"(ad), "r"(bar + B_VX + roff0), "r"(bar + B_VX + roff1), "r"(l16), "r"(16384 - 4096 * nq) : "memory");
                if (XST < 3) bar_sync(8, 64);
                TR(6);
                if (t > 0 && XST < 4) store_o(t - 1);
                if (late) { cnt_wait(g_cnt + (C_X + t + 1) * 8, 64 * (EP + 1)); fence_async_global(); }
                TRG(t + 1, 0);
                mbar_wait(bar + B_XFREE, t & 1);
                if (t + 1 < NT) { fetch_tile(t + 1); TRG(t + 1, 1); }
                TR(7);
            }
            uint4 kx[3][2], vx[4][2];
            const uint32_t lp = LSWAP;
#pragma unroll
            for (int m = 0; m < 3; m++) {
                kx[m][0] = ldsm4(sb + O_KX + m * 2048 + L * 1024 + lp);
                kx[m][1] = ldsm4(sb + O_KX + m * 2048 + L * 1024 + 512 + lp);
            }
            if (w == 3) asm volatile("cp.async.bulk.wait_group.read 0;" ::: "memory");
            mbar_wait(bar + B_VX, t & 1);
            TR(0);
            bar_sync(4, 384);
            float s0[4] = {0, 0, 0, 0}, s1[4] = {0, 0, 0, 0}, sm[4] = {0, 0, 0, 0};
            {
                const uint4 q01 = ldsm4(sb + O_QM + L * 256 + l16 + (l16 & 256));
                const uint2 q2 = ldsm2(sb + O_QM + 1024 + L * 256 + l16);
                uint4 km_[3];
#pragma unroll
                for (int m = 0; m < 3; m++) km_[m] = ldsm4(sb + O_KM + m * 512 + (lp ^ (L << 8)));
                bar_arrive(5, 256);
                mma16(s0, kx[0][0].x, kx[0][0].y, kx[0][0].z, kx[0][0].w, q01.x, q01.y);
                mma16(s1, kx[0][1].x, kx[0][1].y, kx[0][1].z, kx[0][1].w, q01.x, q01.y);
                mma16(sm, km_[0].x, km_[0].y, km_[0].z, km_[0].w, q01.x, q01.y);
                mma16(s0, kx[1][0].x, kx[1][0].y, kx[1][0].z, kx[1][0].w, q01.z, q01.w);
                mma16(s1, kx[1][1].x, kx[1][1].y, kx[1][1].z, kx[1][1].w, q01.z, q01.w);
                mma16(sm, km_[1].x, km_[1].y, km_[1].z, km_[1].w, q01.z, q01.w);
                mma16(s0, kx[2][0].x, kx[2][0].y, kx[2][0].z, kx[2][0].w, q2.x, q2.y);
                mma16(s1, kx[2][1].x, kx[2][1].y, kx[2][1].z, kx[2][1].w, q2.x, q2.y);
                mma16(sm, km_[2].x, km_[2].y, km_[2].z, km_[2].w, q2.x, q2.y);
                const uint32_t ad = sb + O_SM + (1 - hf) * 1280 + L * 640 + rd;
                sta128(ad + l16, pk(s0[0], s0[1]), pk(s0[2], s0[3]), pk(s1[0], s1[1]), pk(s1[2], s1[3]), bar + B_SM + rd);
                sta32(ad + 512 + (l16 >> 2), pk(sm[0], sm[1]), bar + B_SM + rd);
            }
            TR(1);
            if (t + 1 == NT) break;
#pragma unroll
            for (int m = 0; m < 8; m++) vx[m >> 1][m & 1] = lds128(sb + O_VX + (hf * 4 + (m >> 1)) * 2048 + L * 1024 + (m & 1) * 512 + l16);
            const uint32_t tag = (t + EP * (NT - 1) + 1) & 1;
            uint32_t ident = IDENT;
            asm volatile("" : "+r"(ident));
            mbar_wait(bar + B_SM, t & 1);
            TR(2);
            {
                const uint32_t ad = sb + O_SM + L * 640;
                const uint4 u = lds128(ad + l16), v = lds128(ad + 1280 + l16);
                const uint32_t x = lds32(ad + 512 + (l16 >> 2)), y = lds32(ad + 1280 + 512 + (l16 >> 2));
                mma8(s0, u.x, u.y, ident); mma8(s1, u.z, u.w, ident); mma8(s0, v.x, v.y, ident); mma8(s1, v.z, v.w, ident);
                sm[0] += bf_lo(x) + bf_lo(y); sm[1] += bf_hi(x) + bf_hi(y);
            }
            uint2 vm[4];
#pragma unroll
            for (int m = 0; m < 4; m++) vm[m] = lds64(sb + O_VM + (hf * 4 + m) * 512 + l16 + L * 8);
            float mx0 = fmaxf(fmaxf(fmaxf(s0[0], s0[2]), fmaxf(s1[0], s1[2])), sm[0]);
            float mx1 = fmaxf(fmaxf(fmaxf(s0[1], s0[3]), fmaxf(s1[1], s1[3])), sm[1]);
#pragma unroll
            for (int o = 4; o < 32; o <<= 1) { mx0 = fmaxf(mx0, __shfl_xor_sync(~0u, mx0, o)); mx1 = fmaxf(mx1, __shfl_xor_sync(~0u, mx1, o)); }
            mx0 *= -SC; mx1 *= -SC;
            s0[0] = ex2(fmaf(s0[0], SC, mx0)); s0[1] = ex2(fmaf(s0[1], SC, mx1));
            s0[2] = ex2(fmaf(s0[2], SC, mx0)); s0[3] = ex2(fmaf(s0[3], SC, mx1));
            const uint32_t pb0 = movm(pk(s0[0], s0[1])), pb1 = movm(pk(s0[2], s0[3]));
            s1[0] = ex2(fmaf(s1[0], SC, mx0)); s1[1] = ex2(fmaf(s1[1], SC, mx1));
            s1[2] = ex2(fmaf(s1[2], SC, mx0)); s1[3] = ex2(fmaf(s1[3], SC, mx1));
            const uint32_t pb2 = movm(pk(s1[0], s1[1])), pb3 = movm(pk(s1[2], s1[3]));
            sm[0] = ex2(fmaf(sm[0], SC, mx0)); sm[1] = ex2(fmaf(sm[1], SC, mx1));
            const uint32_t pm = movm(pk(sm[0], sm[1]));
            float o[4][4], l[4] = {0, 0, 0, 0};
            const uint32_t one = 0x3f803f80;
            mma8(l, one, one, pb0); mma8(l, one, one, pb1);
#pragma unroll
            for (int m = 0; m < 4; m++) { o[m][0] = o[m][1] = o[m][2] = o[m][3] = 0.f; mma16(o[m], vx[m][0].x, vx[m][0].y, vx[m][0].z, vx[m][0].w, pb0, pb1); }
            mma8(l, one, one, pb2); mma8(l, one, one, pb3);
#pragma unroll
            for (int m = 0; m < 4; m++) mma16(o[m], vx[m][1].x, vx[m][1].y, vx[m][1].z, vx[m][1].w, pb2, pb3);
            mma8(l, one, one, pm);
#pragma unroll
            for (int m = 0; m < 4; m++) mma8(o[m], vm[m].x, vm[m].y, pm);
            const float l0 = rcp(l[0]), l1 = rcp(l[1]);
#pragma unroll
            for (int m = 0; m < 4; m += 2)
                stsm4t(sb + O_OX + (hf * 4 + m) * 512 + (L ^ ((h >> 2) & 1)) * 256   + ((l16 & 0x100) << 1) + (l16 & 0xf0),
                       pk(o[m][0] * l0, o[m][1] * l1), pk(o[m][2] * l0, o[m][3] * l1), pk(o[m + 1][0] * l0, o[m + 1][1] * l1), pk(o[m + 1][2] * l0, o[m + 1][3] * l1));
            TR(3);
            char* const pdst = ex + poff;
            const char* const rsrc = ex + roff + l16;
            uint4 v[4] = {};
            bar_sync(6, 128);
            {
                uint4 bo[8], a1[8], z;
                const uint32_t wad = WOAD;
#pragma unroll
                for (int kk = 0; kk < 8; kk++) bo[kk] = ldsm4(sb + O_OX + kk * 512 + l16);
#pragma unroll
                for (int G = 0; G < 3; G++) {
                    float e[4][4];
#pragma unroll
                    for (int q = 0; q < 4; q++) e[q][0] = e[q][1] = e[q][2] = e[q][3] = 0.f;
#pragma unroll
                    for (int kk = 0; kk < 8; kk++) {
                        const uint4 f = G == 0 ? a0[kk] : a1[kk];
                        mma16(e[(kk & 1) * 2], f.x, f.y, f.z, f.w, bo[kk].x, bo[kk].y);
                        mma16(e[(kk & 1) * 2 + 1], f.x, f.y, f.z, f.w, bo[kk].z, bo[kk].w);
                        if (G == 2 && kk == EK) {
#pragma unroll
                            for (int i = 0; i < 4; i++) { v[i].x = ~tag; ldg_pkt_if(v[i], rsrc + i * 512, w < EARLY); }
                            sched_fence(rzero, 5);
                            bar_arrive(11, 384);
                        }
                        if (G == 1) a1[kk] = ldsm4t(wad + 32768 + kk * 2048);
                        if (G == 0 && kk == FK) {
                            sched_fence(rzero, 2);
#pragma unroll
                            for (int j = 0; j < 8; j++) a1[j] = ldsm4t(wad + 16384 + j * 2048);
                        }
                    }
                    if (G > 0) asm volatile("{.reg .pred p; setp.eq.u32 p, %5, 0; @p st.shared.v4.u32 [%0], {%1,%2,%3,%4};}" :: "r"(__float_as_uint(e[0][0])), "r"(z.x), "r"(z.y), "r"(z.z), "r"(z.w), "r"(rzero));
                    z = make_uint4((pk(e[0][0] + e[2][0], e[0][1] + e[2][1]) & ~1u) | tag, pk(e[0][2] + e[2][2], e[0][3] + e[2][3]),
                                   pk(e[1][0] + e[3][0], e[1][1] + e[3][1]), pk(e[1][2] + e[3][2], e[1][3] + e[3][3]));
                    stg_pkt(pdst + (G == 2 ? 16384 : G * 2048), z.x, z.y, z.z, z.w);
                    if (G == 0) { TR(9); TRD(t, 0); }
                    if (G < 2) sched_fence(rzero, 3 + G);
                }
            }
            TR(4);
            if (w < 3) {
                bar_arrive(7, 256);
                OPQ();
                const uint32_t tagm = tag;
                uint32_t m0v = 0;
                if (t + 1 <= LAG) {
                    const unsigned short* m = reinterpret_cast<const unsigned short*>(mem0) + ((l16 >> 3) & 6) * DM + 192 * w + 16 * (b >> 3) + (b & 7) + ((l16 >> 4) & 8);
                    m0v = m[0] | (m[DM] << 16);
                }
                delay(DLY1);
                for (int n = 0; __any_sync(~0u, lop_bad(lop_bad(0, v[0].x, v[1].x, tagm), v[2].x, v[3].x, tagm) & 1); n++) {
#pragma unroll
                    for (int i = 0; i < 4; i++) v[i] = ldg_pkt(rsrc + i * 512);
                    fault_if(n > POLL_LIMIT, n);
                }
                TR(5); TRD(t, 1);
                float s[8];
                s[4] = (bf_lo(v[0].z) + bf_lo(v[1].z)) + (bf_lo(v[2].z) + bf_lo(v[3].z)); s[5] = (bf_hi(v[0].z) + bf_hi(v[1].z)) + (bf_hi(v[2].z) + bf_hi(v[3].z));
                s[6] = (bf_lo(v[0].w) + bf_lo(v[1].w)) + (bf_lo(v[2].w) + bf_lo(v[3].w)); s[7] = (bf_hi(v[0].w) + bf_hi(v[1].w)) + (bf_hi(v[2].w) + bf_hi(v[3].w));
                s[2] = (bf_lo(v[0].y) + bf_lo(v[1].y)) + (bf_lo(v[2].y) + bf_lo(v[3].y)); s[3] = (bf_hi(v[0].y) + bf_hi(v[1].y)) + (bf_hi(v[2].y) + bf_hi(v[3].y));
                s[0] = (bf_lo(v[0].x) + bf_lo(v[1].x)) + (bf_lo(v[2].x) + bf_lo(v[3].x)); s[1] = (bf_hi(v[0].x) + bf_hi(v[1].x)) + (bf_hi(v[2].x) + bf_hi(v[3].x));
#pragma unroll
                for (int j = 0; j < 4; j++) s[j] += __shfl_xor_sync(~0u, s[j + 4], 16);
#pragma unroll
                for (int j = 0; j < 2; j++) s[j] += __shfl_xor_sync(~0u, s[j + 2], 8);
#pragma unroll
                for (int j = 0; j < 2; j++) s[j] += __shfl_xor_sync(~0u, s[j], 4);
                char* const mem_w = ex + mem_off(w, 0);
                uint32_t res = t + 1 <= LAG && l16 >= 256 ? m0v : pk(s[0], s[1]);
                if ((l16 & 48) == 0) res = (res & ~1u) | tag;
                stg_word(mem_w + (mem_off(0, b >> 3) - mem_off(0, 0)) + (b & 7) * 16 + (((l16 & 64) << 6) + ((l16 & 128) << 1) + ((l16 & 256) >> 1) + ((l16 >> 2) & 12)), res, true);
                if (w + 5 == XST) bar_arrive(8, 64);
                TR(6); TRD(t, 2);
                delay(DLY2);
                const char* src = mem_w + (side ^ page_par(0x180000)) * 4096 + l16;
                const uint32_t gdst = sb + O_MB + w * 6144 + l16;
                uint4 x[12];
#pragma unroll
                for (int i = 0; i < 12; i++) x[i] = ldg_pkt(src + (mem_off(0, i) - mem_off(0, 0)));
                for (int n = 0;; n++) {
                    uint32_t bad = 0;
#pragma unroll
                    for (int i = 0; i < 12; i += 2) bad = lop_bad(bad, x[i].x, x[i + 1].x, tagm);
                    if (!__any_sync(~0u, bad & 1)) break;
#pragma unroll
                    for (int i = 0; i < 12; i++) ldg_pkt_retry(x[i], src + (mem_off(0, i) - mem_off(0, 0)), tagm);
                    fault_if(n > POLL_LIMIT, n);
                }
#pragma unroll
                for (int i = 0; i < 12; i++) sts128(gdst + i * 512, x[i].x, x[i].y, x[i].z, x[i].w);
                TR(7); TRD(t, 3);
                fence_async_smem();
                bar_arrive(12 + w, 160);
                bar_arrive(1 + w, 160);
                if (w == XST) bar_arrive(8, 64);
                TR(8);
            } else {
                mbar_wait(bar + B_X, (t + 1) & 1);
                bar_sync(7, 256);
                fence_async_smem();
                arm();
                __syncwarp();
                mbar_arrive_all3(bar + B_WIN, l16 >> 4);
                if (XST > 4) bar_sync(8, 64);
                if (XST >= 4) { delay(DLYO); store_o(t); }
                late = t + 2 < NT && cnt_poll(g_cnt + (C_X + t + 2) * 8, 64 * (EP + 1), bar + B_EP, (t + 1) & 1);
                fence_async_global();
                TR(5);
            }
        }
        if (w == 3) { bar_sync(7, 160); fence_async_smem(); store_o(NT - 1); asm volatile("cp.async.bulk.wait_group 0;" ::: "memory"); }
        cluster_sync();
    }
    TR_DUMP(b);
}

#define VG 12
#define HB 3
#define HA 2
#define HW 0
namespace ka {
constexpr int O_WA = 196608;
constexpr int A_KB = 21504;
constexpr int O_RING = 194560;
constexpr int O_BAR = 230400;
constexpr int SMEM = O_BAR + 256 + 1024;
constexpr float SC = 0.23570226039551584f * 1.4426950408889634f;
}

template <int NP, int KB = 4096>
DEVI void row_task(const uint4* res, const uint4* part, uint4* xout, char* img, int pos, int lane, uint32_t tag) {
    const bool on = lane < 24;
    const int ln = on ? lane : 0;
    uint4 rv[3], pv[NP > 0 ? NP * 3 : 1];
#pragma unroll
    for (int i = 0; i < 3; i++) rv[i] = ldg128(res + i * 24 + ln);
#pragma unroll
    for (int i = 0; i < NP * 3; i++) pv[i] = ldg_pkt(part + i * 24 + ln);
    if (NP > 0) validate<NP * 3>(pv, part + ln, 384, tag);
#pragma unroll
    for (int q = 0; q < NP * 3 / 2; q++) {
        const uint4 y = pv[q + NP * 3 / 2];
        pv[q] = make_uint4(add2(pv[q].x, y.x), add2(pv[q].y, y.y), add2(pv[q].z, y.z), add2(pv[q].w, y.w));
    }
    float x[24];
#pragma unroll
    for (int i = 0; i < 3; i++) {
        x[8 * i] = bf_lo(rv[i].x); x[8 * i + 1] = bf_hi(rv[i].x); x[8 * i + 2] = bf_lo(rv[i].y); x[8 * i + 3] = bf_hi(rv[i].y);
        x[8 * i + 4] = bf_lo(rv[i].z); x[8 * i + 5] = bf_hi(rv[i].z); x[8 * i + 6] = bf_lo(rv[i].w); x[8 * i + 7] = bf_hi(rv[i].w);
    }
    if (NP > 0) {
#pragma unroll
        for (int q = 0; q < NP * 3 / 2; q++) {
            const int i = q % 3;
            x[8 * i] += bf_lo(pv[q].x); x[8 * i + 1] += bf_hi(pv[q].x); x[8 * i + 2] += bf_lo(pv[q].y); x[8 * i + 3] += bf_hi(pv[q].y);
            x[8 * i + 4] += bf_lo(pv[q].z); x[8 * i + 5] += bf_hi(pv[q].z); x[8 * i + 6] += bf_lo(pv[q].w); x[8 * i + 7] += bf_hi(pv[q].w);
        }
#pragma unroll
        for (int i = 0; i < 3; i++) {
            uint32_t w[4];
#pragma unroll
            for (int j = 0; j < 4; j++) { w[j] = pk(x[8 * i + 2 * j], x[8 * i + 2 * j + 1]); x[8 * i + 2 * j] = bf_lo(w[j]); x[8 * i + 2 * j + 1] = bf_hi(w[j]); }
            stg128p(xout + i * 24 + ln, w[0], w[1], w[2], w[3], on);
        }
    }
    if (img) {
        float s = 0.f;
#pragma unroll
        for (int j = 0; j < 24; j++) s += x[j];
        if (!on) s = 0.f;
#pragma unroll
        for (int o = 1; o < 32; o <<= 1) s += __shfl_xor_sync(~0u, s, o);
        const float mean = s * (1.f / DM);
        float v = 0.f;
#pragma unroll
        for (int j = 0; j < 24; j++) { x[j] -= mean; v = fmaf(x[j], x[j], v); }
        if (!on) v = 0.f;
#pragma unroll
        for (int o = 1; o < 32; o <<= 1) v += __shfl_xor_sync(~0u, v, o);
        const float rs = rsqrtf(v * (1.f / DM) + 1e-5f);
        char* dst = img + (ln >> 3) * KB + pos * 128 + (((ln ^ pos) & 7) << 4);
#pragma unroll
        for (int i = 0; i < 3; i++)
            stg128p(dst + i * (3 * KB), pk(x[8 * i] * rs, x[8 * i + 1] * rs), pk(x[8 * i + 2] * rs, x[8 * i + 3] * rs),
                    pk(x[8 * i + 4] * rs, x[8 * i + 5] * rs), pk(x[8 * i + 6] * rs, x[8 * i + 7] * rs), on);
    }
}

DEVI void rows_a(const uint4* xin, int f, int i, int lane, uint32_t ep, int warp) {
    for (int u = 0; u < LAG; u++) cnt_hint(g_cnt + (C_X + u + (f ? 0 : NSEG)) * 8, lane);
#pragma unroll 1
    for (int seg = 0; seg < NSEG; seg++) {
        const int j = seg + f * LAGA, u = seg + f * LAG, row = seg * 32 + i;
        hint_wait(g_cnt + (C_WA + j * 4 + f * 2 + (i & 1)) * 8, 24 * (ep + 1));
        TRG(u, 0);
        row_task<4, 8192>((f ? g_x + 2048 * 72 : xin) + row * 72, g_pa + ((j & (RING - 1)) * 64 + f * 32 + i) * 288,
                    g_x + (f * 4096 + row) * 72, reinterpret_cast<char*>(g_xt + u * 4608 + f * 256), i, lane, ring_tag<NTA>(j, ep));
        TRG(u, 1);
        cnt_add(g_cnt + (C_X + u) * 8, lane);
        TRG(u, 2);
    }
}

__global__ void __launch_bounds__(384, 1)
k_aux(const __nv_bfloat16* __restrict__ x0, const __nv_bfloat16* __restrict__ wqkv, const __nv_bfloat16* __restrict__ wo,
      const __nv_bfloat16* __restrict__ Wo, __nv_bfloat16* __restrict__ out) {
    using namespace ka;
    extern __shared__ unsigned char smem_raw[];
    const uint32_t sb = (smem_u32(smem_raw) + 1023) & ~1023u;
    const int tid = threadIdx.x, lane = tid & 31, warp = __shfl_sync(~0u, tid >> 5, 0), g = lane >> 2, c = lane & 3;
    const int b = blockIdx.x;
    const uint32_t bar = sb + O_BAR;
    const uint32_t ep = __shfl_sync(~0u, ldg32(&g_epoch), 0);

    TRG(79, 0);
    const uint4* xin = reinterpret_cast<const uint4*>(x0);
    if (warp >= 8 || b == 35) {
        asm volatile("setmaxnreg.dec.sync.aligned.u32 128;");
        const int rw = b < 24 ? (warp - 8) * 24 + b : b < 35 ? (warp - 8) * 11 + b - 24 : 96 + 2 * warp;
        if (b < 24 || b == 35) {
#pragma unroll 1
            for (int row = rw; row < 2048; row += (row & 1) ? 23 : 1) {
                if (lane == 0 && b == 35 && row < 2024) prefetch_l2(xin + (row + 24) * 72, 1152);
                row_task<0>(xin + row * 72, nullptr, nullptr, reinterpret_cast<char*>(g_xa + (row >> 5) * 4608), (row & 1) * 16 + ((row & 31) >> 1), lane, 0);
                if (b < 24) { cnt_add(g_cnt + (C_N0 + (row >> 5)) * 8, lane); break; }
                if (row & 1) cnt_add<2>(g_cnt + (C_N0 + (row >> 5)) * 8, lane);
            }
        }
        if (rw < 32) {
            const int f = b < 24, i = rw;
#pragma unroll 1
            for (int seg = 0; seg < NSEG; seg++) {
                const int u = seg + f * LAG, row = seg * 32 + i;
                hint_wait(g_cnt + (C_WB + u * 4 + f * 2 + (i >> 4)) * 8, 24 * (ep + 1));
                TRG(u, 0);
                row_task<8>(g_x + (f * 4096 + row) * 72, g_pb + ((u & (RING - 1)) * 64 + f * 32 + i) * 576,
                            f ? reinterpret_cast<uint4*>(out) + row * 72 : g_x + (2048 + row) * 72,
                            f ? nullptr : reinterpret_cast<char*>(g_xa + (seg + LAGA) * 4608 + 2304), (i & 1) * 16 + (i >> 1), lane, ring_tag(u, ep));
                TRG(u, 1);
                cnt_add(g_cnt + (C_RB + f * NSEG + seg) * 8, lane);
                TRG(u, 2);
            }
            if (f && rw == 31) {
                asm volatile("griddepcontrol.wait;" ::: "memory");
                if (lane == 0) g_epoch = ep + 1;
            }
        } else if (rw < 64 && b < 24) rows_a(xin, 0, rw - 32, lane, ep, warp);
        return;
    }

    if (b < 24) {
        if (warp >= 4) {
            const int kq = b / 6, nq = b % 6;
            uint4 v[17];
#pragma unroll
            for (int q = 0; q < 17; q++) {
                const int it = q * 4 + warp - 4, kr = (it / 3) * 8 + g, s = kq * 11 + (kr >> 4), a = s >> 2, j = s & 3, e = kr & 15;
                const int head = 3 * a + (j < 3 ? j : e >> 1), row = head * 18 + (j < 3 ? e : 16 + (e & 1));
                v[q] = make_uint4(0, 0, 0, 0);
                if (it < 66 && head < 32 && (j < 3 || e < 6)) v[q] = *reinterpret_cast<const uint4*>(wo + row * DM + nq * 96 + (it % 3) * 32 + c * 8);
            }
#pragma unroll
            for (int q = 0; q < 17; q++) {
                const int it = q * 4 + warp - 4;
                const uint32_t ad = sb + O_WA + (it % 3) * 4 * 2816 + (it / 3) * 128 + lane * 4;
                if (it < 66) { sts32(ad, v[q].x); sts32(ad + 2816, v[q].y); sts32(ad + 2 * 2816, v[q].z); sts32(ad + 3 * 2816, v[q].w); }
            }
        } else {
            const int kg = b / 3, ng = b % 3;
            delay(DLYB);
#pragma unroll 1
            for (int bt = 0; bt < 4; bt++) {
                uint4 v[24];
#pragma unroll
                for (int q = 0; q < 24; q++)
                    v[q] = *reinterpret_cast<const uint4*>(Wo + (size_t)(kg * 512 + (bt * 4 + q / 6) * 32 + warp * 8 + g) * DM + ng * 192 + (q % 6) * 32 + c * 8);
#pragma unroll
                for (int q = 0; q < 24; q++) {
                    const uint32_t ad = sb + (q % 6) * 4 * 8192 + ((bt * 4 + q / 6) * 4 + warp) * 128 + lane * 4;
                    sts32(ad, v[q].x); sts32(ad + 8192, v[q].y); sts32(ad + 2 * 8192, v[q].z); sts32(ad + 3 * 8192, v[q].w);
                }
            }
        }
        fence_async_smem();
        bar_sync(2 + (warp >> 2), 128);
    } else {
        for (int i = tid; i < 2048; i += 256) sts128(sb + O_RING + i * 16, 0, 0, 0, 0);
        if (tid < 17) mbar_init(bar + tid * 8, tid >= 4 && tid < 8 ? 4 : 1);
        fence_async_smem();
        bar_sync(1, 256);
    }
    TRG(79, 1);
    const int wq = warp & 3;

    if (warp < 4) {
        asm volatile("setmaxnreg.inc.sync.aligned.u32 256;");
        if (b < 24) {
            const int kg = b / 3, ng = b % 3;
            const uint32_t blo = ((sb >> 4) & 0x3fff) | (8u << 16);
            uint4 a[32];
            bool pre = false;
#pragma unroll 1
            for (int u = 0; u < NT; u++) {
                const uint32_t tag = ring_tag(u, ep);
                const uint4* src = g_o + (((u & (RING - 1)) * 256 + kg * 32) * 4 + wq) * 32 + lane;
                if (!pre) {
                    hint_wait(g_cnt + (C_O + u * 8 + kg) * 8, 12 * (ep + 1));
#pragma unroll
                    for (int i = 0; i < VG; i++) a[i] = ldg_pkt(src + i * 128);
                }
                TRG(u, 0);
                float d[96];
                validate<VG>(a, src, 2048, tag);
#pragma unroll
                for (int i = VG; i < 32; i++) a[i] = ldg_pkt(src + i * 128);
                wg_fence();
#pragma unroll
                for (int i = 0; i < 32; i++) {
                    if (i == VG) { validate<32 - VG>(a + VG, src + VG * 128, 2048, tag); wg_fence(); }
                    wgmma_rs192t(d, a[i].x, a[i].y, a[i].z, a[i].w, mkdesc(blo + i * 16, 512), i > 0);
                    if (i == 23 || i == 31) wg_commit();
                }
                wg_wait<1>();
                pre = u + 1 < NT && __all_sync(~0u, ldg_word(g_cnt + (C_O + (u + 1) * 8 + kg) * 8) >= 12 * (ep + 1));
                if (pre) {
                    const uint4* nx = g_o + ((((u + 1) & (RING - 1)) * 256 + kg * 32) * 4 + wq) * 32 + lane;
#pragma unroll
                    for (int i = 0; i < VG; i++) a[i] = ldg_pkt(nx + i * 128);
                }
                wg_wait<0>();
                TRG(u, 1);
                uint4* dst = g_pb + (((u & (RING - 1)) * 64 + wq * 16 + g) * 8 + kg) * 72 + ng * 24 + c;
#pragma unroll
                for (int m = 0; m < 6; m++) {
                    if (m == HB) cnt_hint(g_cnt + (C_WB + u * 4 + wq) * 8, lane);
                    stg128(dst + 4 * m, (pk(d[16 * m], d[16 * m + 1]) & ~1u) | tag, pk(d[16 * m + 4], d[16 * m + 5]), pk(d[16 * m + 8], d[16 * m + 9]), pk(d[16 * m + 12], d[16 * m + 13]));
                    stg128(dst + 4 * m + 8 * 576, (pk(d[16 * m + 2], d[16 * m + 3]) & ~1u) | tag, pk(d[16 * m + 6], d[16 * m + 7]), pk(d[16 * m + 10], d[16 * m + 11]), pk(d[16 * m + 14], d[16 * m + 15]));
                }
                TRG(u, 3);
            }
        } else {
            const int a = b - 24, f = wq >> 1;
            const uint32_t blo = ((sb >> 4) & 0x3fff) | (8u << 16), alo = (((sb + O_RING) >> 4) & 0x3fff) | (1u << 16);
            const bool m0 = 2 * c <= g, m1 = 2 * c + 1 <= g;
            const uint32_t M = (m0 ? 0xffffu : 0u) | (m1 ? 0xffff0000u : 0u);
            uint32_t kh[7], vh[7];
#pragma unroll
            for (int i = 0; i < 7; i++) kh[i] = vh[i] = 0;
            int it = 0;
#pragma unroll 1
            for (int u = 0; u < NTA; u++) {
                float d[84];
#pragma unroll 1
                for (int kb = 0; kb < 9; kb++, it++) {
                    mbar_wait(bar + (it & 3) * 8, (it >> 2) & 1);
                    if (u == 0) mbar_wait(bar + 64 + kb * 8, 0);
                    if (kb == 0) TRG(u, 0);
                    wg_fence();
#pragma unroll
                    for (int q = 0; q < 4; q++)
                        wgmma_ss168t(d, mkdesc(alo + (it & 3) * 512 + q * 2, km::DESC_HI), mkdesc(blo + kb * (A_KB >> 4) + q * 16, 64), kb + q > 0);
                    wg_commit();
                    wg_wait<1>();
                    mbar_arrive(bar + 32 + ((it - 1) & 3) * 8, lane == 0 && kb > 0);
                }
                wg_wait<0>();
                mbar_arrive(bar + 32 + ((it - 1) & 3) * 8, lane == 0);
                TRG(u, 1);
                const bool first = u == f * LAGA;
                const uint32_t tag = ring_tag<NTA>(u, ep);
                const uint32_t qt0 = pk(d[72], d[73]), qt1 = pk(d[74], d[75]), kt0 = pk(d[76], d[77]), kt1 = pk(d[78], d[79]);
                const uint32_t vt0 = movm(pk(d[80], d[81])), vt1 = movm(pk(d[82], d[83]));
                float ot[4] = {0, 0, 0, 0};
                uint4* dst = g_oa + (((u & (RING - 1)) * 4 + wq) * 44 + a * 4) * 32 + lane;
#pragma unroll
                for (int h = 0; h < 3; h++) {
                    const float* q = d + 8 * h; const float* k = d + 24 + 8 * h; const float* v = d + 48 + 8 * h;
                    const uint32_t q0 = pk(q[0], q[1]), q1 = pk(q[2], q[3]), q2 = pk(q[4], q[5]), q3 = pk(q[6], q[7]);
                    const uint32_t k0 = pk(k[0], k[1]), k1 = pk(k[4], k[5]), k2 = pk(k[2], k[3]), k3 = pk(k[6], k[7]);
                    const uint32_t v0 = movm(pk(v[0], v[1])), v1 = movm(pk(v[2], v[3])), v2 = movm(pk(v[4], v[5])), v3 = movm(pk(v[6], v[7]));
                    const uint32_t t0 = c == h ? qt0 : 0, t1 = c == h ? qt1 : 0;
                    float sp[4] = {0, 0, 0, 0}, sl[4] = {0, 0, 0, 0}, sh[4] = {0, 0, 0, 0};
                    mma16(sp, q0, q1, q2, q3, kh[2 * h], kh[2 * h + 1]); mma16(sl, q0, q1, q2, q3, k0, k1); mma16(sh, q0, q1, q2, q3, k2, k3);
                    mma8(sp, t0, t1, kh[6]); mma8(sl, t0, t1, kt0); mma8(sh, t0, t1, kt1);
                    float x0_ = m0 ? sl[0] : first ? -INFINITY : sp[0], x1_ = m1 ? sl[1] : first ? -INFINITY : sp[1];
                    float y0_ = m0 ? sh[2] : sl[2], y1_ = m1 ? sh[3] : sl[3];
                    float mx = fmaxf(x0_, x1_), my = fmaxf(y0_, y1_);
#pragma unroll
                    for (int o = 1; o < 4; o <<= 1) { mx = fmaxf(mx, __shfl_xor_sync(~0u, mx, o)); my = fmaxf(my, __shfl_xor_sync(~0u, my, o)); }
                    mx *= -SC; my *= -SC;
                    x0_ = ex2(fmaf(x0_, SC, mx)); x1_ = ex2(fmaf(x1_, SC, mx)); y0_ = ex2(fmaf(y0_, SC, my)); y1_ = ex2(fmaf(y1_, SC, my));
                    float lx = x0_ + x1_, ly = y0_ + y1_;
#pragma unroll
                    for (int o = 1; o < 4; o <<= 1) { lx += __shfl_xor_sync(~0u, lx, o); ly += __shfl_xor_sync(~0u, ly, o); }
                    lx = rcp(lx); ly = rcp(ly);
                    const uint32_t px = pk(x0_ * lx, x1_ * lx), py = pk(y0_ * ly, y1_ * ly);
                    const uint32_t hm = (g >> 1) == h ? ~0u : 0u;
                    float o0[4] = {0, 0, 0, 0}, o1[4] = {0, 0, 0, 0};
                    mma16(o0, px & M, py & ~M, 0, py & M, v0, v1); mma16(o1, px & M, py & ~M, 0, py & M, v2, v3);
                    mma16(ot, px & M, py & ~M, 0, py & M, vt0 & hm, vt1 & hm);
                    mma8(o0, px & ~M, 0, vh[2 * h]); mma8(o1, px & ~M, 0, vh[2 * h + 1]); mma8(ot, px & ~M, 0, vh[6] & hm);
                    if (h == HA) cnt_hint(g_cnt + (C_A + u * 4 + wq) * 8, lane);
                    stg128(dst + h * 32, (pk(o0[0], o0[1]) & ~1u) | tag, pk(o0[2], o0[3]), pk(o1[0], o1[1]), pk(o1[2], o1[3]));
                    kh[2 * h] = k2; kh[2 * h + 1] = k3; vh[2 * h] = v1; vh[2 * h + 1] = v3;
                }
                kh[6] = kt1; vh[6] = vt1;
                stg128(dst + 96, (pk(ot[0], ot[1]) & ~1u) | tag, pk(ot[2], ot[3]), 0, 0);
                TRG(u, 2);
            }
        }
    } else {
        asm volatile("setmaxnreg.dec.sync.aligned.u32 120;");
        if (b < 24) {
            const int kq = b / 6, nq = b % 6;
            const uint32_t blo = (((sb + O_WA) >> 4) & 0x3fff) | (8u << 16);
#pragma unroll 1
            for (int u = 0; u < NTA; u++) {
                hint_wait(g_cnt + (C_A + u * 4 + wq) * 8, 11 * (ep + 1));
                const uint32_t tag = ring_tag<NTA>(u, ep);
                TRG(u, 0);
                const uint4* src = g_oa + (((u & (RING - 1)) * 4 + wq) * 44 + kq * 11) * 32 + lane;
                uint4 a[11];
                float d[48];
#pragma unroll
                for (int i = 0; i < 11; i++) a[i] = ldg_pkt(src + i * 32);
                validate<11>(a, src, 512, tag);
                wg_fence();
#pragma unroll
                for (int i = 0; i < 11; i++) wgmma_rs96t(d, a[i].x, a[i].y, a[i].z, a[i].w, mkdesc(blo + i * 16, 176), i > 0);
                wg_commit();
                wg_wait<0>();
                TRG(u, 1);
                uint4* dst = g_pa + (((u & (RING - 1)) * 64 + (wq >> 1) * 32 + 2 * g + (wq & 1)) * 4 + kq) * 72 + nq * 12 + c;
#pragma unroll
                for (int m = 0; m < 3; m++) {
                    if (m == HW) cnt_hint(g_cnt + (C_WA + u * 4 + wq) * 8, lane);
                    stg128(dst + 4 * m, (pk(d[16 * m], d[16 * m + 1]) & ~1u) | tag, pk(d[16 * m + 4], d[16 * m + 5]), pk(d[16 * m + 8], d[16 * m + 9]), pk(d[16 * m + 12], d[16 * m + 13]));
                    stg128(dst + 4 * m + 16 * 288, (pk(d[16 * m + 2], d[16 * m + 3]) & ~1u) | tag, pk(d[16 * m + 6], d[16 * m + 7]), pk(d[16 * m + 10], d[16 * m + 11]), pk(d[16 * m + 14], d[16 * m + 15]));
                }
                TRG(u, 3);
            }
        } else if (warp == 4) {
            mbar_expect(bar + 64 + lane * 8, A_KB, lane < 9);
            int it = 0;
#pragma unroll 1
            for (int u = 0; u < NTA; u++) {
                if (u == 0) { cnt_wait(g_cnt + C_W * 8, 96 * (ep + 1)); TRG(78, 0); }
                if (u < NSEG) cnt_wait(g_cnt + (C_N0 + u) * 8, 32 * (ep + 1));
                if (u > LAGA + LAG) cnt_wait(g_cnt + (C_RB + NSEG + u - LAGA - LAG - 1) * 8, 32 * (ep + 1));
                if (u >= LAGA) cnt_wait(g_cnt + (C_RB + u - LAGA) * 8, 32 * (ep + 1));
                TRG(u, 0);
                asm volatile("fence.proxy.async.global;" ::: "memory");
                const bool on = lane == 0 ? u < NSEG : lane == 1 && u >= LAGA;
#pragma unroll 1
                for (int kb = 0; kb < 9; kb++, it++) {
                    if (it >= 4) mbar_wait(bar + 32 + (it & 3) * 8, ((it >> 2) - 1) & 1);
                    mbar_expect(bar + (it & 3) * 8, u < NSEG && u >= LAGA ? 8192 : 4096, lane == 0);
                    asm volatile("{.reg .pred p; setp.ne.u32 p, %3, 0; @p cp.async.bulk.shared::cluster.global.mbarrier::complete_tx::bytes [%0], [%1], 4096, [%2];}"
                        :: "r"(sb + O_RING + (it & 3) * 8192 + (lane & 1) * 4096), "l"(g_xa + u * 4608 + (lane & 1) * 2304 + kb * 256), "r"(bar + (it & 3) * 8), "r"((uint32_t)on) : "memory");
                    if (u == 0) asm volatile("{.reg .pred p; setp.ne.u32 p, %4, 0; @p cp.async.bulk.shared::cluster.global.mbarrier::complete_tx::bytes [%0], [%1], %3, [%2];}"
                        :: "r"(sb + lane * A_KB), "l"(g_wa + ((b - 24) * 9 + lane) * (A_KB / 16)), "r"(bar + 64 + lane * 8), "n"(A_KB),
                           "r"((uint32_t)(lane < 9 && kb == (lane < 4 ? lane : lane < 6 ? 3 : lane - 2))) : "memory");
                }
            }
        } else if ((warp - 5) * 11 + b - 24 < 32) rows_a(xin, 1, (warp - 5) * 11 + b - 24, lane, ep, warp);
    }
}

extern "C" void kernel_launch(void* const* d_in, const int* in_sizes, int n_in, void* d_out, int out_size) {
    const __nv_bfloat16* x = (const __nv_bfloat16*)d_in[0];
    const __nv_bfloat16* wqkv = (const __nv_bfloat16*)d_in[1];
    const __nv_bfloat16* wo = (const __nv_bfloat16*)d_in[2];
    const __nv_bfloat16* mem0 = (const __nv_bfloat16*)d_in[4];
    const __nv_bfloat16* Wq = (const __nv_bfloat16*)d_in[5];
    const __nv_bfloat16* Wk = (const __nv_bfloat16*)d_in[6];
    const __nv_bfloat16* Wv = (const __nv_bfloat16*)d_in[7];
    const __nv_bfloat16* Wo = (const __nv_bfloat16*)d_in[8];
    cudaFuncSetAttribute(k_main, cudaFuncAttributeMaxDynamicSharedMemorySize, km::SMEM);
    cudaFuncSetAttribute(k_aux, cudaFuncAttributeMaxDynamicSharedMemorySize, ka::SMEM);
    cudaStream_t s = cudaStreamPerThread;
    k_main<<<96, 384, km::SMEM, s>>>(x, wqkv, wo, mem0, Wq, Wk, Wv, Wo);
    cudaLaunchConfig_t cfg = {};
    cudaLaunchAttribute at[1];
    at[0].id = cudaLaunchAttributeProgrammaticStreamSerialization;
    at[0].val.programmaticStreamSerializationAllowed = 1;
    cfg.stream = s; cfg.attrs = at; cfg.numAttrs = 1;
    cfg.gridDim = dim3(36); cfg.blockDim = dim3(384); cfg.dynamicSmemBytes = ka::SMEM;
    cudaLaunchKernelEx(&cfg, k_aux, x, wqkv, wo, Wo, (__nv_bfloat16*)d_out);
}
```

```cpp
#include <cuda_runtime.h>
#include <cuda_bf16.h>
#include <stdint.h>

#define LAG 7
constexpr int NSEG = 64;
constexpr int NT = NSEG + LAG;
#define AHEAD 1
constexpr int LAGA = LAG + AHEAD;
constexpr int NTA = NSEG + LAGA;
#define RING_ 8
constexpr int RING = RING_;
constexpr int DM = 576;

__device__ __align__(1024) uint4 g_xt[NT * 2 * 9 * 256];
__device__ __align__(1024) uint4 g_o[RING * 4 * 256 * 32];
__device__ __align__(1024) uint4 g_ex[2 * 131072];
__device__ unsigned g_side[96];
__device__ __align__(1024) uint4 g_pb[RING * 64 * 8 * 72];
__device__ __align__(1024) uint4 g_pa[RING * 64 * 4 * 72];
__device__ __align__(1024) uint4 g_oa[RING * 4 * 44 * 32];
__device__ __align__(1024) uint4 g_xa[NTA * 2 * 9 * 256];
__device__ __align__(1024) uint4 g_wa[11 * 9 * 21 * 64];
__device__ __align__(1024) uint4 g_x[3 * 2048 * 72];

constexpr int C_X = 0;
constexpr int C_O = C_X + NT;
constexpr int C_WB = C_O + NT * 8;
constexpr int C_RB = C_WB + NT * 4;
constexpr int C_A = C_RB + 2 * NSEG;
constexpr int C_WA = C_A + NTA * 4;
constexpr int C_N0 = C_WA + NTA * 4;
constexpr int C_W = C_N0 + NSEG;
constexpr int C_DONE = C_W + 1;
constexpr int C_TOTAL = C_DONE + 1;
__device__ __align__(1024) unsigned g_cnt[C_TOTAL * 8];
__device__ unsigned g_epoch;

#define TR(i)
#define TR1(i)
#define TR_ON(t)
#define TR_INIT(base)
#define TR_DUMP(slot)
#define TRG(t, i)
constexpr int TR_BYTES = 0;

#define DEVI __device__ __forceinline__
DEVI uint32_t smem_u32(const void* p) { return (uint32_t)__cvta_generic_to_shared(p); }
DEVI uint32_t pk(float lo, float hi) { uint32_t r; asm("cvt.rn.bf16x2.f32 %0, %1, %2;" : "=r"(r) : "f"(hi), "f"(lo)); return r; }
DEVI float bf_lo(uint32_t u) { return __uint_as_float(u << 16); }
DEVI float bf_hi(uint32_t u) { return __uint_as_float(u & 0xffff0000u); }
DEVI uint32_t add2(uint32_t a, uint32_t b) { uint32_t d; asm("add.rn.bf16x2 %0, %1, %2;" : "=r"(d) : "r"(a), "r"(b)); return d; }
DEVI uint32_t movm(uint32_t a) { uint32_t d; asm volatile("movmatrix.sync.aligned.m8n8.trans.b16 %0, %1;" : "=r"(d) : "r"(a)); return d; }
DEVI float2 shfl2(float a, float b, int o) {
    float2 r; asm volatile("shfl.sync.bfly.b32 %0, %2, %4, 31, -1; shfl.sync.bfly.b32 %1, %3, %4, 31, -1;" : "=&f"(r.x), "=f"(r.y) : "f"(a), "f"(b), "r"(o)); return r;
}
DEVI float ex2(float x) { float y; asm("ex2.approx.ftz.f32 %0, %1;" : "=f"(y) : "f"(x)); return y; }
DEVI float rcp(float x) { float y; asm("rcp.approx.ftz.f32 %0, %1;" : "=f"(y) : "f"(x)); return y; }
DEVI void mma16(float (&d)[4], uint32_t a0, uint32_t a1, uint32_t a2, uint32_t a3, uint32_t b0, uint32_t b1) {
    asm volatile("mma.sync.aligned.m16n8k16.row.col.f32.bf16.bf16.f32 {%0,%1,%2,%3}, {%4,%5,%6,%7}, {%8,%9}, {%0,%1,%2,%3};"
        : "+f"(d[0]), "+f"(d[1]), "+f"(d[2]), "+f"(d[3]) : "r"(a0), "r"(a1), "r"(a2), "r"(a3), "r"(b0), "r"(b1));
}
DEVI void mma8(float (&d)[4], uint32_t a0, uint32_t a1, uint32_t b0) {
    asm volatile("mma.sync.aligned.m16n8k8.row.col.f32.bf16.bf16.f32 {%0,%1,%2,%3}, {%4,%5}, {%6}, {%0,%1,%2,%3};"
        : "+f"(d[0]), "+f"(d[1]), "+f"(d[2]), "+f"(d[3]) : "r"(a0), "r"(a1), "r"(b0));
}
DEVI uint4 lds128(uint32_t a) { uint4 v; asm volatile("ld.shared.v4.u32 {%0,%1,%2,%3}, [%4];" : "=r"(v.x), "=r"(v.y), "=r"(v.z), "=r"(v.w) : "r"(a) : "memory"); return v; }
DEVI uint2 lds64(uint32_t a) { uint2 v; asm volatile("ld.shared.v2.u32 {%0,%1}, [%2];" : "=r"(v.x), "=r"(v.y) : "r"(a) : "memory"); return v; }
DEVI uint32_t lds32(uint32_t a) { uint32_t v; asm volatile("ld.shared.u32 %0, [%1];" : "=r"(v) : "r"(a) : "memory"); return v; }
DEVI uint32_t lds32v(uint32_t a) { uint32_t v; asm volatile("ld.volatile.shared.u32 %0, [%1];" : "=r"(v) : "r"(a) : "memory"); return v; }
DEVI uint4 lds128v(uint32_t a) { uint4 v; asm volatile("ld.volatile.shared.v4.u32 {%0,%1,%2,%3}, [%4];" : "=r"(v.x), "=r"(v.y), "=r"(v.z), "=r"(v.w) : "r"(a) : "memory"); return v; }
DEVI uint32_t lds16(uint32_t a) { uint32_t v; asm volatile("ld.shared.u16 %0, [%1];" : "=r"(v) : "r"(a) : "memory"); return v; }
DEVI uint4 ldsm4(uint32_t a) { uint4 v; asm volatile("ldmatrix.sync.aligned.m8n8.x4.shared.b16 {%0,%1,%2,%3}, [%4];" : "=r"(v.x), "=r"(v.y), "=r"(v.z), "=r"(v.w) : "r"(a) : "memory"); return v; }
DEVI uint4 ldsm4p(uint32_t a, bool pred) {
    uint4 v; asm volatile("{.reg .pred p; setp.ne.u32 p, %5, 0; @p ldmatrix.sync.aligned.m8n8.x4.shared.b16 {%0,%1,%2,%3}, [%4];}" : "=r"(v.x), "=r"(v.y), "=r"(v.z), "=r"(v.w) : "r"(a), "r"((uint32_t)pred) : "memory"); return v;
}
DEVI uint4 ldsm4t(uint32_t a) { uint4 v; asm volatile("ldmatrix.sync.aligned.m8n8.x4.trans.shared.b16 {%0,%1,%2,%3}, [%4];" : "=r"(v.x), "=r"(v.y), "=r"(v.z), "=r"(v.w) : "r"(a) : "memory"); return v; }
DEVI uint2 ldsm2(uint32_t a) { uint2 v; asm volatile("ldmatrix.sync.aligned.m8n8.x2.shared.b16 {%0,%1}, [%2];" : "=r"(v.x), "=r"(v.y) : "r"(a) : "memory"); return v; }
DEVI void stsm4t(uint32_t a, uint32_t x, uint32_t y, uint32_t z, uint32_t w) { asm volatile("stmatrix.sync.aligned.m8n8.x4.trans.shared.b16 [%0], {%1,%2,%3,%4};" :: "r"(a), "r"(x), "r"(y), "r"(z), "r"(w) : "memory"); }
DEVI void sts128(uint32_t a, uint32_t x, uint32_t y, uint32_t z, uint32_t w) { asm volatile("st.shared.v4.u32 [%0], {%1,%2,%3,%4};" :: "r"(a), "r"(x), "r"(y), "r"(z), "r"(w) : "memory"); }
DEVI void sts64(uint32_t a, uint32_t x, uint32_t y) { asm volatile("st.shared.v2.u32 [%0], {%1,%2};" :: "r"(a), "r"(x), "r"(y) : "memory"); }
DEVI void sts32(uint32_t a, uint32_t x) { asm volatile("st.shared.u32 [%0], %1;" :: "r"(a), "r"(x) : "memory"); }
DEVI void sts32p(uint32_t a, uint32_t x, bool pred) { asm volatile("{.reg .pred p; setp.ne.u32 p, %2, 0; @p st.shared.u32 [%0], %1;}" :: "r"(a), "r"(x), "r"((uint32_t)pred) : "memory"); }
DEVI void sta128(uint32_t a, uint32_t x, uint32_t y, uint32_t z, uint32_t w, uint32_t bar) {
    asm volatile("st.async.weak.shared::cluster.mbarrier::complete_tx::bytes.v4.b32 [%0], {%1,%2,%3,%4}, [%5];" :: "r"(a), "r"(x), "r"(y), "r"(z), "r"(w), "r"(bar) : "memory");
}
DEVI void sta128p(uint32_t a, uint32_t x, uint32_t y, uint32_t z, uint32_t w, uint32_t bar, bool pred) {
    asm volatile("{.reg .pred p; setp.ne.u32 p, %6, 0; @p st.async.weak.shared::cluster.mbarrier::complete_tx::bytes.v4.b32 [%0], {%1,%2,%3,%4}, [%5];}" :: "r"(a), "r"(x), "r"(y), "r"(z), "r"(w), "r"(bar), "r"((uint32_t)pred) : "memory");
}
DEVI void sta64(uint32_t a, uint32_t x, uint32_t y, uint32_t bar) {
    asm volatile("st.async.weak.shared::cluster.mbarrier::complete_tx::bytes.v2.b32 [%0], {%1,%2}, [%3];" :: "r"(a), "r"(x), "r"(y), "r"(bar) : "memory");
}
DEVI void sta32(uint32_t a, uint32_t x, uint32_t bar) {
    asm volatile("st.async.weak.shared::cluster.mbarrier::complete_tx::bytes.b32 [%0], %1, [%2];" :: "r"(a), "r"(x), "r"(bar) : "memory");
}
DEVI uint4 ldg_pkt(const void* p) {
    uint4 v;
    asm volatile("ld.relaxed.gpu.global.v4.u32 {%0,%1,%2,%3}, [%4];" : "=r"(v.x), "=r"(v.y), "=r"(v.z), "=r"(v.w) : "l"(p) : "memory");
    return v;
}
DEVI void ldg_pkt_if(uint4& v, const void* p, bool pred) {
    asm volatile("{.reg .pred p; setp.ne.u32 p, %5, 0; @p ld.relaxed.gpu.global.v4.u32 {%0,%1,%2,%3}, [%4];}"
        : "+r"(v.x), "+r"(v.y), "+r"(v.z), "+r"(v.w) : "l"(p), "r"((uint32_t)pred) : "memory");
}
DEVI void ldg_pkt_retry(uint4& v, const void* p, uint32_t tag) {
    asm volatile("{.reg .pred p; .reg .b32 t; lop3.b32 t, %0, %5, 1, 0x28; setp.ne.u32 p, t, 0; @p ld.relaxed.gpu.global.v4.u32 {%0,%1,%2,%3}, [%4];}"
        : "+r"(v.x), "+r"(v.y), "+r"(v.z), "+r"(v.w) : "l"(p), "r"(tag) : "memory");
}
DEVI void stg_pkt(void* p, uint32_t x, uint32_t y, uint32_t z, uint32_t w) {
    asm volatile("st.relaxed.gpu.global.v4.u32 [%0], {%1,%2,%3,%4};" :: "l"(p), "r"(x), "r"(y), "r"(z), "r"(w) : "memory");
}
DEVI uint32_t ldg_word(const void* p) { uint32_t v; asm volatile("ld.relaxed.gpu.global.u32 %0, [%1];" : "=r"(v) : "l"(p) : "memory"); return v; }
DEVI void stg_word(void* p, uint32_t x, bool pred) {
    asm volatile("{.reg .pred p; setp.ne.u32 p, %2, 0; @p st.relaxed.gpu.global.u32 [%0], %1;}" :: "l"(p), "r"(x), "r"((uint32_t)pred) : "memory");
}
DEVI uint2 ldg64nc(const void* p) { uint2 v; asm volatile("ld.global.nc.L1::no_allocate.v2.u32 {%0,%1}, [%2];" : "=r"(v.x), "=r"(v.y) : "l"(p)); return v; }
DEVI void prefetch_l2(const void* p, uint32_t bytes) { asm volatile("cp.async.bulk.prefetch.L2.global [%0], %1;" :: "l"(p), "r"(bytes) : "memory"); }
DEVI uint4 ldg128(const void* p) { uint4 v; asm volatile("ld.global.cg.v4.u32 {%0,%1,%2,%3}, [%4];" : "=r"(v.x), "=r"(v.y), "=r"(v.z), "=r"(v.w) : "l"(p) : "memory"); return v; }
DEVI uint2 ldg64(const void* p) { uint2 v; asm volatile("ld.global.cg.v2.u32 {%0,%1}, [%2];" : "=r"(v.x), "=r"(v.y) : "l"(p) : "memory"); return v; }
DEVI uint32_t ldg32(const void* p) { uint32_t v; asm volatile("ld.global.cg.u32 %0, [%1];" : "=r"(v) : "l"(p) : "memory"); return v; }
DEVI void stg128(void* p, uint32_t x, uint32_t y, uint32_t z, uint32_t w) { asm volatile("st.global.cg.v4.u32 [%0], {%1,%2,%3,%4};" :: "l"(p), "r"(x), "r"(y), "r"(z), "r"(w) : "memory"); }
DEVI void stg128p(void* p, uint32_t x, uint32_t y, uint32_t z, uint32_t w, bool pred) { asm volatile("{.reg .pred p; setp.ne.u32 p, %5, 0; @p st.global.cg.v4.u32 [%0], {%1,%2,%3,%4};}" :: "l"(p), "r"(x), "r"(y), "r"(z), "r"(w), "r"((uint32_t)pred) : "memory"); }
DEVI void stg64(void* p, uint32_t x, uint32_t y) { asm volatile("st.global.cg.v2.u32 [%0], {%1,%2};" :: "l"(p), "r"(x), "r"(y) : "memory"); }
DEVI void stg32(void* p, uint32_t x) { asm volatile("st.global.cg.u32 [%0], %1;" :: "l"(p), "r"(x) : "memory"); }
DEVI void cp16(uint32_t dst, const void* src) { asm volatile("cp.async.cg.shared.global [%0], [%1], 16;" :: "r"(dst), "l"(src) : "memory"); }
DEVI void cp16_if(uint32_t dst, const void* src, bool pred) { asm volatile("{.reg .pred p; setp.ne.u32 p, %2, 0; @p cp.async.cg.shared.global [%0], [%1], 16;}" :: "r"(dst), "l"(src), "r"((uint32_t)pred) : "memory"); }
DEVI void cp_commit() { asm volatile("cp.async.commit_group;" ::: "memory"); }
DEVI void cp4(uint32_t dst, const void* src) { asm volatile("cp.async.ca.shared.global [%0], [%1], 4;" :: "r"(dst), "l"(src) : "memory"); }
template <int N> DEVI void cp_wait() { asm volatile("cp.async.wait_group %0;" :: "n"(N) : "memory"); }
DEVI void cp_wait_all() { asm volatile("cp.async.wait_all;" ::: "memory"); }
DEVI void bar_sync(int id, int n) { asm volatile("bar.sync %0, %1;" :: "r"(id), "r"(n) : "memory"); }
DEVI void bar_arrive(int id, int n) { asm volatile("bar.arrive %0, %1;" :: "r"(id), "r"(n) : "memory"); }
DEVI void fence_async_smem() { asm volatile("fence.proxy.async.shared::cta;" ::: "memory"); }
DEVI void fence_async_global() { asm volatile("fence.proxy.async.global;" ::: "memory"); }
DEVI void mbar_init(uint32_t b, int n) { asm volatile("mbarrier.init.shared.b64 [%0], %1;" :: "r"(b), "r"(n) : "memory"); }
DEVI void mbar_expect(uint32_t b, uint32_t bytes, bool pred) {
    asm volatile("{.reg .pred p; setp.ne.u32 p, %2, 0; @p mbarrier.arrive.expect_tx.shared.b64 _, [%0], %1;}" :: "r"(b), "r"(bytes), "r"((uint32_t)pred) : "memory");
}
DEVI void mbar_arrive(uint32_t b, bool pred) { asm volatile("{.reg .pred p; setp.ne.u32 p, %1, 0; @p mbarrier.arrive.shared.b64 _, [%0];}" :: "r"(b), "r"((uint32_t)pred) : "memory"); }
DEVI void mbar_arrive_all3(uint32_t b, uint32_t lane) {
    asm volatile("{.reg .pred p; .reg .u32 a; setp.lt.u32 p, %1, 3; @p mapa.shared::cluster.u32 a, %0, %1; @p mbarrier.arrive.relaxed.cluster.shared::cluster.b64 _, [a];}" :: "r"(b), "r"(lane) : "memory");
}
#define FAULT "or.b32 n, n, 1; st.volatile.shared.u32 [n], n;\n"
#define LIM1 "400000"
#define LIM2 "2000000"
DEVI void fault_if(bool p, uint32_t n) { asm volatile("{.reg .pred p; setp.ne.u32 p, %0, 0; @p st.volatile.shared.u32 [%1], %1;}" :: "r"((uint32_t)p), "r"(n | 1) : "memory"); }
DEVI void mbar_wait(uint32_t b, uint32_t parity) {
    asm volatile("{.reg .pred p; .reg .u32 n;\n"
        "mbarrier.try_wait.parity.shared::cta.b64 p, [%0], %1;\n"
        "@p bra.uni D%=;\n"
        "mov.u32 n, 0;\n"
        "W%=: mbarrier.try_wait.parity.shared::cta.b64 p, [%0], %1;\n"
        "@p bra.uni D%=;\n"
        "add.u32 n, n, 1; setp.lt.u32 p, n, " LIM1 "; @p bra.uni W%=;\n"
        FAULT
        "D%=:}" :: "r"(b), "r"(parity) : "memory");
}
constexpr int POLL_LIMIT = 2000000;
DEVI void cnt_wait(const unsigned* c, unsigned target) {
    asm volatile("{.reg .pred p; .reg .u32 n, v;\n"
        "ld.acquire.gpu.global.u32 v, [%0];\n"
        "setp.ge.u32 p, v, %1; vote.sync.all.pred p, p, 0xffffffff; @p bra.uni D%=;\n"
        "mov.u32 n, 0;\n"
        "W%=: ld.acquire.gpu.global.u32 v, [%0];\n"
        "setp.ge.u32 p, v, %1; vote.sync.all.pred p, p, 0xffffffff; @p bra.uni D%=;\n"
        "add.u32 n, n, 1; setp.lt.u32 p, n, " LIM2 "; @p bra.uni W%=;\n"
        FAULT
        "D%=:}" :: "l"(c), "r"(target) : "memory");
}
DEVI void hint_wait(const unsigned* c, unsigned target) {
    asm volatile("{.reg .pred p; .reg .u32 n, v;\n"
        "ld.relaxed.gpu.global.u32 v, [%0];\n"
        "setp.ge.u32 p, v, %1; vote.sync.all.pred p, p, 0xffffffff; @p bra.uni D%=;\n"
        "mov.u32 n, 0;\n"
        "W%=: ld.relaxed.gpu.global.u32 v, [%0];\n"
        "setp.ge.u32 p, v, %1; vote.sync.all.pred p, p, 0xffffffff; @p bra.uni D%=;\n"
        "add.u32 n, n, 1; setp.lt.u32 p, n, " LIM2 "; @p bra.uni W%=;\n"
        FAULT
        "D%=:}" :: "l"(c), "r"(target) : "memory");
}
template <int N = 1> DEVI void cnt_add(unsigned* c, int lane) {
    asm volatile("{.reg .pred p; setp.eq.u32 p, %1, 0; fence.acq_rel.gpu; bar.warp.sync 0xffffffff; @p red.relaxed.gpu.global.add.u32 [%0], %2;}" :: "l"(c + lane), "r"(lane), "n"(N) : "memory");
}
DEVI void cnt_hint(unsigned* c, int lane) {
    asm volatile("{.reg .pred p; setp.eq.u32 p, %1, 0; @p red.relaxed.gpu.global.add.u32 [%0], 1;}" :: "l"(c + lane), "r"(lane) : "memory");
}
template <int N = NT> DEVI uint32_t ring_tag(unsigned u, uint32_t ep) { return (u / RING + ep * ((N - 1 - u % RING) / RING + 1) + 1) & 1; }
static_assert(RING >= LAGA && RING > LAG, "ring too short");
DEVI uint32_t lop_bad(uint32_t acc, uint32_t x, uint32_t y, uint32_t tag) {
    uint32_t d; asm("{.reg .b32 t; lop3.b32 t, %2, %3, %4, 0x7e; or.b32 %0, t, %1;}" : "=r"(d) : "r"(acc), "r"(x), "r"(y), "r"(tag)); return d;
}
template <int N> DEVI void validate(uint4* v, const void* p, int step, uint32_t tag) {
    for (int n = 0;; n++) {
        uint32_t bad = 0;
#pragma unroll
        for (int i = 0; i < N; i += 2) bad = lop_bad(bad, v[i].x, v[i + 1 < N ? i + 1 : i].x, tag);
        if (!__any_sync(~0u, bad & 1)) break;
#pragma unroll
        for (int i = 0; i < N; i++) ldg_pkt_retry(v[i], static_cast<const char*>(p) + i * step, tag);
        fault_if(n > POLL_LIMIT, n);
    }
}
DEVI uint32_t page_par(uint32_t off) { return __popc((off >> 12) & 0xb2) & 1; }
DEVI uint32_t inbox_off(int b) { return (b >> 1) * 32768 + (b & 1) * 8192; }
DEVI uint32_t mem_off(int w, int i) { return 0x180000 + w * 1024 + (i & 1) * 512 + (i & 3) * 16384 + (i < 4 ? 0 : i < 8 ? 0x30000 : 0x40000); }
DEVI void sched_fence(uint32_t zero, uint32_t id) { asm volatile("{.reg .pred p; setp.ne.u32 p, %0, %1; @p bra.uni D%=; exit; D%=:}" :: "r"(zero), "r"(id) : "memory"); }
DEVI uint32_t clk() { uint32_t c; asm volatile("mov.u32 %0, %%clock;" : "=r"(c) :: "memory"); return c; }
DEVI void delay(uint32_t n) {
    if (n) asm volatile("{.reg .pred p; .reg .u32 c, e; mov.u32 e, %%clock;\n W%=: mov.u32 c, %%clock; sub.u32 c, c, e; setp.lt.u32 p, c, %0; @p bra.uni W%=;}" :: "r"(n) : "memory");
}
DEVI void delay_until(uint32_t t0, uint32_t n) {
    asm volatile("{.reg .pred p; .reg .u32 c;\n W%=: mov.u32 c, %%clock; sub.u32 c, c, %1; setp.lt.u32 p, c, %0; @p bra.uni W%=;}" :: "r"(n), "r"(t0) : "memory");
}
DEVI void wg_fence() { asm volatile("wgmma.fence.sync.aligned;" ::: "memory"); }
DEVI void wg_commit() { asm volatile("wgmma.commit_group.sync.aligned;" ::: "memory"); }
template <int N> DEVI void wg_wait() { asm volatile("wgmma.wait_group.sync.aligned %0;" :: "n"(N) : "memory"); }
DEVI uint64_t mkdesc(uint32_t lo, uint32_t hi) { uint64_t d; asm("mov.b64 %0, {%1,%2};" : "=l"(d) : "r"(lo), "r"(hi)); return d; }
DEVI void cluster_arrive() { asm volatile("barrier.cluster.arrive.relaxed.aligned;" ::: "memory"); }
DEVI void cluster_wait() { asm volatile("barrier.cluster.wait.aligned;" ::: "memory"); }
DEVI void cluster_sync() { asm volatile("barrier.cluster.arrive.aligned;\n barrier.cluster.wait.aligned;" ::: "memory"); }
DEVI void wgmma_ss16t(float (&d)[8], uint64_t da, uint64_t db, int acc) {
    asm volatile("{.reg .pred p; setp.ne.b32 p, %10, 0;\n"
        "wgmma.mma_async.sync.aligned.m64n16k16.f32.bf16.bf16 {%0,%1,%2,%3,%4,%5,%6,%7}, %8, %9, p, 1, 1, 0, 1;}"
        : "+f"(d[0]), "+f"(d[1]), "+f"(d[2]), "+f"(d[3]), "+f"(d[4]), "+f"(d[5]), "+f"(d[6]), "+f"(d[7])
        : "l"(da), "l"(db), "r"(acc));
}
DEVI void wgmma_ss16a(float (&d)[8], uint64_t da, uint64_t db, int acc) {
    asm volatile("{.reg .pred p; setp.ne.b32 p, %10, 0;\n"
        "wgmma.mma_async.sync.aligned.m64n16k16.f32.bf16.bf16 {%0,%1,%2,%3,%4,%5,%6,%7}, %8, %9, p, 1, 1, 1, 0;}"
        : "+f"(d[0]), "+f"(d[1]), "+f"(d[2]), "+f"(d[3]), "+f"(d[4]), "+f"(d[5]), "+f"(d[6]), "+f"(d[7])
        : "l"(da), "l"(db), "r"(acc));
}
DEVI void wgmma_ss64(float (&d)[32], uint64_t da, uint64_t db, int acc) {
    asm volatile("{.reg .pred p; setp.ne.b32 p, %34, 0;\n"
        "wgmma.mma_async.sync.aligned.m64n64k16.f32.bf16.bf16 {%0,%1,%2,%3,%4,%5,%6,%7,%8,%9,%10,%11,%12,%13,%14,%15,%16,%17,%18,%19,%20,%21,%22,%23,%24,%25,%26,%27,%28,%29,%30,%31}, %32, %33, p, 1, 1, 0, 0;}"
        : "+f"(d[0]), "+f"(d[1]), "+f"(d[2]), "+f"(d[3]), "+f"(d[4]), "+f"(d[5]), "+f"(d[6]), "+f"(d[7]), "+f"(d[8]), "+f"(d[9]), "+f"(d[10]), "+f"(d[11]), "+f"(d[12]), "+f"(d[13]), "+f"(d[14]), "+f"(d[15]), "+f"(d[16]), "+f"(d[17]), "+f"(d[18]), "+f"(d[19]), "+f"(d[20]), "+f"(d[21]), "+f"(d[22]), "+f"(d[23]), "+f"(d[24]), "+f"(d[25]), "+f"(d[26]), "+f"(d[27]), "+f"(d[28]), "+f"(d[29]), "+f"(d[30]), "+f"(d[31])
        : "l"(da), "l"(db), "r"(acc));
}
DEVI void wgmma_rs16t(float (&d)[8], uint32_t a0, uint32_t a1, uint32_t a2, uint32_t a3, uint64_t db, int acc) {
    asm volatile("{.reg .pred p; setp.ne.b32 p, %13, 0;\n"
        "wgmma.mma_async.sync.aligned.m64n16k16.f32.bf16.bf16 {%0,%1,%2,%3,%4,%5,%6,%7}, {%8,%9,%10,%11}, %12, p, 1, 1, 1;}"
        : "+f"(d[0]), "+f"(d[1]), "+f"(d[2]), "+f"(d[3]), "+f"(d[4]), "+f"(d[5]), "+f"(d[6]), "+f"(d[7])
        : "r"(a0), "r"(a1), "r"(a2), "r"(a3), "l"(db), "r"(acc));
}
DEVI void wgmma_rs64(float (&d)[32], uint32_t a0, uint32_t a1, uint32_t a2, uint32_t a3, uint64_t db, int acc) {
    asm volatile("{.reg .pred p; setp.ne.b32 p, %37, 0;\n"
        "wgmma.mma_async.sync.aligned.m64n64k16.f32.bf16.bf16 {%0,%1,%2,%3,%4,%5,%6,%7,%8,%9,%10,%11,%12,%13,%14,%15,%16,%17,%18,%19,%20,%21,%22,%23,%24,%25,%26,%27,%28,%29,%30,%31}, {%32,%33,%34,%35}, %36, p, 1, 1, 0;}"
        : "+f"(d[0]), "+f"(d[1]), "+f"(d[2]), "+f"(d[3]), "+f"(d[4]), "+f"(d[5]), "+f"(d[6]), "+f"(d[7]), "+f"(d[8]), "+f"(d[9]), "+f"(d[10]), "+f"(d[11]), "+f"(d[12]), "+f"(d[13]), "+f"(d[14]), "+f"(d[15]), "+f"(d[16]), "+f"(d[17]), "+f"(d[18]), "+f"(d[19]), "+f"(d[20]), "+f"(d[21]), "+f"(d[22]), "+f"(d[23]), "+f"(d[24]), "+f"(d[25]), "+f"(d[26]), "+f"(d[27]), "+f"(d[28]), "+f"(d[29]), "+f"(d[30]), "+f"(d[31])
        : "r"(a0), "r"(a1), "r"(a2), "r"(a3), "l"(db), "r"(acc));
}
DEVI void wgmma_ss168t(float (&d)[84], uint64_t da, uint64_t db, int acc) {
    asm volatile("{.reg .pred p; setp.ne.b32 p, %86, 0;\n"
        "wgmma.mma_async.sync.aligned.m64n168k16.f32.bf16.bf16 {%0,%1,%2,%3,%4,%5,%6,%7,%8,%9,%10,%11,%12,%13,%14,%15,%16,%17,%18,%19,%20,%21,%22,%23,%24,%25,%26,%27,%28,%29,%30,%31,%32,%33,%34,%35,%36,%37,%38,%39,%40,%41,%42,%43,%44,%45,%46,%47,%48,%49,%50,%51,%52,%53,%54,%55,%56,%57,%58,%59,%60,%61,%62,%63,%64,%65,%66,%67,%68,%69,%70,%71,%72,%73,%74,%75,%76,%77,%78,%79,%80,%81,%82,%83}, %84, %85, p, 1, 1, 0, 1;}"
        : "+f"(d[0]), "+f"(d[1]), "+f"(d[2]), "+f"(d[3]), "+f"(d[4]), "+f"(d[5]), "+f"(d[6]), "+f"(d[7]), "+f"(d[8]), "+f"(d[9]), "+f"(d[10]), "+f"(d[11]), "+f"(d[12]), "+f"(d[13]), "+f"(d[14]), "+f"(d[15]), "+f"(d[16]), "+f"(d[17]), "+f"(d[18]), "+f"(d[19]), "+f"(d[20]), "+f"(d[21]), "+f"(d[22]), "+f"(d[23]), "+f"(d[24]), "+f"(d[25]), "+f"(d[26]), "+f"(d[27]), "+f"(d[28]), "+f"(d[29]), "+f"(d[30]), "+f"(d[31]), "+f"(d[32]), "+f"(d[33]), "+f"(d[34]), "+f"(d[35]), "+f"(d[36]), "+f"(d[37]), "+f"(d[38]), "+f"(d[39]), "+f"(d[40]), "+f"(d[41]), "+f"(d[42]), "+f"(d[43]), "+f"(d[44]), "+f"(d[45]), "+f"(d[46]), "+f"(d[47]), "+f"(d[48]), "+f"(d[49]), "+f"(d[50]), "+f"(d[51]), "+f"(d[52]), "+f"(d[53]), "+f"(d[54]), "+f"(d[55]), "+f"(d[56]), "+f"(d[57]), "+f"(d[58]), "+f"(d[59]), "+f"(d[60]), "+f"(d[61]), "+f"(d[62]), "+f"(d[63]), "+f"(d[64]), "+f"(d[65]), "+f"(d[66]), "+f"(d[67]), "+f"(d[68]), "+f"(d[69]), "+f"(d[70]), "+f"(d[71]), "+f"(d[72]), "+f"(d[73]), "+f"(d[74]), "+f"(d[75]), "+f"(d[76]), "+f"(d[77]), "+f"(d[78]), "+f"(d[79]), "+f"(d[80]), "+f"(d[81]), "+f"(d[82]), "+f"(d[83])
        : "l"(da), "l"(db), "r"(acc));
}
DEVI void wgmma_rs96t(float (&d)[48], uint32_t a0, uint32_t a1, uint32_t a2, uint32_t a3, uint64_t db, int acc) {
    asm volatile("{.reg .pred p; setp.ne.b32 p, %53, 0;\n"
        "wgmma.mma_async.sync.aligned.m64n96k16.f32.bf16.bf16 {%0,%1,%2,%3,%4,%5,%6,%7,%8,%9,%10,%11,%12,%13,%14,%15,%16,%17,%18,%19,%20,%21,%22,%23,%24,%25,%26,%27,%28,%29,%30,%31,%32,%33,%34,%35,%36,%37,%38,%39,%40,%41,%42,%43,%44,%45,%46,%47}, {%48,%49,%50,%51}, %52, p, 1, 1, 1;}"
        : "+f"(d[0]), "+f"(d[1]), "+f"(d[2]), "+f"(d[3]), "+f"(d[4]), "+f"(d[5]), "+f"(d[6]), "+f"(d[7]), "+f"(d[8]), "+f"(d[9]), "+f"(d[10]), "+f"(d[11]), "+f"(d[12]), "+f"(d[13]), "+f"(d[14]), "+f"(d[15]), "+f"(d[16]), "+f"(d[17]), "+f"(d[18]), "+f"(d[19]), "+f"(d[20]), "+f"(d[21]), "+f"(d[22]), "+f"(d[23]), "+f"(d[24]), "+f"(d[25]), "+f"(d[26]), "+f"(d[27]), "+f"(d[28]), "+f"(d[29]), "+f"(d[30]), "+f"(d[31]), "+f"(d[32]), "+f"(d[33]), "+f"(d[34]), "+f"(d[35]), "+f"(d[36]), "+f"(d[37]), "+f"(d[38]), "+f"(d[39]), "+f"(d[40]), "+f"(d[41]), "+f"(d[42]), "+f"(d[43]), "+f"(d[44]), "+f"(d[45]), "+f"(d[46]), "+f"(d[47])
        : "r"(a0), "r"(a1), "r"(a2), "r"(a3), "l"(db), "r"(acc));
}
DEVI void wgmma_rs192t(float (&d)[96], uint32_t a0, uint32_t a1, uint32_t a2, uint32_t a3, uint64_t db, int acc) {
    asm volatile("{.reg .pred p; setp.ne.b32 p, %101, 0;\n"
        "wgmma.mma_async.sync.aligned.m64n192k16.f32.bf16.bf16 {%0,%1,%2,%3,%4,%5,%6,%7,%8,%9,%10,%11,%12,%13,%14,%15,%16,%17,%18,%19,%20,%21,%22,%23,%24,%25,%26,%27,%28,%29,%30,%31,%32,%33,%34,%35,%36,%37,%38,%39,%40,%41,%42,%43,%44,%45,%46,%47,%48,%49,%50,%51,%52,%53,%54,%55,%56,%57,%58,%59,%60,%61,%62,%63,%64,%65,%66,%67,%68,%69,%70,%71,%72,%73,%74,%75,%76,%77,%78,%79,%80,%81,%82,%83,%84,%85,%86,%87,%88,%89,%90,%91,%92,%93,%94,%95}, {%96,%97,%98,%99}, %100, p, 1, 1, 1;}"
        : "+f"(d[0]), "+f"(d[1]), "+f"(d[2]), "+f"(d[3]), "+f"(d[4]), "+f"(d[5]), "+f"(d[6]), "+f"(d[7]), "+f"(d[8]), "+f"(d[9]), "+f"(d[10]), "+f"(d[11]), "+f"(d[12]), "+f"(d[13]), "+f"(d[14]), "+f"(d[15]), "+f"(d[16]), "+f"(d[17]), "+f"(d[18]), "+f"(d[19]), "+f"(d[20]), "+f"(d[21]), "+f"(d[22]), "+f"(d[23]), "+f"(d[24]), "+f"(d[25]), "+f"(d[26]), "+f"(d[27]), "+f"(d[28]), "+f"(d[29]), "+f"(d[30]), "+f"(d[31]), "+f"(d[32]), "+f"(d[33]), "+f"(d[34]), "+f"(d[35]), "+f"(d[36]), "+f"(d[37]), "+f"(d[38]), "+f"(d[39]), "+f"(d[40]), "+f"(d[41]), "+f"(d[42]), "+f"(d[43]), "+f"(d[44]), "+f"(d[45]), "+f"(d[46]), "+f"(d[47]), "+f"(d[48]), "+f"(d[49]), "+f"(d[50]), "+f"(d[51]), "+f"(d[52]), "+f"(d[53]), "+f"(d[54]), "+f"(d[55]), "+f"(d[56]), "+f"(d[57]), "+f"(d[58]), "+f"(d[59]), "+f"(d[60]), "+f"(d[61]), "+f"(d[62]), "+f"(d[63]), "+f"(d[64]), "+f"(d[65]), "+f"(d[66]), "+f"(d[67]), "+f"(d[68]), "+f"(d[69]), "+f"(d[70]), "+f"(d[71]), "+f"(d[72]), "+f"(d[73]), "+f"(d[74]), "+f"(d[75]), "+f"(d[76]), "+f"(d[77]), "+f"(d[78]), "+f"(d[79]), "+f"(d[80]), "+f"(d[81]), "+f"(d[82]), "+f"(d[83]), "+f"(d[84]), "+f"(d[85]), "+f"(d[86]), "+f"(d[87]), "+f"(d[88]), "+f"(d[89]), "+f"(d[90]), "+f"(d[91]), "+f"(d[92]), "+f"(d[93]), "+f"(d[94]), "+f"(d[95])
        : "r"(a0), "r"(a1), "r"(a2), "r"(a3), "l"(db), "r"(acc));
}

#define TRD(t, i)
namespace km {
#define NSS 6
#define RG "184"
#define RW "136"
#define NFL 2
#define NR1 3
#define NR2 3
#define EK 7
#define FK 5
#define LDP 3
#define SND 1
#define NGAP 0
constexpr int O_H = 0;
constexpr int O_MB = 73728;
constexpr int O_VX = 96768;
constexpr int O_KX = 113152;
constexpr int O_QX = 119296;
constexpr int O_VM = 125440;
constexpr int O_KM = 129536;
constexpr int O_QM = 131072;
constexpr int O_SM = 132608;
constexpr int O_ST = 135168;
constexpr int O_OX = 145408;
constexpr int O_WO = 149504;
constexpr int O_OS = O_WO;
constexpr int O_WS = O_WO + 49152;
constexpr int O_RL = 110592;
constexpr int O_BAR = O_WS + NSS * 4096;
constexpr int SMEM = O_BAR + 128 + 1024 + TR_BYTES;
enum { B_X = 0, B_WIN = 16, B_VX = 24, B_SM = 32, B_ST = 40, B_EP = 56 };
#define DLY1 (100 * w)
#define DLY2 400
#define EARLY 1
#define DLYO 250
#define DLY0 5000
#define PFON 0
#define PLACE 1
#define XST 7
#define DLYW 9000
#define DLYB 4000
constexpr uint32_t DESC_HI = (1024 >> 4) | (1u << 30);
constexpr float SC = 0.08838834764831845f * 1.4426950408889634f;
}

__global__ void __cluster_dims__(3, 1, 1) __launch_bounds__(384, 1)
k_main(const __nv_bfloat16* __restrict__ x0, const __nv_bfloat16* __restrict__ wqkv, const __nv_bfloat16* __restrict__ wo,
       const __nv_bfloat16* __restrict__ mem0, const __nv_bfloat16* __restrict__ Wq, const __nv_bfloat16* __restrict__ Wk,
       const __nv_bfloat16* __restrict__ Wv, const __nv_bfloat16* __restrict__ Wo) {
    using namespace km;
    extern __shared__ unsigned char smem_raw[];
    const uint32_t sb = (smem_u32(smem_raw) + 1023) & ~1023u;
    const int tid = threadIdx.x, lane = tid & 31, warp = __shfl_sync(~0u, tid >> 5, 0);
    uint32_t l16 = __shfl_sync(~0u, lane * 16, lane);
#define OPQ() asm volatile("" : "+r"(l16))
    const int b = blockIdx.x, h = b / 3, r = b % 3;
    const int nq = r == 2 ? 2 : 3;
    const uint32_t bar = sb + O_BAR;
    asm volatile("griddepcontrol.launch_dependents;");
    const uint32_t t_start = clk();
    if (warp == 0 && b < 72) {
        if (lane == 0) { mbar_init(bar + 96, 1); fence_async_smem(); mbar_expect(bar + 96, 8 * 3456, true); }
        __syncwarp();
        if (lane < 8) asm volatile("cp.async.bulk.shared::cluster.global.mbarrier::complete_tx::bytes [%0], [%1], 3456, [%2];" :: "r"(sb + O_RL + lane * 3472), "l"(wqkv + (b * 8 + lane) * 1728), "r"(bar + 96) : "memory");
    }
    if (tid == 352) {
        prefetch_l2(x0 + b * (2 * DM), 2 * 1152); prefetch_l2(wo + b * (6 * DM), 6 * 1152);
    }
    if (tid == 320) sts32(bar + 64, ldg32(&g_epoch));
#define EP lds32(bar + 64)
    TR_INIT(bar + 128);
    TRG(79, 0);
    uint32_t roff0, roff1;
    {
        uint32_t y0, y1;
        asm("mapa.shared::cluster.u32 %0, %1, %2;" : "=r"(y0) : "r"(sb), "r"((r + 1) % 3));
        asm("mapa.shared::cluster.u32 %0, %1, %2;" : "=r"(y1) : "r"(sb), "r"((r + 2) % 3));
        roff0 = y0 - sb; roff1 = y1 - sb;
    }
#define IDENT (((l16 >> 7) == ((l16 >> 4) & 3) ? 0x3f80u : 0u) << ((l16 >> 2) & 16))
#define LSWAP ((l16 & 0x70) | ((l16 & 0x80) << 1) | ((l16 & 0x100) >> 1))
    const uint32_t nv_remote = 8 - (8 - 2 * nq);

    if (warp < 8) {
        asm volatile("setmaxnreg.inc.sync.aligned.u32 " RG ";");
        constexpr int SSP = 36 / NSS;
#define IS_SS(kk) ((kk) % SSP == 3)
#define AI(kk) (4 * ((kk) - ((kk) + SSP - 4) / SSP))
        uint32_t a[144 - 4 * NSS];
        {
            const int ci = tid & 15, slot = ci >> 1, d0 = tid >> 4;
            const __nv_bfloat16* src = slot < nq ? Wq + (3 * r + slot) * 16 : slot < 2 * nq ? Wk + (3 * r + slot - nq) * 16 : Wv + (2 * r + slot - 2 * nq) * 16;
            src += h * 128 + (ci & 1) * 8 + d0 * 4096;
            auto issue = [&](int q) {
#pragma unroll
                for (int i = 0; i < 3; i++) if (q < 12) cp16(sb + (q * 3 + i) * 4096 + d0 * 256 + ((ci ^ (d0 & 7)) << 4), src + (size_t)(q * 3 + i) * 65536);
                asm volatile("cp.async.commit_group;" ::: "memory");
            };
            if (b < 72) {
                bar_sync(10, 256);
                mbar_wait(bar + 96, 0);
                TR1(4);
#pragma unroll 2
                for (int ag = tid >> 3; ag < 231; ag += 32) {
                    const int a = ag / 21, gr = ag % 21, tl = gr >= 18;
                    const int head = 3 * a + (tl ? 0 : (gr % 6) >> 1), nw = tl ? min(3, 32 - head) : head < 32 ? 4 : 0;
                    const uint32_t p = sb + O_RL + (tid & 7) * 3472 + (tl ? gr - 18 : gr / 6) * 1152 + head * 36 + (tl ? 32 : (gr & 1) * 16), step = tl ? 36 : 4;
                    uint32_t v[4];
#pragma unroll
                    for (int i = 0; i < 4; i++) { v[i] = lds32(p + i * step); if (i >= nw) v[i] = 0; }
                    stg128(g_wa + ((a * 9 + (b >> 3)) * 21 + gr) * 64 + (b & 7) * 8 + (tid & 7), v[0], v[1], v[2], v[3]);
                }
            }
            {
                bar_arrive(15, 288);
                TR1(5);
                delay_until(t_start, DLY0);
#pragma unroll
                for (int q = 0; q < NFL; q++) issue(q);
            }
            TR1(1);
            const int mi = lane >> 3;
            const uint32_t ad = sb + ((mi >> 1) * 8 + (lane & 7)) * 256 + (((warp * 2 + (mi & 1)) ^ (lane & 7)) << 4);
#pragma unroll
            for (int kk = 0; kk < 36; kk++) {
                if (kk % 3 == 0) { cp_wait<NFL - 1>(); issue(kk / 3 + NFL); bar_sync(10, 256); }
                const uint4 f = ldsm4t(ad + kk * 4096);
                if (IS_SS(kk)) {
                    const uint32_t o0 = sb + O_WS + (kk / SSP) * 4096 + warp * 512 + lane * 4;
                    sts32(o0, f.x); sts32(o0 + 256, f.y); sts32(o0 + 128, f.z); sts32(o0 + 384, f.w);
                } else { a[AI(kk)] = f.x; a[AI(kk) + 1] = f.y; a[AI(kk) + 2] = f.z; a[AI(kk) + 3] = f.w; }
            }
            TR1(2);
            bar_sync(9, 384);
#pragma unroll
            for (int i = 0; i < 9; i++) sts128(sb + O_H + i * 8192 + 4096 + tid * 16, 0, 0, 0, 0);
#pragma unroll
            for (int i = 0; i < 8; i++) if (i * 256 + tid < (O_OX - O_KX) / 16) sts128(sb + O_KX + i * 4096 + tid * 16, 0, 0, 0, 0);
            fence_async_smem();
            cluster_sync();
        }
        TR1(3);
        const int kind = warp < nq ? 0 : warp < 2 * nq ? 1 : 2;
        const int sl = kind == 0 ? warp : kind == 1 ? warp - nq : 2 * r + warp - 2 * nq;
        const uint32_t adX0 = sb + (kind == 0 ? O_QX : kind == 1 ? O_KX : O_VX) + sl * 2048;
        const uint32_t adM0 = sb + (kind == 0 ? O_QM : kind == 1 ? O_KM : O_VM) + sl * 512;
        const uint32_t hlo = (((sb + O_H) >> 4) & 0x3fff) | (1u << 16);
        const uint32_t mlo = (((sb + O_MB) >> 4) & 0x3fff) | (16u << 16);
        const uint32_t wlo = (((sb + O_WS + (warp >> 2) * 2048) >> 4) & 0x3fff) | (8u << 16);
        const int L = (warp >> 1) & 1, qh = warp & 1;
        const uint32_t st = sb + O_ST + warp * 1280;

#pragma unroll 1
        for (int t = -1;; t++) {
            TR_ON(t);
            OPQ();
            const uint32_t adX = adX0 + l16, adM = adM0 + l16, l8 = l16 >> 1;
            const uint32_t lq = LSWAP;
            if (t >= 0) {
                float d0[8], d1[8];
                {
#pragma unroll
                    for (int G = 0; G < 3; G++) {
                        if (warp < 4) bar_sync(1 + G, 160); else bar_sync(12 + G, 160);
                        if (G == 0) wg_fence();
#pragma unroll
                        for (int q = 0; q < 12; q++) {
                            const int kk = 12 * G + q;
                            const uint64_t db = mkdesc(mlo + kk * 32, 8);
                            if (IS_SS(kk)) wgmma_ss16t((kk & 1) ? d1 : d0, mkdesc(wlo + (kk / SSP) * 256, 16), db, 1);
                            else wgmma_rs16t((kk & 1) ? d1 : d0, a[AI(kk)], a[AI(kk) + 1], a[AI(kk) + 2], a[AI(kk) + 3], db, kk >= 2);
                            if (kk == 0) TR(0);
                        }
                    }
                    wg_commit();
                }
#define PM(i) pk(d0[2 * (i)] + d1[2 * (i)], d0[2 * (i) + 1] + d1[2 * (i) + 1])
                if (warp >= 4) {
                    wg_wait<0>();
                    TR(1);
                    const uint32_t p0 = PM(0), p1 = PM(1), p2 = PM(2), p3 = PM(3);
                    if (kind == 2) {
                        sts128(adM, p0, p1, p2, p3);
                        bar_arrive(4, 384);
                        sta128(adM + roff0, p0, p1, p2, p3, bar + B_SM + roff0);
                        sta128(adM + roff1, p0, p1, p2, p3, bar + B_SM + roff1);
                    } else {
                        stsm4t(adM, p0, p1, p2, p3);
                        bar_arrive(4, 384);
                    }
                } else {
                    uint4 q[3], k[3][2];
                    mbar_wait(bar + B_EP, t & 1);
#pragma unroll
                    for (int m = 0; m < LDP; m++) {
                        q[m] = ldsm4(sb + O_QX + m * 2048 + warp * 512 + lq);
                        k[m][0] = ldsm4(sb + O_KX + m * 2048 + L * 1024 + l16); k[m][1] = ldsm4(sb + O_KX + m * 2048 + L * 1024 + 512 + l16);
                    }
                    wg_wait<0>();
                    TR(1);
                    stsm4t(adM, PM(0), PM(1), PM(2), PM(3));
                    bar_arrive(4, 384);
                    sched_fence(gridDim.y, 6);
#pragma unroll
                    for (int m = LDP; m < 3; m++) {
                        q[m] = ldsm4(sb + O_QX + m * 2048 + warp * 512 + lq);
                        k[m][0] = ldsm4(sb + O_KX + m * 2048 + L * 1024 + l16); k[m][1] = ldsm4(sb + O_KX + m * 2048 + L * 1024 + 512 + l16);
                    }
                    float s[5][4];
                    {
                        float y[4] = {0, 0, 0, 0};
#pragma unroll
                        for (int n = 0; n < 5; n++) s[n][0] = s[n][1] = s[n][2] = s[n][3] = 0.f;
#pragma unroll
                        for (int m = 0; m < 3; m++) {
                            mma16(s[0], q[m].x, q[m].y, q[m].z, q[m].w, k[m][0].x, k[m][0].y); mma16(s[1], q[m].x, q[m].y, q[m].z, q[m].w, k[m][0].z, k[m][0].w);
                            mma16(s[2], q[m].x, q[m].y, q[m].z, q[m].w, k[m][1].x, k[m][1].y); mma16(s[3], q[m].x, q[m].y, q[m].z, q[m].w, k[m][1].z, k[m][1].w);
                        }
                        auto send = [&]() {
                            uint32_t w0 = pk(s[0][0], s[0][1]), w1 = pk(s[0][2], s[0][3]), w2 = pk(s[1][0], s[1][1]), w3 = pk(s[1][2], s[1][3]);
                            sta128(st + l16 + 5120 + roff0, w0, w1, w2, w3, bar + B_ST + roff0);
                            sta128(st + l16 + roff1, w0, w1, w2, w3, bar + B_ST + roff1);
                            w0 = pk(s[2][0], s[2][1]); w1 = pk(s[2][2], s[2][3]); w2 = pk(s[3][0], s[3][1]); w3 = pk(s[3][2], s[3][3]);
                            sta128p(st + l16 + 5120 + 512 + roff0, w0, w1, w2, w3, bar + B_ST + roff0, qh);
                            sta128p(st + l16 + 512 + roff1, w0, w1, w2, w3, bar + B_ST + roff1, qh);
                        };
                        sched_fence(gridDim.y, 7);
                        bar_sync(5, 256);
                        const uint4 k01 = ldsm4(sb + O_KM + L * 256 + l16 + (l16 & 256));
                        const uint2 k2 = ldsm2(sb + O_KM + 1024 + L * 256 + l16);
                        if (SND == 0) send();
                        mma16(s[4], q[0].x, q[0].y, q[0].z, q[0].w, k01.x, k01.y);
                        mma16(y, q[1].x, q[1].y, q[1].z, q[1].w, k01.z, k01.w);
                        mma16(s[4], q[2].x, q[2].y, q[2].z, q[2].w, k2.x, k2.y);
#pragma unroll
                        for (int j = 0; j < 4; j++) s[4][j] += y[j];
                        const uint32_t w0 = pk(s[4][0], s[4][1]), w1 = pk(s[4][2], s[4][3]);
                        if (NGAP > 0) bar_arrive(10, 256);
                        sta64(st + l8 + 5120 + 1024 + roff0, w0, w1, bar + B_ST + roff0);
                        sta64(st + l8 + 1024 + roff1, w0, w1, bar + B_ST + roff1);
                        if (SND == 1) send();
                        TR(2);
                        const int lim = 16 * qh + (int)(l16 >> 6) - (int)((l16 >> 3) & 6);
#pragma unroll
                        for (int n = 0; n < 4; n++)
#pragma unroll
                            for (int j = 0; j < 4; j++) if (!(n == 0 && j >= 2) && 8 * (n - (j >> 1)) + (j & 1) > lim) s[n][j] = -1e30f;
#pragma unroll
                        for (int n = 0; n < 4; n++) asm volatile("" : "+f"(s[n][0]), "+f"(s[n][1]), "+f"(s[n][2]), "+f"(s[n][3]));
                    }
                    uint4 v0[3], v1[3]; uint2 vm[3];
                    const uint32_t vad = sb + O_VX + 3 * r * 2048 + L * 1024 + l16;
#pragma unroll
                    for (int m = 0; m < 3; m++) v0[m] = lds128(vad + m * 2048);
                    const uint32_t otag = ring_tag(t, EP);
                    uint32_t ident = IDENT;
                    asm volatile("" : "+r"(ident));
                    mbar_wait(bar + B_SM, t & 1);
                    mbar_wait(bar + B_ST, t & 1);
                    TR(3);
                    float mx0, mx1;
                    {
                        const uint4 u = lds128(st + l16), v = lds128(st + 512 + l16); const uint2 w = lds64(st + 1024 + l8);
                        const uint4 x = lds128(st + 5120 + l16), y = lds128(st + 5120 + 512 + l16); const uint2 z = lds64(st + 5120 + 1024 + l8);
                        mma8(s[0], u.x, u.y, ident); mma8(s[1], u.z, u.w, ident); mma8(s[2], v.x, v.y, ident); mma8(s[3], v.z, v.w, ident); mma8(s[4], w.x, w.y, ident);
                        mma8(s[0], x.x, x.y, ident); mma8(s[1], x.z, x.w, ident); mma8(s[2], y.x, y.y, ident); mma8(s[3], y.z, y.w, ident); mma8(s[4], z.x, z.y, ident);
                        mx0 = fmaxf(fmaxf(fmaxf(s[0][0], s[0][1]), fmaxf(s[1][0], s[1][1])), fmaxf(fmaxf(s[2][0], s[2][1]), fmaxf(s[3][0], s[3][1])));
                        mx1 = fmaxf(fmaxf(fmaxf(s[0][2], s[0][3]), fmaxf(s[1][2], s[1][3])), fmaxf(fmaxf(s[2][2], s[2][3]), fmaxf(s[3][2], s[3][3])));
                        mx0 = fmaxf(mx0, fmaxf(s[4][0], s[4][1])); mx1 = fmaxf(mx1, fmaxf(s[4][2], s[4][3]));
                    }
#pragma unroll
                    for (int o = 1; o < 4; o <<= 1) { const float2 z = shfl2(mx0, mx1, o); mx0 = fmaxf(mx0, z.x); mx1 = fmaxf(mx1, z.y); }
                    mx0 *= -SC; mx1 *= -SC;
                    float l[4] = {0, 0, 0, 0};
                    uint32_t p[10];
#pragma unroll
                    for (int n = 0; n < 5; n++) {
                        const float e0 = ex2(fmaf(s[n][0], SC, mx0)), e1 = ex2(fmaf(s[n][1], SC, mx0));
                        const float e2 = ex2(fmaf(s[n][2], SC, mx1)), e3 = ex2(fmaf(s[n][3], SC, mx1));
                        p[2 * n] = pk(e0, e1); p[2 * n + 1] = pk(e2, e3);
                        mma8(l, p[2 * n], p[2 * n + 1], 0x3f803f80);
                    }
#pragma unroll
                    for (int m = 0; m < 3; m++) vm[m] = lds64(sb + O_VM + (3 * r + m) * 512 + l16 + L * 8);
                    sched_fence(gridDim.y, 5);
                    const float l0 = rcp(l[0]), l1 = rcp(l[2]);
                    float o[6][4];
#pragma unroll
                    for (int m = 0; m < 6; m++) o[m][0] = o[m][1] = o[m][2] = o[m][3] = 0.f;
#pragma unroll
                    for (int m = 0; m < 3; m++) { mma8(o[2 * m], p[0], p[1], v0[m].x); mma8(o[2 * m + 1], p[0], p[1], v0[m].y); }
#pragma unroll
                    for (int m = 0; m < 3; m++) { mma8(o[2 * m], p[2], p[3], v0[m].z); mma8(o[2 * m + 1], p[2], p[3], v0[m].w); v1[m] = lds128(vad + m * 2048 + 512); }
#pragma unroll
                    for (int m = 0; m < 3; m++) { mma8(o[2 * m], p[8], p[9], vm[m].x); mma8(o[2 * m + 1], p[8], p[9], vm[m].y); }
#pragma unroll
                    for (int m = 0; m < 3; m++) { mma8(o[2 * m], p[4], p[5], v1[m].x); mma8(o[2 * m + 1], p[4], p[5], v1[m].y); }
#pragma unroll
                    for (int m = 0; m < 3; m++) { mma8(o[2 * m], p[6], p[7], v1[m].z); mma8(o[2 * m + 1], p[6], p[7], v1[m].w); }
                    sched_fence(gridDim.y, 8);
                    if (t + 1 < NT) bar_arrive(11, 384);
#pragma unroll
                    for (int m = 0; m < 3; m++)
                        sts128(sb + O_OS + warp * 512 + m * 2048 + l16, (pk(o[2 * m][0] * l0, o[2 * m][1] * l0) & ~1u) | otag, pk(o[2 * m][2] * l1, o[2 * m][3] * l1),
                               pk(o[2 * m + 1][0] * l0, o[2 * m + 1][1] * l0), pk(o[2 * m + 1][2] * l1, o[2 * m + 1][3] * l1));
                    TR(4);
                }
            }
            if (t + 1 >= NT) break;
            {
                float d[32];
                if (warp < 4) bar_sync(7, 256);
                else {
                    if (warp == 7) {
                        const int u = t + 1;
                        if (t >= 0) { mbar_wait(bar + B_EP, t & 1); mbar_wait(bar + B_VX, t & 1); }
                        cnt_wait(g_cnt + (C_X + u) * 8, 64 * (EP + 1));
                        fence_async_global();
                        TRG(u, 0);
                        const bool a0 = u < NSEG, a1 = u >= LAG;
                        mbar_expect(bar + B_X, ((int)a0 + (int)a1) * 36864, l16 == 0);
                        const uint32_t off = r * 24576 + (l16 << 9) + (a0 ? 0 : 4096);
                        asm volatile("{.reg .pred p; setp.lt.u32 p, %5, %6;\n"
                            "@p cp.async.bulk.shared::cluster.global.mbarrier::complete_tx::bytes.multicast::cluster [%0], [%1], %4, [%2], %3;}"
                            :: "r"(sb + O_H + off), "l"(reinterpret_cast<const char*>(g_xt + u * 4608) + off), "r"(bar + B_X), "h"((uint16_t)7),
                               "r"(a0 && a1 ? 24576 : 4096), "r"(l16), "r"(a0 && a1 ? 16 : 48) : "memory");
                        TR(2);
                    }
                    mbar_wait(bar + B_X, (t + 1) & 1);
                    TR(3);
                    if (t >= 0) bar_sync(NGAP > 0 ? 10 : 11, NGAP > 0 ? 256 : 384);
                }
                wg_fence();
                TR(6);
#pragma unroll
                for (int kk = 0; kk < 36; kk++) {
                    if (NGAP > 0 && kk == NGAP) asm volatile("{.reg .pred p; setp.ne.u32 p, %0, 0; @p bar.sync 11, 384;}" :: "r"((uint32_t)(warp >= 4 && t >= 0)) : "memory");
                    const uint64_t db = mkdesc(hlo + ((kk >> 2) * 8192 + (kk & 3) * 32) / 16, DESC_HI);
                    if (IS_SS(kk)) wgmma_ss64(d, mkdesc(wlo + (kk / SSP) * 256, 16), db, 1);
                    else wgmma_rs64(d, a[AI(kk)], a[AI(kk) + 1], a[AI(kk) + 2], a[AI(kk) + 3], db, kk > 0);
                }
                wg_commit();
                TR(5);
                mbar_wait(bar + B_WIN, (t + 1) & 1);
                wg_wait<0>();
                TR(7);
                uint32_t p[16];
#pragma unroll
                for (int u = 0; u < 16; u++) p[u] = pk(d[2 * u], d[2 * u + 1]);
                if (kind == 2) {
#pragma unroll
                    for (int u = 0; u < 4; u++) sts128(adX + u * 512, p[4 * u], p[4 * u + 1], p[4 * u + 2], p[4 * u + 3]);
                } else {
#pragma unroll
                    for (int u = 0; u < 4; u++) stsm4t(adX + u * 512, p[4 * u], p[4 * u + 1], p[4 * u + 2], p[4 * u + 3]);
                }
                __syncwarp();
                asm volatile("{.reg .pred p; setp.eq.u32 p, %1, 0; @p mbarrier.arrive.shared.b64 _, [%0];}" :: "r"(bar + B_EP), "r"(l16) : "memory");
                TR(8);
            }
        }
        if (warp < 4) bar_arrive(7, 160); else if (NGAP > 0) bar_sync(10, 256);
        cluster_sync();
    } else {
        asm volatile("setmaxnreg.dec.sync.aligned.u32 " RW ";");
        const int w = warp - 8, t2 = tid - 256;
        if (t2 == 0) {
            mbar_init(bar + B_X, 1); mbar_init(bar + B_WIN, 3);
            mbar_init(bar + B_VX, 1); mbar_init(bar + B_SM, 1); mbar_init(bar + B_ST, 1); mbar_init(bar + B_EP, 8);
            asm volatile("fence.mbarrier_init.release.cluster;" ::: "memory");
        }
        char* const ex = reinterpret_cast<char*>((reinterpret_cast<uintptr_t>(g_ex) + 0x1fffff) & ~(uintptr_t)0x1fffff);
        char* rbase = ex; uint32_t side = 0;
        {
            uint32_t m0[5][4];
#pragma unroll
            for (int i = 0; i < 5; i++) {
                const unsigned short* m = reinterpret_cast<const unsigned short*>(mem0) + min(i * 128 + t2, DM - 1);
#pragma unroll
                for (int j = 0; j < 4; j++) m0[i][j] = m[2 * j * DM] | (m[(2 * j + 1) * DM] << 16);
            }
            if (w == 3) { bar_sync(15, 288); cnt_add(g_cnt + C_W * 8, lane); TR1(1); }
            if (t2 >= 96 && t2 < 99 && PFON) prefetch_l2((t2 == 96 ? Wq : t2 == 97 ? Wk : Wv) + b * (6 * 4096), 6 * 8192);
            delay_until(t_start, DLYW);
#pragma unroll 4
            for (int i = t2; i < 128 * 24; i += 128) {
                const int e = (i >> 3) & 127, G = i >> 10, q = i & 7;
                cp16(sb + O_WO + G * 16384 + e * 128 + ((q ^ (e & 7) ^ ((h >> 1) & 1)) << 4), Wo + (size_t)(h * 128 + e) * DM + G * 192 + r * 64 + q * 8);
            }
            bar_sync(9, 384);
#pragma unroll
            for (int i = 0; i < 5; i++) {
                const int k = min(i * 128 + t2, DM - 1);
                const uint32_t ad = sb + O_MB + (k >> 3) * 256 + (k & 7) * 16;
                sts128(ad, m0[i][0], m0[i][1], m0[i][2], m0[i][3]); sts128(ad + 128, m0[i][0], m0[i][1], m0[i][2], m0[i][3]);
            }
            fence_async_smem();
        }
        auto arm = [&]() {
            const uint32_t ln = l16 >> 4;
            mbar_expect(bar + B_VX + (ln & 3) * 8, ln == 0 ? nv_remote * 2048 : ln == 1 ? nv_remote * 512 + 2560 : 8192, ln < 3);
        };
        if (w == 3) arm();
        cluster_sync();
        TR1(3);
        const int L = w >> 1, hf = w & 1;
        const uint32_t rd = hf ? roff1 : roff0;
        const uint32_t rzero = gridDim.y + 100;
#define WOAD (sb + O_WO + ((l16 & 0x100) << 2) + ((l16 & 0x70) << 3) + (((w * 32) | ((l16 >> 3) & 16)) ^ (l16 & 0x70)))

        auto store_o = [&](int u) {
            asm volatile("{.reg .pred p; setp.eq.u32 p, %3, 0;\n"
                "@p cp.async.bulk.global.shared::cta.bulk_group [%0], [%1], %2;\n cp.async.bulk.commit_group;}"
                :: "l"(g_o + ((u & (RING - 1)) * 256 + h * 8 + 3 * r) * 128), "r"(sb + O_OS), "r"(nq * 2048), "r"(l16) : "memory");
            cnt_hint(g_cnt + (C_O + u * 8 + (h >> 2)) * 8, l16);
            TRG(u, 2);
        };
        if (w < 3) {
            bar_arrive(7, 256);
            bar_arrive(1 + w, 160); bar_arrive(12 + w, 160);
            if (w < 2) {
                unsigned* pp = reinterpret_cast<unsigned*>(ex + inbox_off(b) + 16384 + w * 4096 + 2048);
                uint32_t best = ~0u, v = 0;
                if (lane == 0) {
#pragma unroll 1
                    for (int i = 0; i < 6; i++) {
                        const uint32_t c0 = clk();
                        v = atomicAdd(pp + (v >> 31), 0);
                        asm volatile("" :: "r"(v) : "memory");
                        sts32(bar + 80, v);
                        best = min(best, clk() - c0);
                    }
                    sts32(bar + 72 + w * 4, best);
                }
            }
            bar_sync(15, 96);
            const uint32_t xs = PLACE ? lds32(bar + 76) < lds32(bar + 72) : 0, ep = EP;
            side = PLACE ? xs ^ page_par(inbox_off(b)) : 0;
            rbase = ex + inbox_off(b) + xs * 4096;
            const uint32_t inv = (ep * (NT - 1)) & 1;
#pragma unroll
            for (int i = 0; i < 4; i++) stg128(rbase + (w == 2 ? 16384 : w * 2048) + i * 512 + lane * 16, inv, 0, 0, 0);
            __threadfence();
            bar_sync(15, 96);
            if (t2 == 0) stg_word(g_side + b, (ep + 1) * 2 + xs, true);
            TR1(4);
        } else {
            mbar_arrive_all3(bar + B_WIN, l16 >> 4);

        }
        cp_wait_all();
        bar_sync(6, 128);
        uint32_t poff;
        {
            const int rb = r * 32 + w * 8 + (lane >> 2);
            const uint32_t want = EP + 1;
            uint32_t v;
            for (int n = 0; __any_sync(~0u, ((v = ldg_word(g_side + rb)) >> 1) != want); n++) fault_if(n > POLL_LIMIT, n);
            __threadfence();
            poff = inbox_off(rb) + (v & 1) * 4096 + h * 64 + (lane & 3) * 16;
        }
        side = __shfl_sync(~0u, side, 0);
        const uint32_t roff = __shfl_sync(~0u, (uint32_t)(rbase - ex), 0) + (w == 2 ? 16384 : (w & 1) * 2048);
        uint4 a0[8];
#pragma unroll
        for (int kk = 0; kk < 8; kk++) a0[kk] = ldsm4t(WOAD + kk * 2048);
        if (w == 3) { mbar_wait(bar + B_X, 0); bar_arrive(7, 256); }
#pragma unroll 1
        for (int t = 0;; t++) {
            TR_ON(t);
            OPQ();
            mbar_wait(bar + B_EP, t & 1);
            if (w == 3) {
                fence_async_smem();
                const uint32_t ad = sb + O_VX + r * 4096;
                asm volatile("{.reg .pred p; setp.eq.u32 p, %5, 0;\n"
                    "@p cp.async.bulk.shared::cluster.shared::cta.mbarrier::complete_tx::bytes [%0], [%2], %6, [%3];\n"
                    "@p cp.async.bulk.shared::cluster.shared::cta.mbarrier::complete_tx::bytes [%1], [%2], %6, [%4];}"
                    :: "r"(ad + roff0), "r"(ad + roff1), "r"(ad), "r"(bar + B_VX + roff0), "r"(bar + B_VX + roff1), "r"(l16), "r"(16384 - 4096 * nq) : "memory");
                TR(7);
            }
            uint4 kx[3][2], vx[4][2];
            const uint32_t lp = LSWAP;
#pragma unroll
            for (int m = 0; m < 3; m++) {
                kx[m][0] = ldsm4(sb + O_KX + m * 2048 + L * 1024 + lp);
                kx[m][1] = ldsm4(sb + O_KX + m * 2048 + L * 1024 + 512 + lp);
            }
            if (w == 3) asm volatile("cp.async.bulk.wait_group.read 0;" ::: "memory");
            mbar_wait(bar + B_VX, t & 1);
            TR(0);
            bar_sync(4, 384);
            float s0[4] = {0, 0, 0, 0}, s1[4] = {0, 0, 0, 0}, sm[4] = {0, 0, 0, 0};
            {
                const uint4 q01 = ldsm4(sb + O_QM + L * 256 + l16 + (l16 & 256));
                const uint2 q2 = ldsm2(sb + O_QM + 1024 + L * 256 + l16);
                uint4 km_[3];
#pragma unroll
                for (int m = 0; m < 3; m++) km_[m] = ldsm4(sb + O_KM + m * 512 + (lp ^ (L << 8)));
                bar_arrive(5, 256);
                mma16(s0, kx[0][0].x, kx[0][0].y, kx[0][0].z, kx[0][0].w, q01.x, q01.y);
                mma16(s1, kx[0][1].x, kx[0][1].y, kx[0][1].z, kx[0][1].w, q01.x, q01.y);
                mma16(sm, km_[0].x, km_[0].y, km_[0].z, km_[0].w, q01.x, q01.y);
                mma16(s0, kx[1][0].x, kx[1][0].y, kx[1][0].z, kx[1][0].w, q01.z, q01.w);
                mma16(s1, kx[1][1].x, kx[1][1].y, kx[1][1].z, kx[1][1].w, q01.z, q01.w);
                mma16(sm, km_[1].x, km_[1].y, km_[1].z, km_[1].w, q01.z, q01.w);
                mma16(s0, kx[2][0].x, kx[2][0].y, kx[2][0].z, kx[2][0].w, q2.x, q2.y);
                mma16(s1, kx[2][1].x, kx[2][1].y, kx[2][1].z, kx[2][1].w, q2.x, q2.y);
                mma16(sm, km_[2].x, km_[2].y, km_[2].z, km_[2].w, q2.x, q2.y);
                const uint32_t ad = sb + O_SM + (1 - hf) * 1280 + L * 640 + rd;
                sta128(ad + l16, pk(s0[0], s0[1]), pk(s0[2], s0[3]), pk(s1[0], s1[1]), pk(s1[2], s1[3]), bar + B_SM + rd);
                sta32(ad + 512 + (l16 >> 2), pk(sm[0], sm[1]), bar + B_SM + rd);
            }
            TR(1);
            if (t + 1 == NT) break;
#pragma unroll
            for (int m = 0; m < 8; m++) vx[m >> 1][m & 1] = lds128(sb + O_VX + (hf * 4 + (m >> 1)) * 2048 + L * 1024 + (m & 1) * 512 + l16);
            const uint32_t tag = (t + EP * (NT - 1) + 1) & 1;
            uint32_t ident = IDENT;
            asm volatile("" : "+r"(ident));
            mbar_wait(bar + B_SM, t & 1);
            TR(2);
            {
                const uint32_t ad = sb + O_SM + L * 640;
                const uint4 u = lds128(ad + l16), v = lds128(ad + 1280 + l16);
                const uint32_t x = lds32(ad + 512 + (l16 >> 2)), y = lds32(ad + 1280 + 512 + (l16 >> 2));
                mma8(s0, u.x, u.y, ident); mma8(s1, u.z, u.w, ident); mma8(s0, v.x, v.y, ident); mma8(s1, v.z, v.w, ident);
                sm[0] += bf_lo(x) + bf_lo(y); sm[1] += bf_hi(x) + bf_hi(y);
            }
            uint2 vm[4];
#pragma unroll
            for (int m = 0; m < 4; m++) vm[m] = lds64(sb + O_VM + (hf * 4 + m) * 512 + l16 + L * 8);
            float mx0 = fmaxf(fmaxf(fmaxf(s0[0], s0[2]), fmaxf(s1[0], s1[2])), sm[0]);
            float mx1 = fmaxf(fmaxf(fmaxf(s0[1], s0[3]), fmaxf(s1[1], s1[3])), sm[1]);
#pragma unroll
            for (int o = 4; o < 32; o <<= 1) { mx0 = fmaxf(mx0, __shfl_xor_sync(~0u, mx0, o)); mx1 = fmaxf(mx1, __shfl_xor_sync(~0u, mx1, o)); }
            mx0 *= -SC; mx1 *= -SC;
            s0[0] = ex2(fmaf(s0[0], SC, mx0)); s0[1] = ex2(fmaf(s0[1], SC, mx1));
            s0[2] = ex2(fmaf(s0[2], SC, mx0)); s0[3] = ex2(fmaf(s0[3], SC, mx1));
            const uint32_t pb0 = movm(pk(s0[0], s0[1])), pb1 = movm(pk(s0[2], s0[3]));
            s1[0] = ex2(fmaf(s1[0], SC, mx0)); s1[1] = ex2(fmaf(s1[1], SC, mx1));
            s1[2] = ex2(fmaf(s1[2], SC, mx0)); s1[3] = ex2(fmaf(s1[3], SC, mx1));
            const uint32_t pb2 = movm(pk(s1[0], s1[1])), pb3 = movm(pk(s1[2], s1[3]));
            sm[0] = ex2(fmaf(sm[0], SC, mx0)); sm[1] = ex2(fmaf(sm[1], SC, mx1));
            const uint32_t pm = movm(pk(sm[0], sm[1]));
            float o[4][4], l[4] = {0, 0, 0, 0};
            const uint32_t one = 0x3f803f80;
            mma8(l, one, one, pb0); mma8(l, one, one, pb1);
#pragma unroll
            for (int m = 0; m < 4; m++) { o[m][0] = o[m][1] = o[m][2] = o[m][3] = 0.f; mma16(o[m], vx[m][0].x, vx[m][0].y, vx[m][0].z, vx[m][0].w, pb0, pb1); }
            mma8(l, one, one, pb2); mma8(l, one, one, pb3);
#pragma unroll
            for (int m = 0; m < 4; m++) mma16(o[m], vx[m][1].x, vx[m][1].y, vx[m][1].z, vx[m][1].w, pb2, pb3);
            mma8(l, one, one, pm);
#pragma unroll
            for (int m = 0; m < 4; m++) mma8(o[m], vm[m].x, vm[m].y, pm);
            const float l0 = rcp(l[0]), l1 = rcp(l[1]);
#pragma unroll
            for (int m = 0; m < 4; m += 2)
                stsm4t(sb + O_OX + (hf * 4 + m) * 512 + (L ^ ((h >> 2) & 1)) * 256   + ((l16 & 0x100) << 1) + (l16 & 0xf0),
                       pk(o[m][0] * l0, o[m][1] * l1), pk(o[m][2] * l0, o[m][3] * l1), pk(o[m + 1][0] * l0, o[m + 1][1] * l1), pk(o[m + 1][2] * l0, o[m + 1][3] * l1));
            TR(3);
            char* const pdst = ex + poff;
            const char* const rsrc = ex + roff + l16;
            uint4 v[4] = {};
            bar_sync(6, 128);
            {
                uint4 bo[8], a1[8], z;
                const uint32_t wad = WOAD;
#pragma unroll
                for (int kk = 0; kk < 8; kk++) bo[kk] = ldsm4(sb + O_OX + kk * 512 + l16);
#pragma unroll
                for (int G = 0; G < 3; G++) {
                    float e[4][4];
#pragma unroll
                    for (int q = 0; q < 4; q++) e[q][0] = e[q][1] = e[q][2] = e[q][3] = 0.f;
#pragma unroll
                    for (int kk = 0; kk < 8; kk++) {
                        const uint4 f = G == 0 ? a0[kk] : a1[kk];
                        mma16(e[(kk & 1) * 2], f.x, f.y, f.z, f.w, bo[kk].x, bo[kk].y);
                        mma16(e[(kk & 1) * 2 + 1], f.x, f.y, f.z, f.w, bo[kk].z, bo[kk].w);
                        if (G == 2 && kk == EK) {
#pragma unroll
                            for (int i = 0; i < 4; i++) { v[i].x = ~tag; ldg_pkt_if(v[i], rsrc + i * 512, w < EARLY); }
                            sched_fence(rzero, 5);
                            bar_arrive(11, 384);
                        }
                        if (G == 1) a1[kk] = ldsm4t(wad + 32768 + kk * 2048);
                        if (G == 0 && kk == FK) {
                            sched_fence(rzero, 2);
#pragma unroll
                            for (int j = 0; j < 8; j++) a1[j] = ldsm4t(wad + 16384 + j * 2048);
                        }
                    }
                    if (G > 0) asm volatile("{.reg .pred p; setp.eq.u32 p, %5, 0; @p st.shared.v4.u32 [%0], {%1,%2,%3,%4};}" :: "r"(__float_as_uint(e[0][0])), "r"(z.x), "r"(z.y), "r"(z.z), "r"(z.w), "r"(rzero));
                    z = make_uint4((pk(e[0][0] + e[2][0], e[0][1] + e[2][1]) & ~1u) | tag, pk(e[0][2] + e[2][2], e[0][3] + e[2][3]),
                                   pk(e[1][0] + e[3][0], e[1][1] + e[3][1]), pk(e[1][2] + e[3][2], e[1][3] + e[3][3]));
                    stg_pkt(pdst + (G == 2 ? 16384 : G * 2048), z.x, z.y, z.z, z.w);
                    if (G == 0) { TR(9); TRD(t, 0); }
                    if (G < 2) sched_fence(rzero, 3 + G);
                }
            }
            TR(4);
            if (w < 3) {
                bar_arrive(7, 256);
                OPQ();
                const uint32_t tagm = tag;
                uint32_t m0v = 0;
                if (t + 1 <= LAG) {
                    const unsigned short* m = reinterpret_cast<const unsigned short*>(mem0) + ((l16 >> 3) & 6) * DM + 192 * w + 16 * (b >> 3) + (b & 7) + ((l16 >> 4) & 8);
                    m0v = m[0] | (m[DM] << 16);
                }
                delay(DLY1);
                for (int n = 0; __any_sync(~0u, lop_bad(lop_bad(0, v[0].x, v[1].x, tagm), v[2].x, v[3].x, tagm) & 1); n++) {
#pragma unroll
                    for (int i = 0; i < 4; i++) v[i] = ldg_pkt(rsrc + i * 512);
                    fault_if(n > POLL_LIMIT, n);
                }
                TR(5); TRD(t, 1);
                float s[8];
                s[4] = (bf_lo(v[0].z) + bf_lo(v[1].z)) + (bf_lo(v[2].z) + bf_lo(v[3].z)); s[5] = (bf_hi(v[0].z) + bf_hi(v[1].z)) + (bf_hi(v[2].z) + bf_hi(v[3].z));
                s[6] = (bf_lo(v[0].w) + bf_lo(v[1].w)) + (bf_lo(v[2].w) + bf_lo(v[3].w)); s[7] = (bf_hi(v[0].w) + bf_hi(v[1].w)) + (bf_hi(v[2].w) + bf_hi(v[3].w));
                s[2] = (bf_lo(v[0].y) + bf_lo(v[1].y)) + (bf_lo(v[2].y) + bf_lo(v[3].y)); s[3] = (bf_hi(v[0].y) + bf_hi(v[1].y)) + (bf_hi(v[2].y) + bf_hi(v[3].y));
                s[0] = (bf_lo(v[0].x) + bf_lo(v[1].x)) + (bf_lo(v[2].x) + bf_lo(v[3].x)); s[1] = (bf_hi(v[0].x) + bf_hi(v[1].x)) + (bf_hi(v[2].x) + bf_hi(v[3].x));
#pragma unroll
                for (int j = 0; j < 4; j++) s[j] += __shfl_xor_sync(~0u, s[j + 4], 16);
#pragma unroll
                for (int j = 0; j < 2; j++) s[j] += __shfl_xor_sync(~0u, s[j + 2], 8);
#pragma unroll
                for (int j = 0; j < 2; j++) s[j] += __shfl_xor_sync(~0u, s[j], 4);
                char* const mem_w = ex + mem_off(w, 0);
                uint32_t res = t + 1 <= LAG && l16 >= 256 ? m0v : pk(s[0], s[1]);
                if ((l16 & 48) == 0) res = (res & ~1u) | tag;
                stg_word(mem_w + (mem_off(0, b >> 3) - mem_off(0, 0)) + (b & 7) * 16 + (((l16 & 64) << 6) + ((l16 & 128) << 1) + ((l16 & 256) >> 1) + ((l16 >> 2) & 12)), res, true);
                if (w + 5 == XST) bar_arrive(8, 64);
                TR(6); TRD(t, 2);
                delay(DLY2);
                const char* src = mem_w + (side ^ page_par(0x180000)) * 4096 + l16;
                const uint32_t gdst = sb + O_MB + w * 6144 + l16;
                uint4 x[12];
#pragma unroll
                for (int i = 0; i < 12; i++) x[i] = ldg_pkt(src + (mem_off(0, i) - mem_off(0, 0)));
                for (int n = 0;; n++) {
                    uint32_t bad = 0;
#pragma unroll
                    for (int i = 0; i < 12; i += 2) bad = lop_bad(bad, x[i].x, x[i + 1].x, tagm);
                    if (!__any_sync(~0u, bad & 1)) break;
#pragma unroll
                    for (int i = 0; i < 12; i++) ldg_pkt_retry(x[i], src + (mem_off(0, i) - mem_off(0, 0)), tagm);
                    fault_if(n > POLL_LIMIT, n);
                }
#pragma unroll
                for (int i = 0; i < 12; i++) sts128(gdst + i * 512, x[i].x, x[i].y, x[i].z, x[i].w);
                TR(7); TRD(t, 3);
                fence_async_smem();
                bar_arrive(12 + w, 160);
                bar_arrive(1 + w, 160);
                TR(8);
            } else {
                mbar_wait(bar + B_X, (t + 1) & 1);
                bar_sync(7, 256);
                fence_async_smem();
                arm();
                __syncwarp();
                mbar_arrive_all3(bar + B_WIN, l16 >> 4);
                if (XST > 4) bar_sync(8, 64);
                delay(DLYO);
                store_o(t);
                TR(5);
            }
        }
        if (w == 3) { bar_sync(7, 160); fence_async_smem(); store_o(NT - 1); asm volatile("cp.async.bulk.wait_group 0;" ::: "memory"); }
        cluster_sync();
    }
    TR_DUMP(b);
}

#define VG 12
#define HB 3
#define HA 2
#define HW 0
namespace ka {
constexpr int O_WA = 196608;
constexpr int A_KB = 21504;
constexpr int O_RING = 194560;
constexpr int O_BAR = 230400;
constexpr int SMEM = O_BAR + 256 + 1024;
constexpr float SC = 0.23570226039551584f * 1.4426950408889634f;
}

template <int NP, int KB = 4096>
DEVI void row_task(const uint4* res, const uint4* part, uint4* xout, char* img, int pos, int lane, uint32_t tag) {
    const bool on = lane < 24;
    const int ln = on ? lane : 0;
    uint4 rv[3], pv[NP > 0 ? NP * 3 : 1];
#pragma unroll
    for (int i = 0; i < 3; i++) rv[i] = ldg128(res + i * 24 + ln);
#pragma unroll
    for (int i = 0; i < NP * 3; i++) pv[i] = ldg_pkt(part + i * 24 + ln);
    if (NP > 0) validate<NP * 3>(pv, part + ln, 384, tag);
#pragma unroll
    for (int q = 0; q < NP * 3 / 2; q++) {
        const uint4 y = pv[q + NP * 3 / 2];
        pv[q] = make_uint4(add2(pv[q].x, y.x), add2(pv[q].y, y.y), add2(pv[q].z, y.z), add2(pv[q].w, y.w));
    }
    float x[24];
#pragma unroll
    for (int i = 0; i < 3; i++) {
        x[8 * i] = bf_lo(rv[i].x); x[8 * i + 1] = bf_hi(rv[i].x); x[8 * i + 2] = bf_lo(rv[i].y); x[8 * i + 3] = bf_hi(rv[i].y);
        x[8 * i + 4] = bf_lo(rv[i].z); x[8 * i + 5] = bf_hi(rv[i].z); x[8 * i + 6] = bf_lo(rv[i].w); x[8 * i + 7] = bf_hi(rv[i].w);
    }
    if (NP > 0) {
#pragma unroll
        for (int q = 0; q < NP * 3 / 2; q++) {
            const int i = q % 3;
            x[8 * i] += bf_lo(pv[q].x); x[8 * i + 1] += bf_hi(pv[q].x); x[8 * i + 2] += bf_lo(pv[q].y); x[8 * i + 3] += bf_hi(pv[q].y);
            x[8 * i + 4] += bf_lo(pv[q].z); x[8 * i + 5] += bf_hi(pv[q].z); x[8 * i + 6] += bf_lo(pv[q].w); x[8 * i + 7] += bf_hi(pv[q].w);
        }
#pragma unroll
        for (int i = 0; i < 3; i++) {
            uint32_t w[4];
#pragma unroll
            for (int j = 0; j < 4; j++) { w[j] = pk(x[8 * i + 2 * j], x[8 * i + 2 * j + 1]); x[8 * i + 2 * j] = bf_lo(w[j]); x[8 * i + 2 * j + 1] = bf_hi(w[j]); }
            stg128p(xout + i * 24 + ln, w[0], w[1], w[2], w[3], on);
        }
    }
    if (img) {
        float s = 0.f;
#pragma unroll
        for (int j = 0; j < 24; j++) s += x[j];
        if (!on) s = 0.f;
#pragma unroll
        for (int o = 1; o < 32; o <<= 1) s += __shfl_xor_sync(~0u, s, o);
        const float mean = s * (1.f / DM);
        float v = 0.f;
#pragma unroll
        for (int j = 0; j < 24; j++) { x[j] -= mean; v = fmaf(x[j], x[j], v); }
        if (!on) v = 0.f;
#pragma unroll
        for (int o = 1; o < 32; o <<= 1) v += __shfl_xor_sync(~0u, v, o);
        const float rs = rsqrtf(v * (1.f / DM) + 1e-5f);
        char* dst = img + (ln >> 3) * KB + pos * 128 + (((ln ^ pos) & 7) << 4);
#pragma unroll
        for (int i = 0; i < 3; i++)
            stg128p(dst + i * (3 * KB), pk(x[8 * i] * rs, x[8 * i + 1] * rs), pk(x[8 * i + 2] * rs, x[8 * i + 3] * rs),
                    pk(x[8 * i + 4] * rs, x[8 * i + 5] * rs), pk(x[8 * i + 6] * rs, x[8 * i + 7] * rs), on);
    }
}

DEVI void rows_a(const uint4* xin, int f, int i, int lane, uint32_t ep, int warp) {
    for (int u = 0; u < LAG; u++) cnt_hint(g_cnt + (C_X + u + (f ? 0 : NSEG)) * 8, lane);
#pragma unroll 1
    for (int seg = 0; seg < NSEG; seg++) {
        const int j = seg + f * LAGA, u = seg + f * LAG, row = seg * 32 + i;
        hint_wait(g_cnt + (C_WA + j * 4 + f * 2 + (i & 1)) * 8, 24 * (ep + 1));
        TRG(u, 0);
        row_task<4, 8192>((f ? g_x + 2048 * 72 : xin) + row * 72, g_pa + ((j & (RING - 1)) * 64 + f * 32 + i) * 288,
                    g_x + (f * 4096 + row) * 72, reinterpret_cast<char*>(g_xt + u * 4608 + f * 256), i, lane, ring_tag<NTA>(j, ep));
        TRG(u, 1);
        cnt_add(g_cnt + (C_X + u) * 8, lane);
        TRG(u, 2);
    }
}

__global__ void __launch_bounds__(384, 1)
k_aux(const __nv_bfloat16* __restrict__ x0, const __nv_bfloat16* __restrict__ wqkv, const __nv_bfloat16* __restrict__ wo,
      const __nv_bfloat16* __restrict__ Wo, __nv_bfloat16* __restrict__ out) {
    using namespace ka;
    extern __shared__ unsigned char smem_raw[];
    const uint32_t sb = (smem_u32(smem_raw) + 1023) & ~1023u;
    const int tid = threadIdx.x, lane = tid & 31, warp = __shfl_sync(~0u, tid >> 5, 0), g = lane >> 2, c = lane & 3;
    const int b = blockIdx.x;
    const uint32_t bar = sb + O_BAR;
    const uint32_t ep = __shfl_sync(~0u, ldg32(&g_epoch), 0);

    TRG(79, 0);
    const uint4* xin = reinterpret_cast<const uint4*>(x0);
    if (warp >= 8 || b == 35) {
        asm volatile("setmaxnreg.dec.sync.aligned.u32 128;");
        const int rw = b < 24 ? (warp - 8) * 24 + b : b < 35 ? (warp - 8) * 11 + b - 24 : 96 + 2 * warp;
        if (b < 24 || b == 35) {
#pragma unroll 1
            for (int row = rw; row < 2048; row += (row & 1) ? 23 : 1) {
                if (lane == 0 && b == 35 && row < 2024) prefetch_l2(xin + (row + 24) * 72, 1152);
                row_task<0>(xin + row * 72, nullptr, nullptr, reinterpret_cast<char*>(g_xa + (row >> 5) * 4608), (row & 1) * 16 + ((row & 31) >> 1), lane, 0);
                if (b < 24) { cnt_add(g_cnt + (C_N0 + (row >> 5)) * 8, lane); break; }
                if (row & 1) cnt_add<2>(g_cnt + (C_N0 + (row >> 5)) * 8, lane);
            }
        }
        if (rw < 32) {
            const int f = b < 24, i = rw;
#pragma unroll 1
            for (int seg = 0; seg < NSEG; seg++) {
                const int u = seg + f * LAG, row = seg * 32 + i;
                hint_wait(g_cnt + (C_WB + u * 4 + f * 2 + (i >> 4)) * 8, 24 * (ep + 1));
                TRG(u, 0);
                row_task<8>(g_x + (f * 4096 + row) * 72, g_pb + ((u & (RING - 1)) * 64 + f * 32 + i) * 576,
                            f ? reinterpret_cast<uint4*>(out) + row * 72 : g_x + (2048 + row) * 72,
                            f ? nullptr : reinterpret_cast<char*>(g_xa + (seg + LAGA) * 4608 + 2304), (i & 1) * 16 + (i >> 1), lane, ring_tag(u, ep));
                TRG(u, 1);
                cnt_add(g_cnt + (C_RB + f * NSEG + seg) * 8, lane);
                TRG(u, 2);
            }
            if (f && rw == 31) {
                asm volatile("griddepcontrol.wait;" ::: "memory");
                if (lane == 0) g_epoch = ep + 1;
            }
        } else if (rw < 64 && b < 24) rows_a(xin, 0, rw - 32, lane, ep, warp);
        return;
    }

    if (b < 24) {
        if (warp >= 4) {
            const int kq = b / 6, nq = b % 6;
            uint4 v[17];
#pragma unroll
            for (int q = 0; q < 17; q++) {
                const int it = q * 4 + warp - 4, kr = (it / 3) * 8 + g, s = kq * 11 + (kr >> 4), a = s >> 2, j = s & 3, e = kr & 15;
                const int head = 3 * a + (j < 3 ? j : e >> 1), row = head * 18 + (j < 3 ? e : 16 + (e & 1));
                v[q] = make_uint4(0, 0, 0, 0);
                if (it < 66 && head < 32 && (j < 3 || e < 6)) v[q] = *reinterpret_cast<const uint4*>(wo + row * DM + nq * 96 + (it % 3) * 32 + c * 8);
            }
#pragma unroll
            for (int q = 0; q < 17; q++) {
                const int it = q * 4 + warp - 4;
                const uint32_t ad = sb + O_WA + (it % 3) * 4 * 2816 + (it / 3) * 128 + lane * 4;
                if (it < 66) { sts32(ad, v[q].x); sts32(ad + 2816, v[q].y); sts32(ad + 2 * 2816, v[q].z); sts32(ad + 3 * 2816, v[q].w); }
            }
        } else {
            const int kg = b / 3, ng = b % 3;
            delay(DLYB);
#pragma unroll 1
            for (int bt = 0; bt < 4; bt++) {
                uint4 v[24];
#pragma unroll
                for (int q = 0; q < 24; q++)
                    v[q] = *reinterpret_cast<const uint4*>(Wo + (size_t)(kg * 512 + (bt * 4 + q / 6) * 32 + warp * 8 + g) * DM + ng * 192 + (q % 6) * 32 + c * 8);
#pragma unroll
                for (int q = 0; q < 24; q++) {
                    const uint32_t ad = sb + (q % 6) * 4 * 8192 + ((bt * 4 + q / 6) * 4 + warp) * 128 + lane * 4;
                    sts32(ad, v[q].x); sts32(ad + 8192, v[q].y); sts32(ad + 2 * 8192, v[q].z); sts32(ad + 3 * 8192, v[q].w);
                }
            }
        }
        fence_async_smem();
        bar_sync(2 + (warp >> 2), 128);
    } else {
        for (int i = tid; i < 2048; i += 256) sts128(sb + O_RING + i * 16, 0, 0, 0, 0);
        if (tid < 17) mbar_init(bar + tid * 8, tid >= 4 && tid < 8 ? 4 : 1);
        fence_async_smem();
        bar_sync(1, 256);
    }
    TRG(79, 1);
    const int wq = warp & 3;

    if (warp < 4) {
        asm volatile("setmaxnreg.inc.sync.aligned.u32 256;");
        if (b < 24) {
            const int kg = b / 3, ng = b % 3;
            const uint32_t blo = ((sb >> 4) & 0x3fff) | (8u << 16);
            uint4 a[32];
            bool pre = false;
#pragma unroll 1
            for (int u = 0; u < NT; u++) {
                const uint32_t tag = ring_tag(u, ep);
                const uint4* src = g_o + (((u & (RING - 1)) * 256 + kg * 32) * 4 + wq) * 32 + lane;
                if (!pre) {
                    hint_wait(g_cnt + (C_O + u * 8 + kg) * 8, 12 * (ep + 1));
#pragma unroll
                    for (int i = 0; i < VG; i++) a[i] = ldg_pkt(src + i * 128);
                }
                TRG(u, 0);
                float d[96];
                validate<VG>(a, src, 2048, tag);
#pragma unroll
                for (int i = VG; i < 32; i++) a[i] = ldg_pkt(src + i * 128);
                wg_fence();
#pragma unroll
                for (int i = 0; i < 32; i++) {
                    if (i == VG) { validate<32 - VG>(a + VG, src + VG * 128, 2048, tag); wg_fence(); }
                    wgmma_rs192t(d, a[i].x, a[i].y, a[i].z, a[i].w, mkdesc(blo + i * 16, 512), i > 0);
                    if (i == 23 || i == 31) wg_commit();
                }
                wg_wait<1>();
                pre = u + 1 < NT && __all_sync(~0u, ldg_word(g_cnt + (C_O + (u + 1) * 8 + kg) * 8) >= 12 * (ep + 1));
                if (pre) {
                    const uint4* nx = g_o + ((((u + 1) & (RING - 1)) * 256 + kg * 32) * 4 + wq) * 32 + lane;
#pragma unroll
                    for (int i = 0; i < VG; i++) a[i] = ldg_pkt(nx + i * 128);
                }
                wg_wait<0>();
                TRG(u, 1);
                uint4* dst = g_pb + (((u & (RING - 1)) * 64 + wq * 16 + g) * 8 + kg) * 72 + ng * 24 + c;
#pragma unroll
                for (int m = 0; m < 6; m++) {
                    if (m == HB) cnt_hint(g_cnt + (C_WB + u * 4 + wq) * 8, lane);
                    stg128(dst + 4 * m, (pk(d[16 * m], d[16 * m + 1]) & ~1u) | tag, pk(d[16 * m + 4], d[16 * m + 5]), pk(d[16 * m + 8], d[16 * m + 9]), pk(d[16 * m + 12], d[16 * m + 13]));
                    stg128(dst + 4 * m + 8 * 576, (pk(d[16 * m + 2], d[16 * m + 3]) & ~1u) | tag, pk(d[16 * m + 6], d[16 * m + 7]), pk(d[16 * m + 10], d[16 * m + 11]), pk(d[16 * m + 14], d[16 * m + 15]));
                }
                TRG(u, 3);
            }
        } else {
            const int a = b - 24, f = wq >> 1;
            const uint32_t blo = ((sb >> 4) & 0x3fff) | (8u << 16), alo = (((sb + O_RING) >> 4) & 0x3fff) | (1u << 16);
            const bool m0 = 2 * c <= g, m1 = 2 * c + 1 <= g;
            const uint32_t M = (m0 ? 0xffffu : 0u) | (m1 ? 0xffff0000u : 0u);
            uint32_t kh[7], vh[7];
#pragma unroll
            for (int i = 0; i < 7; i++) kh[i] = vh[i] = 0;
            int it = 0;
#pragma unroll 1
            for (int u = 0; u < NTA; u++) {
                float d[84];
#pragma unroll 1
                for (int kb = 0; kb < 9; kb++, it++) {
                    mbar_wait(bar + (it & 3) * 8, (it >> 2) & 1);
                    if (u == 0) mbar_wait(bar + 64 + kb * 8, 0);
                    if (kb == 0) TRG(u, 0);
                    wg_fence();
#pragma unroll
                    for (int q = 0; q < 4; q++)
                        wgmma_ss168t(d, mkdesc(alo + (it & 3) * 512 + q * 2, km::DESC_HI), mkdesc(blo + kb * (A_KB >> 4) + q * 16, 64), kb + q > 0);
                    wg_commit();
                    wg_wait<1>();
                    mbar_arrive(bar + 32 + ((it - 1) & 3) * 8, lane == 0 && kb > 0);
                }
                wg_wait<0>();
                mbar_arrive(bar + 32 + ((it - 1) & 3) * 8, lane == 0);
                TRG(u, 1);
                const bool first = u == f * LAGA;
                const uint32_t tag = ring_tag<NTA>(u, ep);
                const uint32_t qt0 = pk(d[72], d[73]), qt1 = pk(d[74], d[75]), kt0 = pk(d[76], d[77]), kt1 = pk(d[78], d[79]);
                const uint32_t vt0 = movm(pk(d[80], d[81])), vt1 = movm(pk(d[82], d[83]));
                float ot[4] = {0, 0, 0, 0};
                uint4* dst = g_oa + (((u & (RING - 1)) * 4 + wq) * 44 + a * 4) * 32 + lane;
#pragma unroll
                for (int h = 0; h < 3; h++) {
                    const float* q = d + 8 * h; const float* k = d + 24 + 8 * h; const float* v = d + 48 + 8 * h;
                    const uint32_t q0 = pk(q[0], q[1]), q1 = pk(q[2], q[3]), q2 = pk(q[4], q[5]), q3 = pk(q[6], q[7]);
                    const uint32_t k0 = pk(k[0], k[1]), k1 = pk(k[4], k[5]), k2 = pk(k[2], k[3]), k3 = pk(k[6], k[7]);
                    const uint32_t v0 = movm(pk(v[0], v[1])), v1 = movm(pk(v[2], v[3])), v2 = movm(pk(v[4], v[5])), v3 = movm(pk(v[6], v[7]));
                    const uint32_t t0 = c == h ? qt0 : 0, t1 = c == h ? qt1 : 0;
                    float sp[4] = {0, 0, 0, 0}, sl[4] = {0, 0, 0, 0}, sh[4] = {0, 0, 0, 0};
                    mma16(sp, q0, q1, q2, q3, kh[2 * h], kh[2 * h + 1]); mma16(sl, q0, q1, q2, q3, k0, k1); mma16(sh, q0, q1, q2, q3, k2, k3);
                    mma8(sp, t0, t1, kh[6]); mma8(sl, t0, t1, kt0); mma8(sh, t0, t1, kt1);
                    float x0_ = m0 ? sl[0] : first ? -INFINITY : sp[0], x1_ = m1 ? sl[1] : first ? -INFINITY : sp[1];
                    float y0_ = m0 ? sh[2] : sl[2], y1_ = m1 ? sh[3] : sl[3];
                    float mx = fmaxf(x0_, x1_), my = fmaxf(y0_, y1_);
#pragma unroll
                    for (int o = 1; o < 4; o <<= 1) { mx = fmaxf(mx, __shfl_xor_sync(~0u, mx, o)); my = fmaxf(my, __shfl_xor_sync(~0u, my, o)); }
                    mx *= -SC; my *= -SC;
                    x0_ = ex2(fmaf(x0_, SC, mx)); x1_ = ex2(fmaf(x1_, SC, mx)); y0_ = ex2(fmaf(y0_, SC, my)); y1_ = ex2(fmaf(y1_, SC, my));
                    float lx = x0_ + x1_, ly = y0_ + y1_;
#pragma unroll
                    for (int o = 1; o < 4; o <<= 1) { lx += __shfl_xor_sync(~0u, lx, o); ly += __shfl_xor_sync(~0u, ly, o); }
                    lx = rcp(lx); ly = rcp(ly);
                    const uint32_t px = pk(x0_ * lx, x1_ * lx), py = pk(y0_ * ly, y1_ * ly);
                    const uint32_t hm = (g >> 1) == h ? ~0u : 0u;
                    float o0[4] = {0, 0, 0, 0}, o1[4] = {0, 0, 0, 0};
                    mma16(o0, px & M, py & ~M, 0, py & M, v0, v1); mma16(o1, px & M, py & ~M, 0, py & M, v2, v3);
                    mma16(ot, px & M, py & ~M, 0, py & M, vt0 & hm, vt1 & hm);
                    mma8(o0, px & ~M, 0, vh[2 * h]); mma8(o1, px & ~M, 0, vh[2 * h + 1]); mma8(ot, px & ~M, 0, vh[6] & hm);
                    if (h == HA) cnt_hint(g_cnt + (C_A + u * 4 + wq) * 8, lane);
                    stg128(dst + h * 32, (pk(o0[0], o0[1]) & ~1u) | tag, pk(o0[2], o0[3]), pk(o1[0], o1[1]), pk(o1[2], o1[3]));
                    kh[2 * h] = k2; kh[2 * h + 1] = k3; vh[2 * h] = v1; vh[2 * h + 1] = v3;
                }
                kh[6] = kt1; vh[6] = vt1;
                stg128(dst + 96, (pk(ot[0], ot[1]) & ~1u) | tag, pk(ot[2], ot[3]), 0, 0);
                TRG(u, 2);
            }
        }
    } else {
        asm volatile("setmaxnreg.dec.sync.aligned.u32 120;");
        if (b < 24) {
            const int kq = b / 6, nq = b % 6;
            const uint32_t blo = (((sb + O_WA) >> 4) & 0x3fff) | (8u << 16);
#pragma unroll 1
            for (int u = 0; u < NTA; u++) {
                hint_wait(g_cnt + (C_A + u * 4 + wq) * 8, 11 * (ep + 1));
                const uint32_t tag = ring_tag<NTA>(u, ep);
                TRG(u, 0);
                const uint4* src = g_oa + (((u & (RING - 1)) * 4 + wq) * 44 + kq * 11) * 32 + lane;
                uint4 a[11];
                float d[48];
#pragma unroll
                for (int i = 0; i < 11; i++) a[i] = ldg_pkt(src + i * 32);
                validate<11>(a, src, 512, tag);
                wg_fence();
#pragma unroll
                for (int i = 0; i < 11; i++) wgmma_rs96t(d, a[i].x, a[i].y, a[i].z, a[i].w, mkdesc(blo + i * 16, 176), i > 0);
                wg_commit();
                wg_wait<0>();
                TRG(u, 1);
                uint4* dst = g_pa + (((u & (RING - 1)) * 64 + (wq >> 1) * 32 + 2 * g + (wq & 1)) * 4 + kq) * 72 + nq * 12 + c;
#pragma unroll
                for (int m = 0; m < 3; m++) {
                    if (m == HW) cnt_hint(g_cnt + (C_WA + u * 4 + wq) * 8, lane);
                    stg128(dst + 4 * m, (pk(d[16 * m], d[16 * m + 1]) & ~1u) | tag, pk(d[16 * m + 4], d[16 * m + 5]), pk(d[16 * m + 8], d[16 * m + 9]), pk(d[16 * m + 12], d[16 * m + 13]));
                    stg128(dst + 4 * m + 16 * 288, (pk(d[16 * m + 2], d[16 * m + 3]) & ~1u) | tag, pk(d[16 * m + 6], d[16 * m + 7]), pk(d[16 * m + 10], d[16 * m + 11]), pk(d[16 * m + 14], d[16 * m + 15]));
                }
                TRG(u, 3);
            }
        } else if (warp == 4) {
            mbar_expect(bar + 64 + lane * 8, A_KB, lane < 9);
            int it = 0;
#pragma unroll 1
            for (int u = 0; u < NTA; u++) {
                if (u == 0) { cnt_wait(g_cnt + C_W * 8, 96 * (ep + 1)); TRG(78, 0); }
                if (u < NSEG) cnt_wait(g_cnt + (C_N0 + u) * 8, 32 * (ep + 1));
                if (u > LAGA + LAG) cnt_wait(g_cnt + (C_RB + NSEG + u - LAGA - LAG - 1) * 8, 32 * (ep + 1));
                if (u >= LAGA) cnt_wait(g_cnt + (C_RB + u - LAGA) * 8, 32 * (ep + 1));
                TRG(u, 0);
                asm volatile("fence.proxy.async.global;" ::: "memory");
                const bool on = lane == 0 ? u < NSEG : lane == 1 && u >= LAGA;
#pragma unroll 1
                for (int kb = 0; kb < 9; kb++, it++) {
                    if (it >= 4) mbar_wait(bar + 32 + (it & 3) * 8, ((it >> 2) - 1) & 1);
                    mbar_expect(bar + (it & 3) * 8, u < NSEG && u >= LAGA ? 8192 : 4096, lane == 0);
                    asm volatile("{.reg .pred p; setp.ne.u32 p, %3, 0; @p cp.async.bulk.shared::cluster.global.mbarrier::complete_tx::bytes [%0], [%1], 4096, [%2];}"
                        :: "r"(sb + O_RING + (it & 3) * 8192 + (lane & 1) * 4096), "l"(g_xa + u * 4608 + (lane & 1) * 2304 + kb * 256), "r"(bar + (it & 3) * 8), "r"((uint32_t)on) : "memory");
                    if (u == 0) asm volatile("{.reg .pred p; setp.ne.u32 p, %4, 0; @p cp.async.bulk.shared::cluster.global.mbarrier::complete_tx::bytes [%0], [%1], %3, [%2];}"
                        :: "r"(sb + lane * A_KB), "l"(g_wa + ((b - 24) * 9 + lane) * (A_KB / 16)), "r"(bar + 64 + lane * 8), "n"(A_KB),
                           "r"((uint32_t)(lane < 9 && kb == (lane < 4 ? lane : lane < 6 ? 3 : lane - 2))) : "memory");
                }
            }
        } else if ((warp - 5) * 11 + b - 24 < 32) rows_a(xin, 1, (warp - 5) * 11 + b - 24, lane, ep, warp);
    }
}

extern "C" void kernel_launch(void* const* d_in, const int* in_sizes, int n_in, void* d_out, int out_size) {
    const __nv_bfloat16* x = (const __nv_bfloat16*)d_in[0];
    const __nv_bfloat16* wqkv = (const __nv_bfloat16*)d_in[1];
    const __nv_bfloat16* wo = (const __nv_bfloat16*)d_in[2];
    const __nv_bfloat16* mem0 = (const __nv_bfloat16*)d_in[4];
    const __nv_bfloat16* Wq = (const __nv_bfloat16*)d_in[5];
    const __nv_bfloat16* Wk = (const __nv_bfloat16*)d_in[6];
    const __nv_bfloat16* Wv = (const __nv_bfloat16*)d_in[7];
    const __nv_bfloat16* Wo = (const __nv_bfloat16*)d_in[8];
    cudaFuncSetAttribute(k_main, cudaFuncAttributeMaxDynamicSharedMemorySize, km::SMEM);
    cudaFuncSetAttribute(k_aux, cudaFuncAttributeMaxDynamicSharedMemorySize, ka::SMEM);
    cudaStream_t s = cudaStreamPerThread;
    k_main<<<96, 384, km::SMEM, s>>>(x, wqkv, wo, mem0, Wq, Wk, Wv, Wo);
    cudaLaunchConfig_t cfg = {};
    cudaLaunchAttribute at[1];
    at[0].id = cudaLaunchAttributeProgrammaticStreamSerialization;
    at[0].val.programmaticStreamSerializationAllowed = 1;
    cfg.stream = s; cfg.attrs = at; cfg.numAttrs = 1;
    cfg.gridDim = dim3(36); cfg.blockDim = dim3(384); cfg.dynamicSmemBytes = ka::SMEM;
    cudaLaunchKernelEx(&cfg, k_aux, x, wqkv, wo, Wo, (__nv_bfloat16*)d_out);
}
```

```cpp
#include <cuda_runtime.h>
#include <cuda_bf16.h>
#include <stdint.h>

#define LAG 7
constexpr int NSEG = 64;
constexpr int NT = NSEG + LAG;
#define AHEAD 1
constexpr int LAGA = LAG + AHEAD;
constexpr int NTA = NSEG + LAGA;
#define RING_ 8
constexpr int RING = RING_;
constexpr int DM = 576;

__device__ __align__(1024) uint4 g_xt[NT * 2 * 9 * 256];
__device__ __align__(1024) uint4 g_o[RING * 4 * 256 * 32];
__device__ __align__(1024) uint4 g_ex[2 * 131072];
__device__ unsigned g_side[96];
__device__ __align__(1024) uint4 g_pb[RING * 64 * 8 * 72];
__device__ __align__(1024) uint4 g_pa[RING * 64 * 4 * 72];
__device__ __align__(1024) uint4 g_oa[RING * 4 * 44 * 32];
__device__ __align__(1024) uint4 g_xa[NTA * 2 * 9 * 256];
__device__ __align__(1024) uint4 g_wa[11 * 9 * 21 * 64];
__device__ __align__(1024) uint4 g_x[3 * 2048 * 72];

constexpr int C_X = 0;
constexpr int C_O = C_X + NT;
constexpr int C_WB = C_O + NT * 8;
constexpr int C_RB = C_WB + NT * 4;
constexpr int C_A = C_RB + 2 * NSEG;
constexpr int C_WA = C_A + NTA * 4;
constexpr int C_N0 = C_WA + NTA * 4;
constexpr int C_W = C_N0 + NSEG;
constexpr int C_DONE = C_W + 1;
constexpr int C_TOTAL = C_DONE + 1;
__device__ __align__(1024) unsigned g_cnt[C_TOTAL * 8];
__device__ unsigned g_epoch;

#define TR(i)
#define TR1(i)
#define TR_ON(t)
#define TR_INIT(base)
#define TR_DUMP(slot)
#define TRG(t, i)
constexpr int TR_BYTES = 0;

#define DEVI __device__ __forceinline__
DEVI uint32_t smem_u32(const void* p) { return (uint32_t)__cvta_generic_to_shared(p); }
DEVI uint32_t pk(float lo, float hi) { uint32_t r; asm("cvt.rn.bf16x2.f32 %0, %1, %2;" : "=r"(r) : "f"(hi), "f"(lo)); return r; }
DEVI float bf_lo(uint32_t u) { return __uint_as_float(u << 16); }
DEVI float bf_hi(uint32_t u) { return __uint_as_float(u & 0xffff0000u); }
DEVI uint32_t add2(uint32_t a, uint32_t b) { uint32_t d; asm("add.rn.bf16x2 %0, %1, %2;" : "=r"(d) : "r"(a), "r"(b)); return d; }
DEVI uint32_t movm(uint32_t a) { uint32_t d; asm volatile("movmatrix.sync.aligned.m8n8.trans.b16 %0, %1;" : "=r"(d) : "r"(a)); return d; }
DEVI float2 shfl2(float a, float b, int o) {
    float2 r; asm volatile("shfl.sync.bfly.b32 %0, %2, %4, 31, -1; shfl.sync.bfly.b32 %1, %3, %4, 31, -1;" : "=&f"(r.x), "=f"(r.y) : "f"(a), "f"(b), "r"(o)); return r;
}
DEVI float ex2(float x) { float y; asm("ex2.approx.ftz.f32 %0, %1;" : "=f"(y) : "f"(x)); return y; }
DEVI float rcp(float x) { float y; asm("rcp.approx.ftz.f32 %0, %1;" : "=f"(y) : "f"(x)); return y; }
DEVI void mma16(float (&d)[4], uint32_t a0, uint32_t a1, uint32_t a2, uint32_t a3, uint32_t b0, uint32_t b1) {
    asm volatile("mma.sync.aligned.m16n8k16.row.col.f32.bf16.bf16.f32 {%0,%1,%2,%3}, {%4,%5,%6,%7}, {%8,%9}, {%0,%1,%2,%3};"
        : "+f"(d[0]), "+f"(d[1]), "+f"(d[2]), "+f"(d[3]) : "r"(a0), "r"(a1), "r"(a2), "r"(a3), "r"(b0), "r"(b1));
}
DEVI void mma8(float (&d)[4], uint32_t a0, uint32_t a1, uint32_t b0) {
    asm volatile("mma.sync.aligned.m16n8k8.row.col.f32.bf16.bf16.f32 {%0,%1,%2,%3}, {%4,%5}, {%6}, {%0,%1,%2,%3};"
        : "+f"(d[0]), "+f"(d[1]), "+f"(d[2]), "+f"(d[3]) : "r"(a0), "r"(a1), "r"(b0));
}
DEVI uint4 lds128(uint32_t a) { uint4 v; asm volatile("ld.shared.v4.u32 {%0,%1,%2,%3}, [%4];" : "=r"(v.x), "=r"(v.y), "=r"(v.z), "=r"(v.w) : "r"(a) : "memory"); return v; }
DEVI uint2 lds64(uint32_t a) { uint2 v; asm volatile("ld.shared.v2.u32 {%0,%1}, [%2];" : "=r"(v.x), "=r"(v.y) : "r"(a) : "memory"); return v; }
DEVI uint32_t lds32(uint32_t a) { uint32_t v; asm volatile("ld.shared.u32 %0, [%1];" : "=r"(v) : "r"(a) : "memory"); return v; }
DEVI uint32_t lds32v(uint32_t a) { uint32_t v; asm volatile("ld.volatile.shared.u32 %0, [%1];" : "=r"(v) : "r"(a) : "memory"); return v; }
DEVI uint4 lds128v(uint32_t a) { uint4 v; asm volatile("ld.volatile.shared.v4.u32 {%0,%1,%2,%3}, [%4];" : "=r"(v.x), "=r"(v.y), "=r"(v.z), "=r"(v.w) : "r"(a) : "memory"); return v; }
DEVI uint32_t lds16(uint32_t a) { uint32_t v; asm volatile("ld.shared.u16 %0, [%1];" : "=r"(v) : "r"(a) : "memory"); return v; }
DEVI uint4 ldsm4(uint32_t a) { uint4 v; asm volatile("ldmatrix.sync.aligned.m8n8.x4.shared.b16 {%0,%1,%2,%3}, [%4];" : "=r"(v.x), "=r"(v.y), "=r"(v.z), "=r"(v.w) : "r"(a) : "memory"); return v; }
DEVI uint4 ldsm4p(uint32_t a, bool pred) {
    uint4 v; asm volatile("{.reg .pred p; setp.ne.u32 p, %5, 0; @p ldmatrix.sync.aligned.m8n8.x4.shared.b16 {%0,%1,%2,%3}, [%4];}" : "=r"(v.x), "=r"(v.y), "=r"(v.z), "=r"(v.w) : "r"(a), "r"((uint32_t)pred) : "memory"); return v;
}
DEVI uint4 ldsm4t(uint32_t a) { uint4 v; asm volatile("ldmatrix.sync.aligned.m8n8.x4.trans.shared.b16 {%0,%1,%2,%3}, [%4];" : "=r"(v.x), "=r"(v.y), "=r"(v.z), "=r"(v.w) : "r"(a) : "memory"); return v; }
DEVI uint2 ldsm2(uint32_t a) { uint2 v; asm volatile("ldmatrix.sync.aligned.m8n8.x2.shared.b16 {%0,%1}, [%2];" : "=r"(v.x), "=r"(v.y) : "r"(a) : "memory"); return v; }
DEVI void stsm4t(uint32_t a, uint32_t x, uint32_t y, uint32_t z, uint32_t w) { asm volatile("stmatrix.sync.aligned.m8n8.x4.trans.shared.b16 [%0], {%1,%2,%3,%4};" :: "r"(a), "r"(x), "r"(y), "r"(z), "r"(w) : "memory"); }
DEVI void sts128(uint32_t a, uint32_t x, uint32_t y, uint32_t z, uint32_t w) { asm volatile("st.shared.v4.u32 [%0], {%1,%2,%3,%4};" :: "r"(a), "r"(x), "r"(y), "r"(z), "r"(w) : "memory"); }
DEVI void sts64(uint32_t a, uint32_t x, uint32_t y) { asm volatile("st.shared.v2.u32 [%0], {%1,%2};" :: "r"(a), "r"(x), "r"(y) : "memory"); }
DEVI void sts32(uint32_t a, uint32_t x) { asm volatile("st.shared.u32 [%0], %1;" :: "r"(a), "r"(x) : "memory"); }
DEVI void sts32p(uint32_t a, uint32_t x, bool pred) { asm volatile("{.reg .pred p; setp.ne.u32 p, %2, 0; @p st.shared.u32 [%0], %1;}" :: "r"(a), "r"(x), "r"((uint32_t)pred) : "memory"); }
DEVI void sta128(uint32_t a, uint32_t x, uint32_t y, uint32_t z, uint32_t w, uint32_t bar) {
    asm volatile("st.async.weak.shared::cluster.mbarrier::complete_tx::bytes.v4.b32 [%0], {%1,%2,%3,%4}, [%5];" :: "r"(a), "r"(x), "r"(y), "r"(z), "r"(w), "r"(bar) : "memory");
}
DEVI void sta128p(uint32_t a, uint32_t x, uint32_t y, uint32_t z, uint32_t w, uint32_t bar, bool pred) {
    asm volatile("{.reg .pred p; setp.ne.u32 p, %6, 0; @p st.async.weak.shared::cluster.mbarrier::complete_tx::bytes.v4.b32 [%0], {%1,%2,%3,%4}, [%5];}" :: "r"(a), "r"(x), "r"(y), "r"(z), "r"(w), "r"(bar), "r"((uint32_t)pred) : "memory");
}
DEVI void sta64(uint32_t a, uint32_t x, uint32_t y, uint32_t bar) {
    asm volatile("st.async.weak.shared::cluster.mbarrier::complete_tx::bytes.v2.b32 [%0], {%1,%2}, [%3];" :: "r"(a), "r"(x), "r"(y), "r"(bar) : "memory");
}
DEVI void sta32(uint32_t a, uint32_t x, uint32_t bar) {
    asm volatile("st.async.weak.shared::cluster.mbarrier::complete_tx::bytes.b32 [%0], %1, [%2];" :: "r"(a), "r"(x), "r"(bar) : "memory");
}
DEVI uint4 ldg_pkt(const void* p) {
    uint4 v;
    asm volatile("ld.relaxed.gpu.global.v4.u32 {%0,%1,%2,%3}, [%4];" : "=r"(v.x), "=r"(v.y), "=r"(v.z), "=r"(v.w) : "l"(p) : "memory");
    return v;
}
DEVI void ldg_pkt_if(uint4& v, const void* p, bool pred) {
    asm volatile("{.reg .pred p; setp.ne.u32 p, %5, 0; @p ld.relaxed.gpu.global.v4.u32 {%0,%1,%2,%3}, [%4];}"
        : "+r"(v.x), "+r"(v.y), "+r"(v.z), "+r"(v.w) : "l"(p), "r"((uint32_t)pred) : "memory");
}
DEVI void ldg_pkt_retry(uint4& v, const void* p, uint32_t tag) {
    asm volatile("{.reg .pred p; .reg .b32 t; lop3.b32 t, %0, %5, 1, 0x28; setp.ne.u32 p, t, 0; @p ld.relaxed.gpu.global.v4.u32 {%0,%1,%2,%3}, [%4];}"
        : "+r"(v.x), "+r"(v.y), "+r"(v.z), "+r"(v.w) : "l"(p), "r"(tag) : "memory");
}
DEVI void stg_pkt(void* p, uint32_t x, uint32_t y, uint32_t z, uint32_t w) {
    asm volatile("st.relaxed.gpu.global.v4.u32 [%0], {%1,%2,%3,%4};" :: "l"(p), "r"(x), "r"(y), "r"(z), "r"(w) : "memory");
}
DEVI uint32_t ldg_word(const void* p) { uint32_t v; asm volatile("ld.relaxed.gpu.global.u32 %0, [%1];" : "=r"(v) : "l"(p) : "memory"); return v; }
DEVI void stg_word(void* p, uint32_t x, bool pred) {
    asm volatile("{.reg .pred p; setp.ne.u32 p, %2, 0; @p st.relaxed.gpu.global.u32 [%0], %1;}" :: "l"(p), "r"(x), "r"((uint32_t)pred) : "memory");
}
DEVI uint2 ldg64nc(const void* p) { uint2 v; asm volatile("ld.global.nc.L1::no_allocate.v2.u32 {%0,%1}, [%2];" : "=r"(v.x), "=r"(v.y) : "l"(p)); return v; }
DEVI void prefetch_l2(const void* p, uint32_t bytes) { asm volatile("cp.async.bulk.prefetch.L2.global [%0], %1;" :: "l"(p), "r"(bytes) : "memory"); }
DEVI uint4 ldg128(const void* p) { uint4 v; asm volatile("ld.global.cg.v4.u32 {%0,%1,%2,%3}, [%4];" : "=r"(v.x), "=r"(v.y), "=r"(v.z), "=r"(v.w) : "l"(p) : "memory"); return v; }
DEVI uint2 ldg64(const void* p) { uint2 v; asm volatile("ld.global.cg.v2.u32 {%0,%1}, [%2];" : "=r"(v.x), "=r"(v.y) : "l"(p) : "memory"); return v; }
DEVI uint32_t ldg32(const void* p) { uint32_t v; asm volatile("ld.global.cg.u32 %0, [%1];" : "=r"(v) : "l"(p) : "memory"); return v; }
DEVI void stg128(void* p, uint32_t x, uint32_t y, uint32_t z, uint32_t w) { asm volatile("st.global.cg.v4.u32 [%0], {%1,%2,%3,%4};" :: "l"(p), "r"(x), "r"(y), "r"(z), "r"(w) : "memory"); }
DEVI void stg128p(void* p, uint32_t x, uint32_t y, uint32_t z, uint32_t w, bool pred) { asm volatile("{.reg .pred p; setp.ne.u32 p, %5, 0; @p st.global.cg.v4.u32 [%0], {%1,%2,%3,%4};}" :: "l"(p), "r"(x), "r"(y), "r"(z), "r"(w), "r"((uint32_t)pred) : "memory"); }
DEVI void stg64(void* p, uint32_t x, uint32_t y) { asm volatile("st.global.cg.v2.u32 [%0], {%1,%2};" :: "l"(p), "r"(x), "r"(y) : "memory"); }
DEVI void stg32(void* p, uint32_t x) { asm volatile("st.global.cg.u32 [%0], %1;" :: "l"(p), "r"(x) : "memory"); }
DEVI void cp16(uint32_t dst, const void* src) { asm volatile("cp.async.cg.shared.global [%0], [%1], 16;" :: "r"(dst), "l"(src) : "memory"); }
DEVI void cp16_if(uint32_t dst, const void* src, bool pred) { asm volatile("{.reg .pred p; setp.ne.u32 p, %2, 0; @p cp.async.cg.shared.global [%0], [%1], 16;}" :: "r"(dst), "l"(src), "r"((uint32_t)pred) : "memory"); }
DEVI void cp_commit() { asm volatile("cp.async.commit_group;" ::: "memory"); }
DEVI void cp4(uint32_t dst, const void* src) { asm volatile("cp.async.ca.shared.global [%0], [%1], 4;" :: "r"(dst), "l"(src) : "memory"); }
template <int N> DEVI void cp_wait() { asm volatile("cp.async.wait_group %0;" :: "n"(N) : "memory"); }
DEVI void cp_wait_all() { asm volatile("cp.async.wait_all;" ::: "memory"); }
DEVI void bar_sync(int id, int n) { asm volatile("bar.sync %0, %1;" :: "r"(id), "r"(n) : "memory"); }
DEVI void bar_arrive(int id, int n) { asm volatile("bar.arrive %0, %1;" :: "r"(id), "r"(n) : "memory"); }
DEVI void fence_async_smem() { asm volatile("fence.proxy.async.shared::cta;" ::: "memory"); }
DEVI void fence_async_global() { asm volatile("fence.proxy.async.global;" ::: "memory"); }
DEVI void mbar_init(uint32_t b, int n) { asm volatile("mbarrier.init.shared.b64 [%0], %1;" :: "r"(b), "r"(n) : "memory"); }
DEVI void mbar_expect(uint32_t b, uint32_t bytes, bool pred) {
    asm volatile("{.reg .pred p; setp.ne.u32 p, %2, 0; @p mbarrier.arrive.expect_tx.shared.b64 _, [%0], %1;}" :: "r"(b), "r"(bytes), "r"((uint32_t)pred) : "memory");
}
DEVI void mbar_arrive(uint32_t b, bool pred) { asm volatile("{.reg .pred p; setp.ne.u32 p, %1, 0; @p mbarrier.arrive.shared.b64 _, [%0];}" :: "r"(b), "r"((uint32_t)pred) : "memory"); }
DEVI void mbar_arrive_all3(uint32_t b, uint32_t lane) {
    asm volatile("{.reg .pred p; .reg .u32 a; setp.lt.u32 p, %1, 3; @p mapa.shared::cluster.u32 a, %0, %1; @p mbarrier.arrive.relaxed.cluster.shared::cluster.b64 _, [a];}" :: "r"(b), "r"(lane) : "memory");
}
#define FAULT "or.b32 n, n, 1; st.volatile.shared.u32 [n], n;\n"
#define LIM1 "400000"
#define LIM2 "2000000"
DEVI void fault_if(bool p, uint32_t n) { asm volatile("{.reg .pred p; setp.ne.u32 p, %0, 0; @p st.volatile.shared.u32 [%1], %1;}" :: "r"((uint32_t)p), "r"(n | 1) : "memory"); }
DEVI void mbar_wait(uint32_t b, uint32_t parity) {
    asm volatile("{.reg .pred p; .reg .u32 n;\n"
        "mbarrier.try_wait.parity.shared::cta.b64 p, [%0], %1;\n"
        "@p bra.uni D%=;\n"
        "mov.u32 n, 0;\n"
        "W%=: mbarrier.try_wait.parity.shared::cta.b64 p, [%0], %1;\n"
        "@p bra.uni D%=;\n"
        "add.u32 n, n, 1; setp.lt.u32 p, n, " LIM1 "; @p bra.uni W%=;\n"
        FAULT
        "D%=:}" :: "r"(b), "r"(parity) : "memory");
}
constexpr int POLL_LIMIT = 2000000;
DEVI void cnt_wait(const unsigned* c, unsigned target) {
    asm volatile("{.reg .pred p; .reg .u32 n, v;\n"
        "ld.acquire.gpu.global.u32 v, [%0];\n"
        "setp.ge.u32 p, v, %1; vote.sync.all.pred p, p, 0xffffffff; @p bra.uni D%=;\n"
        "mov.u32 n, 0;\n"
        "W%=: ld.acquire.gpu.global.u32 v, [%0];\n"
        "setp.ge.u32 p, v, %1; vote.sync.all.pred p, p, 0xffffffff; @p bra.uni D%=;\n"
        "add.u32 n, n, 1; setp.lt.u32 p, n, " LIM2 "; @p bra.uni W%=;\n"
        FAULT
        "D%=:}" :: "l"(c), "r"(target) : "memory");
}
DEVI void hint_wait(const unsigned* c, unsigned target) {
    asm volatile("{.reg .pred p; .reg .u32 n, v;\n"
        "ld.relaxed.gpu.global.u32 v, [%0];\n"
        "setp.ge.u32 p, v, %1; vote.sync.all.pred p, p, 0xffffffff; @p bra.uni D%=;\n"
        "mov.u32 n, 0;\n"
        "W%=: ld.relaxed.gpu.global.u32 v, [%0];\n"
        "setp.ge.u32 p, v, %1; vote.sync.all.pred p, p, 0xffffffff; @p bra.uni D%=;\n"
        "add.u32 n, n, 1; setp.lt.u32 p, n, " LIM2 "; @p bra.uni W%=;\n"
        FAULT
        "D%=:}" :: "l"(c), "r"(target) : "memory");
}
DEVI void cnt_poll(const unsigned* c, unsigned target, uint32_t b, uint32_t parity, uint32_t flag, uint32_t val) {
    asm volatile("{.reg .pred p, q; .reg .u32 n, v;\n"
        "mov.u32 n, 0;\n"
        "W%=: ld.acquire.gpu.global.u32 v, [%0];\n"
        "setp.ge.u32 q, v, %1; @q st.release.cta.shared.u32 [%4], %5;\n"
        "mbarrier.test_wait.parity.shared::cta.b64 p, [%2], %3;\n"
        "add.u32 n, n, 1; setp.gt.or.u32 p, n, 1000, p; or.pred p, p, q; vote.sync.any.pred p, p, 0xffffffff; @!p bra.uni W%=;\n"
        "}" :: "l"(c), "r"(target), "r"(b), "r"(parity), "r"(flag), "r"(val) : "memory");
}
DEVI uint32_t lds_acq(uint32_t a) { uint32_t v; asm volatile("ld.acquire.cta.shared.u32 %0, [%1];" : "=r"(v) : "r"(a) : "memory"); return v; }
template <int N = 1> DEVI void cnt_add(unsigned* c, int lane) {
    asm volatile("{.reg .pred p; setp.eq.u32 p, %1, 0; fence.acq_rel.gpu; bar.warp.sync 0xffffffff; @p red.relaxed.gpu.global.add.u32 [%0], %2;}" :: "l"(c + lane), "r"(lane), "n"(N) : "memory");
}
DEVI void cnt_hint(unsigned* c, int lane) {
    asm volatile("{.reg .pred p; setp.eq.u32 p, %1, 0; @p red.relaxed.gpu.global.add.u32 [%0], 1;}" :: "l"(c + lane), "r"(lane) : "memory");
}
template <int N = NT> DEVI uint32_t ring_tag(unsigned u, uint32_t ep) { return (u / RING + ep * ((N - 1 - u % RING) / RING + 1) + 1) & 1; }
static_assert(RING >= LAGA && RING > LAG, "ring too short");
DEVI uint32_t lop_bad(uint32_t acc, uint32_t x, uint32_t y, uint32_t tag) {
    uint32_t d; asm("{.reg .b32 t; lop3.b32 t, %2, %3, %4, 0x7e; or.b32 %0, t, %1;}" : "=r"(d) : "r"(acc), "r"(x), "r"(y), "r"(tag)); return d;
}
template <int N> DEVI void validate(uint4* v, const void* p, int step, uint32_t tag) {
    for (int n = 0;; n++) {
        uint32_t bad = 0;
#pragma unroll
        for (int i = 0; i < N; i += 2) bad = lop_bad(bad, v[i].x, v[i + 1 < N ? i + 1 : i].x, tag);
        if (!__any_sync(~0u, bad & 1)) break;
#pragma unroll
        for (int i = 0; i < N; i++) ldg_pkt_retry(v[i], static_cast<const char*>(p) + i * step, tag);
        fault_if(n > POLL_LIMIT, n);
    }
}
DEVI uint32_t page_par(uint32_t off) { return __popc((off >> 12) & 0xb2) & 1; }
DEVI uint32_t inbox_off(int b) { return (b >> 1) * 32768 + (b & 1) * 8192; }
DEVI uint32_t mem_off(int w, int i) { return 0x180000 + w * 1024 + (i & 1) * 512 + (i & 3) * 16384 + (i < 4 ? 0 : i < 8 ? 0x30000 : 0x40000); }
DEVI void sched_fence(uint32_t zero, uint32_t id) { asm volatile("{.reg .pred p; setp.ne.u32 p, %0, %1; @p bra.uni D%=; exit; D%=:}" :: "r"(zero), "r"(id) : "memory"); }
DEVI uint32_t clk() { uint32_t c; asm volatile("mov.u32 %0, %%clock;" : "=r"(c) :: "memory"); return c; }
DEVI void delay(uint32_t n) {
    if (n) asm volatile("{.reg .pred p; .reg .u32 c, e; mov.u32 e, %%clock;\n W%=: mov.u32 c, %%clock; sub.u32 c, c, e; setp.lt.u32 p, c, %0; @p bra.uni W%=;}" :: "r"(n) : "memory");
}
DEVI void delay_until(uint32_t t0, uint32_t n) {
    asm volatile("{.reg .pred p; .reg .u32 c;\n W%=: mov.u32 c, %%clock; sub.u32 c, c, %1; setp.lt.u32 p, c, %0; @p bra.uni W%=;}" :: "r"(n), "r"(t0) : "memory");
}
DEVI void wg_fence() { asm volatile("wgmma.fence.sync.aligned;" ::: "memory"); }
DEVI void wg_commit() { asm volatile("wgmma.commit_group.sync.aligned;" ::: "memory"); }
template <int N> DEVI void wg_wait() { asm volatile("wgmma.wait_group.sync.aligned %0;" :: "n"(N) : "memory"); }
DEVI uint64_t mkdesc(uint32_t lo, uint32_t hi) { uint64_t d; asm("mov.b64 %0, {%1,%2};" : "=l"(d) : "r"(lo), "r"(hi)); return d; }
DEVI void cluster_arrive() { asm volatile("barrier.cluster.arrive.relaxed.aligned;" ::: "memory"); }
DEVI void cluster_wait() { asm volatile("barrier.cluster.wait.aligned;" ::: "memory"); }
DEVI void cluster_sync() { asm volatile("barrier.cluster.arrive.aligned;\n barrier.cluster.wait.aligned;" ::: "memory"); }
DEVI void wgmma_ss16t(float (&d)[8], uint64_t da, uint64_t db, int acc) {
    asm volatile("{.reg .pred p; setp.ne.b32 p, %10, 0;\n"
        "wgmma.mma_async.sync.aligned.m64n16k16.f32.bf16.bf16 {%0,%1,%2,%3,%4,%5,%6,%7}, %8, %9, p, 1, 1, 0, 1;}"
        : "+f"(d[0]), "+f"(d[1]), "+f"(d[2]), "+f"(d[3]), "+f"(d[4]), "+f"(d[5]), "+f"(d[6]), "+f"(d[7])
        : "l"(da), "l"(db), "r"(acc));
}
DEVI void wgmma_ss16a(float (&d)[8], uint64_t da, uint64_t db, int acc) {
    asm volatile("{.reg .pred p; setp.ne.b32 p, %10, 0;\n"
        "wgmma.mma_async.sync.aligned.m64n16k16.f32.bf16.bf16 {%0,%1,%2,%3,%4,%5,%6,%7}, %8, %9, p, 1, 1, 1, 0;}"
        : "+f"(d[0]), "+f"(d[1]), "+f"(d[2]), "+f"(d[3]), "+f"(d[4]), "+f"(d[5]), "+f"(d[6]), "+f"(d[7])
        : "l"(da), "l"(db), "r"(acc));
}
DEVI void wgmma_ss64(float (&d)[32], uint64_t da, uint64_t db, int acc) {
    asm volatile("{.reg .pred p; setp.ne.b32 p, %34, 0;\n"
        "wgmma.mma_async.sync.aligned.m64n64k16.f32.bf16.bf16 {%0,%1,%2,%3,%4,%5,%6,%7,%8,%9,%10,%11,%12,%13,%14,%15,%16,%17,%18,%19,%20,%21,%22,%23,%24,%25,%26,%27,%28,%29,%30,%31}, %32, %33, p, 1, 1, 0, 0;}"
        : "+f"(d[0]), "+f"(d[1]), "+f"(d[2]), "+f"(d[3]), "+f"(d[4]), "+f"(d[5]), "+f"(d[6]), "+f"(d[7]), "+f"(d[8]), "+f"(d[9]), "+f"(d[10]), "+f"(d[11]), "+f"(d[12]), "+f"(d[13]), "+f"(d[14]), "+f"(d[15]), "+f"(d[16]), "+f"(d[17]), "+f"(d[18]), "+f"(d[19]), "+f"(d[20]), "+f"(d[21]), "+f"(d[22]), "+f"(d[23]), "+f"(d[24]), "+f"(d[25]), "+f"(d[26]), "+f"(d[27]), "+f"(d[28]), "+f"(d[29]), "+f"(d[30]), "+f"(d[31])
        : "l"(da), "l"(db), "r"(acc));
}
DEVI void wgmma_rs16t(float (&d)[8], uint32_t a0, uint32_t a1, uint32_t a2, uint32_t a3, uint64_t db, int acc) {
    asm volatile("{.reg .pred p; setp.ne.b32 p, %13, 0;\n"
        "wgmma.mma_async.sync.aligned.m64n16k16.f32.bf16.bf16 {%0,%1,%2,%3,%4,%5,%6,%7}, {%8,%9,%10,%11}, %12, p, 1, 1, 1;}"
        : "+f"(d[0]), "+f"(d[1]), "+f"(d[2]), "+f"(d[3]), "+f"(d[4]), "+f"(d[5]), "+f"(d[6]), "+f"(d[7])
        : "r"(a0), "r"(a1), "r"(a2), "r"(a3), "l"(db), "r"(acc));
}
DEVI void wgmma_rs64(float (&d)[32], uint32_t a0, uint32_t a1, uint32_t a2, uint32_t a3, uint64_t db, int acc) {
    asm volatile("{.reg .pred p; setp.ne.b32 p, %37, 0;\n"
        "wgmma.mma_async.sync.aligned.m64n64k16.f32.bf16.bf16 {%0,%1,%2,%3,%4,%5,%6,%7,%8,%9,%10,%11,%12,%13,%14,%15,%16,%17,%18,%19,%20,%21,%22,%23,%24,%25,%26,%27,%28,%29,%30,%31}, {%32,%33,%34,%35}, %36, p, 1, 1, 0;}"
        : "+f"(d[0]), "+f"(d[1]), "+f"(d[2]), "+f"(d[3]), "+f"(d[4]), "+f"(d[5]), "+f"(d[6]), "+f"(d[7]), "+f"(d[8]), "+f"(d[9]), "+f"(d[10]), "+f"(d[11]), "+f"(d[12]), "+f"(d[13]), "+f"(d[14]), "+f"(d[15]), "+f"(d[16]), "+f"(d[17]), "+f"(d[18]), "+f"(d[19]), "+f"(d[20]), "+f"(d[21]), "+f"(d[22]), "+f"(d[23]), "+f"(d[24]), "+f"(d[25]), "+f"(d[26]), "+f"(d[27]), "+f"(d[28]), "+f"(d[29]), "+f"(d[30]), "+f"(d[31])
        : "r"(a0), "r"(a1), "r"(a2), "r"(a3), "l"(db), "r"(acc));
}
DEVI void wgmma_ss168t(float (&d)[84], uint64_t da, uint64_t db, int acc) {
    asm volatile("{.reg .pred p; setp.ne.b32 p, %86, 0;\n"
        "wgmma.mma_async.sync.aligned.m64n168k16.f32.bf16.bf16 {%0,%1,%2,%3,%4,%5,%6,%7,%8,%9,%10,%11,%12,%13,%14,%15,%16,%17,%18,%19,%20,%21,%22,%23,%24,%25,%26,%27,%28,%29,%30,%31,%32,%33,%34,%35,%36,%37,%38,%39,%40,%41,%42,%43,%44,%45,%46,%47,%48,%49,%50,%51,%52,%53,%54,%55,%56,%57,%58,%59,%60,%61,%62,%63,%64,%65,%66,%67,%68,%69,%70,%71,%72,%73,%74,%75,%76,%77,%78,%79,%80,%81,%82,%83}, %84, %85, p, 1, 1, 0, 1;}"
        : "+f"(d[0]), "+f"(d[1]), "+f"(d[2]), "+f"(d[3]), "+f"(d[4]), "+f"(d[5]), "+f"(d[6]), "+f"(d[7]), "+f"(d[8]), "+f"(d[9]), "+f"(d[10]), "+f"(d[11]), "+f"(d[12]), "+f"(d[13]), "+f"(d[14]), "+f"(d[15]), "+f"(d[16]), "+f"(d[17]), "+f"(d[18]), "+f"(d[19]), "+f"(d[20]), "+f"(d[21]), "+f"(d[22]), "+f"(d[23]), "+f"(d[24]), "+f"(d[25]), "+f"(d[26]), "+f"(d[27]), "+f"(d[28]), "+f"(d[29]), "+f"(d[30]), "+f"(d[31]), "+f"(d[32]), "+f"(d[33]), "+f"(d[34]), "+f"(d[35]), "+f"(d[36]), "+f"(d[37]), "+f"(d[38]), "+f"(d[39]), "+f"(d[40]), "+f"(d[41]), "+f"(d[42]), "+f"(d[43]), "+f"(d[44]), "+f"(d[45]), "+f"(d[46]), "+f"(d[47]), "+f"(d[48]), "+f"(d[49]), "+f"(d[50]), "+f"(d[51]), "+f"(d[52]), "+f"(d[53]), "+f"(d[54]), "+f"(d[55]), "+f"(d[56]), "+f"(d[57]), "+f"(d[58]), "+f"(d[59]), "+f"(d[60]), "+f"(d[61]), "+f"(d[62]), "+f"(d[63]), "+f"(d[64]), "+f"(d[65]), "+f"(d[66]), "+f"(d[67]), "+f"(d[68]), "+f"(d[69]), "+f"(d[70]), "+f"(d[71]), "+f"(d[72]), "+f"(d[73]), "+f"(d[74]), "+f"(d[75]), "+f"(d[76]), "+f"(d[77]), "+f"(d[78]), "+f"(d[79]), "+f"(d[80]), "+f"(d[81]), "+f"(d[82]), "+f"(d[83])
        : "l"(da), "l"(db), "r"(acc));
}
DEVI void wgmma_rs96t(float (&d)[48], uint32_t a0, uint32_t a1, uint32_t a2, uint32_t a3, uint64_t db, int acc) {
    asm volatile("{.reg .pred p; setp.ne.b32 p, %53, 0;\n"
        "wgmma.mma_async.sync.aligned.m64n96k16.f32.bf16.bf16 {%0,%1,%2,%3,%4,%5,%6,%7,%8,%9,%10,%11,%12,%13,%14,%15,%16,%17,%18,%19,%20,%21,%22,%23,%24,%25,%26,%27,%28,%29,%30,%31,%32,%33,%34,%35,%36,%37,%38,%39,%40,%41,%42,%43,%44,%45,%46,%47}, {%48,%49,%50,%51}, %52, p, 1, 1, 1;}"
        : "+f"(d[0]), "+f"(d[1]), "+f"(d[2]), "+f"(d[3]), "+f"(d[4]), "+f"(d[5]), "+f"(d[6]), "+f"(d[7]), "+f"(d[8]), "+f"(d[9]), "+f"(d[10]), "+f"(d[11]), "+f"(d[12]), "+f"(d[13]), "+f"(d[14]), "+f"(d[15]), "+f"(d[16]), "+f"(d[17]), "+f"(d[18]), "+f"(d[19]), "+f"(d[20]), "+f"(d[21]), "+f"(d[22]), "+f"(d[23]), "+f"(d[24]), "+f"(d[25]), "+f"(d[26]), "+f"(d[27]), "+f"(d[28]), "+f"(d[29]), "+f"(d[30]), "+f"(d[31]), "+f"(d[32]), "+f"(d[33]), "+f"(d[34]), "+f"(d[35]), "+f"(d[36]), "+f"(d[37]), "+f"(d[38]), "+f"(d[39]), "+f"(d[40]), "+f"(d[41]), "+f"(d[42]), "+f"(d[43]), "+f"(d[44]), "+f"(d[45]), "+f"(d[46]), "+f"(d[47])
        : "r"(a0), "r"(a1), "r"(a2), "r"(a3), "l"(db), "r"(acc));
}
DEVI void wgmma_rs192t(float (&d)[96], uint32_t a0, uint32_t a1, uint32_t a2, uint32_t a3, uint64_t db, int acc) {
    asm volatile("{.reg .pred p; setp.ne.b32 p, %101, 0;\n"
        "wgmma.mma_async.sync.aligned.m64n192k16.f32.bf16.bf16 {%0,%1,%2,%3,%4,%5,%6,%7,%8,%9,%10,%11,%12,%13,%14,%15,%16,%17,%18,%19,%20,%21,%22,%23,%24,%25,%26,%27,%28,%29,%30,%31,%32,%33,%34,%35,%36,%37,%38,%39,%40,%41,%42,%43,%44,%45,%46,%47,%48,%49,%50,%51,%52,%53,%54,%55,%56,%57,%58,%59,%60,%61,%62,%63,%64,%65,%66,%67,%68,%69,%70,%71,%72,%73,%74,%75,%76,%77,%78,%79,%80,%81,%82,%83,%84,%85,%86,%87,%88,%89,%90,%91,%92,%93,%94,%95}, {%96,%97,%98,%99}, %100, p, 1, 1, 1;}"
        : "+f"(d[0]), "+f"(d[1]), "+f"(d[2]), "+f"(d[3]), "+f"(d[4]), "+f"(d[5]), "+f"(d[6]), "+f"(d[7]), "+f"(d[8]), "+f"(d[9]), "+f"(d[10]), "+f"(d[11]), "+f"(d[12]), "+f"(d[13]), "+f"(d[14]), "+f"(d[15]), "+f"(d[16]), "+f"(d[17]), "+f"(d[18]), "+f"(d[19]), "+f"(d[20]), "+f"(d[21]), "+f"(d[22]), "+f"(d[23]), "+f"(d[24]), "+f"(d[25]), "+f"(d[26]), "+f"(d[27]), "+f"(d[28]), "+f"(d[29]), "+f"(d[30]), "+f"(d[31]), "+f"(d[32]), "+f"(d[33]), "+f"(d[34]), "+f"(d[35]), "+f"(d[36]), "+f"(d[37]), "+f"(d[38]), "+f"(d[39]), "+f"(d[40]), "+f"(d[41]), "+f"(d[42]), "+f"(d[43]), "+f"(d[44]), "+f"(d[45]), "+f"(d[46]), "+f"(d[47]), "+f"(d[48]), "+f"(d[49]), "+f"(d[50]), "+f"(d[51]), "+f"(d[52]), "+f"(d[53]), "+f"(d[54]), "+f"(d[55]), "+f"(d[56]), "+f"(d[57]), "+f"(d[58]), "+f"(d[59]), "+f"(d[60]), "+f"(d[61]), "+f"(d[62]), "+f"(d[63]), "+f"(d[64]), "+f"(d[65]), "+f"(d[66]), "+f"(d[67]), "+f"(d[68]), "+f"(d[69]), "+f"(d[70]), "+f"(d[71]), "+f"(d[72]), "+f"(d[73]), "+f"(d[74]), "+f"(d[75]), "+f"(d[76]), "+f"(d[77]), "+f"(d[78]), "+f"(d[79]), "+f"(d[80]), "+f"(d[81]), "+f"(d[82]), "+f"(d[83]), "+f"(d[84]), "+f"(d[85]), "+f"(d[86]), "+f"(d[87]), "+f"(d[88]), "+f"(d[89]), "+f"(d[90]), "+f"(d[91]), "+f"(d[92]), "+f"(d[93]), "+f"(d[94]), "+f"(d[95])
        : "r"(a0), "r"(a1), "r"(a2), "r"(a3), "l"(db), "r"(acc));
}

#define TRD(t, i)
namespace km {
#define NSS 6
#define RG "184"
#define RW "136"
#define NFL 2
#define NR1 3
#define NR2 3
#define EK 7
#define FK 5
#define LDP 3
#define SND 1
#define NGAP 0
constexpr int O_H = 0;
constexpr int O_MB = 73728;
constexpr int O_VX = 96768;
constexpr int O_KX = 113152;
constexpr int O_QX = 119296;
constexpr int O_VM = 125440;
constexpr int O_KM = 129536;
constexpr int O_QM = 131072;
constexpr int O_SM = 132608;
constexpr int O_ST = 135168;
constexpr int O_OX = 145408;
constexpr int O_WO = 149504;
constexpr int O_OS = O_WO;
constexpr int O_WS = O_WO + 49152;
constexpr int O_RL = 110592;
constexpr int O_BAR = O_WS + NSS * 4096;
constexpr int SMEM = O_BAR + 128 + 1024 + TR_BYTES;
enum { B_X = 0, B_WIN = 16, B_VX = 24, B_SM = 32, B_ST = 40, B_EP = 56 };
#define DLY1 (100 * w)
#define DLY2 480
#define EARLY 1
#define DLYO 0
#define DLY0 6000
#define PFON 0
#define DLYX 0
#define PLACE 1
#define XST 5
#define DLYW 10000
#define DLYB 0
constexpr uint32_t DESC_HI = (1024 >> 4) | (1u << 30);
constexpr float SC = 0.08838834764831845f * 1.4426950408889634f;
}

__global__ void __cluster_dims__(3, 1, 1) __launch_bounds__(384, 1)
k_main(const __nv_bfloat16* __restrict__ x0, const __nv_bfloat16* __restrict__ wqkv, const __nv_bfloat16* __restrict__ wo,
       const __nv_bfloat16* __restrict__ mem0, const __nv_bfloat16* __restrict__ Wq, const __nv_bfloat16* __restrict__ Wk,
       const __nv_bfloat16* __restrict__ Wv, const __nv_bfloat16* __restrict__ Wo) {
    using namespace km;
    extern __shared__ unsigned char smem_raw[];
    const uint32_t sb = (smem_u32(smem_raw) + 1023) & ~1023u;
    const int tid = threadIdx.x, lane = tid & 31, warp = __shfl_sync(~0u, tid >> 5, 0);
    uint32_t l16 = __shfl_sync(~0u, lane * 16, lane);
#define OPQ() asm volatile("" : "+r"(l16))
    const int b = blockIdx.x, h = b / 3, r = b % 3;
    const int nq = r == 2 ? 2 : 3;
    const uint32_t bar = sb + O_BAR;
    asm volatile("griddepcontrol.launch_dependents;");
    const uint32_t t_start = clk();
    if (warp == 0 && b < 72) {
        if (lane == 0) { mbar_init(bar + 96, 1); fence_async_smem(); mbar_expect(bar + 96, 8 * 3456, true); }
        __syncwarp();
        if (lane < 8) asm volatile("cp.async.bulk.shared::cluster.global.mbarrier::complete_tx::bytes [%0], [%1], 3456, [%2];" :: "r"(sb + O_RL + lane * 3472), "l"(wqkv + (b * 8 + lane) * 1728), "r"(bar + 96) : "memory");
    }
    if (tid == 352) {
        prefetch_l2(x0 + b * (2 * DM), 2 * 1152); prefetch_l2(wo + b * (6 * DM), 6 * 1152);
    }
    if (tid == 320) sts32(bar + 64, ldg32(&g_epoch));
#define EP lds32(bar + 64)
    TR_INIT(bar + 128);
    TRG(79, 0);
    uint32_t roff0, roff1;
    {
        uint32_t y0, y1;
        asm("mapa.shared::cluster.u32 %0, %1, %2;" : "=r"(y0) : "r"(sb), "r"((r + 1) % 3));
        asm("mapa.shared::cluster.u32 %0, %1, %2;" : "=r"(y1) : "r"(sb), "r"((r + 2) % 3));
        roff0 = y0 - sb; roff1 = y1 - sb;
    }
#define IDENT (((l16 >> 7) == ((l16 >> 4) & 3) ? 0x3f80u : 0u) << ((l16 >> 2) & 16))
#define LSWAP ((l16 & 0x70) | ((l16 & 0x80) << 1) | ((l16 & 0x100) >> 1))
    const uint32_t nv_remote = 8 - (8 - 2 * nq);

    if (warp < 8) {
        asm volatile("setmaxnreg.inc.sync.aligned.u32 " RG ";");
        constexpr int SSP = 36 / NSS;
#define IS_SS(kk) ((kk) % SSP == 3)
#define AI(kk) (4 * ((kk) - ((kk) + SSP - 4) / SSP))
        uint32_t a[144 - 4 * NSS];
        {
            const int ci = tid & 15, slot = ci >> 1, d0 = tid >> 4;
            const __nv_bfloat16* src = slot < nq ? Wq + (3 * r + slot) * 16 : slot < 2 * nq ? Wk + (3 * r + slot - nq) * 16 : Wv + (2 * r + slot - 2 * nq) * 16;
            src += h * 128 + (ci & 1) * 8 + d0 * 4096;
            auto issue = [&](int q) {
#pragma unroll
                for (int i = 0; i < 3; i++) if (q < 12) cp16(sb + (q * 3 + i) * 4096 + d0 * 256 + ((ci ^ (d0 & 7)) << 4), src + (size_t)(q * 3 + i) * 65536);
                asm volatile("cp.async.commit_group;" ::: "memory");
            };
            if (b < 72) {
                bar_sync(10, 256);
                mbar_wait(bar + 96, 0);
                TR1(4);
#pragma unroll 2
                for (int ag = tid >> 3; ag < 231; ag += 32) {
                    const int a = ag / 21, gr = ag % 21, tl = gr >= 18;
                    const int head = 3 * a + (tl ? 0 : (gr % 6) >> 1), nw = tl ? min(3, 32 - head) : head < 32 ? 4 : 0;
                    const uint32_t p = sb + O_RL + (tid & 7) * 3472 + (tl ? gr - 18 : gr / 6) * 1152 + head * 36 + (tl ? 32 : (gr & 1) * 16), step = tl ? 36 : 4;
                    uint32_t v[4];
#pragma unroll
                    for (int i = 0; i < 4; i++) { v[i] = lds32(p + i * step); if (i >= nw) v[i] = 0; }
                    stg128(g_wa + ((a * 9 + (b >> 3)) * 21 + gr) * 64 + (b & 7) * 8 + (tid & 7), v[0], v[1], v[2], v[3]);
                }
            }
            {
                bar_arrive(15, 288);
                TR1(5);
                delay_until(t_start, DLY0);
#pragma unroll
                for (int q = 0; q < NFL; q++) issue(q);
            }
            TR1(1);
            const int mi = lane >> 3;
            const uint32_t ad = sb + ((mi >> 1) * 8 + (lane & 7)) * 256 + (((warp * 2 + (mi & 1)) ^ (lane & 7)) << 4);
#pragma unroll
            for (int kk = 0; kk < 36; kk++) {
                if (kk % 3 == 0) { cp_wait<NFL - 1>(); issue(kk / 3 + NFL); bar_sync(10, 256); }
                const uint4 f = ldsm4t(ad + kk * 4096);
                if (IS_SS(kk)) {
                    const uint32_t o0 = sb + O_WS + (kk / SSP) * 4096 + warp * 512 + lane * 4;
                    sts32(o0, f.x); sts32(o0 + 256, f.y); sts32(o0 + 128, f.z); sts32(o0 + 384, f.w);
                } else { a[AI(kk)] = f.x; a[AI(kk) + 1] = f.y; a[AI(kk) + 2] = f.z; a[AI(kk) + 3] = f.w; }
            }
            TR1(2);
            bar_sync(9, 384);
#pragma unroll
            for (int i = 0; i < 9; i++) sts128(sb + O_H + i * 8192 + 4096 + tid * 16, 0, 0, 0, 0);
#pragma unroll
            for (int i = 0; i < 8; i++) if (i * 256 + tid < (O_OX - O_KX) / 16) sts128(sb + O_KX + i * 4096 + tid * 16, 0, 0, 0, 0);
            fence_async_smem();
            cluster_sync();
        }
        TR1(3);
        const int kind = warp < nq ? 0 : warp < 2 * nq ? 1 : 2;
        const int sl = kind == 0 ? warp : kind == 1 ? warp - nq : 2 * r + warp - 2 * nq;
        const uint32_t adX0 = sb + (kind == 0 ? O_QX : kind == 1 ? O_KX : O_VX) + sl * 2048;
        const uint32_t adM0 = sb + (kind == 0 ? O_QM : kind == 1 ? O_KM : O_VM) + sl * 512;
        const uint32_t hlo = (((sb + O_H) >> 4) & 0x3fff) | (1u << 16);
        const uint32_t mlo = (((sb + O_MB) >> 4) & 0x3fff) | (16u << 16);
        const uint32_t wlo = (((sb + O_WS + (warp >> 2) * 2048) >> 4) & 0x3fff) | (8u << 16);
        const int L = (warp >> 1) & 1, qh = warp & 1;
        const uint32_t st = sb + O_ST + warp * 1280;

#pragma unroll 1
        for (int t = -1;; t++) {
            TR_ON(t);
            OPQ();
            const uint32_t adX = adX0 + l16, adM = adM0 + l16, l8 = l16 >> 1;
            const uint32_t lq = LSWAP;
            if (t >= 0) {
                float d0[8], d1[8];
                {
#pragma unroll
                    for (int G = 0; G < 3; G++) {
                        if (warp < 4) bar_sync(1 + G, 160); else bar_sync(12 + G, 160);
                        if (G == 0) wg_fence();
#pragma unroll
                        for (int q = 0; q < 12; q++) {
                            const int kk = 12 * G + q;
                            const uint64_t db = mkdesc(mlo + kk * 32, 8);
                            if (IS_SS(kk)) wgmma_ss16t((kk & 1) ? d1 : d0, mkdesc(wlo + (kk / SSP) * 256, 16), db, 1);
                            else wgmma_rs16t((kk & 1) ? d1 : d0, a[AI(kk)], a[AI(kk) + 1], a[AI(kk) + 2], a[AI(kk) + 3], db, kk >= 2);
                            if (kk == 0) TR(0);
                        }
                    }
                    wg_commit();
                }
#define PM(i) pk(d0[2 * (i)] + d1[2 * (i)], d0[2 * (i) + 1] + d1[2 * (i) + 1])
                if (warp >= 4) {
                    wg_wait<0>();
                    TR(1);
                    const uint32_t p0 = PM(0), p1 = PM(1), p2 = PM(2), p3 = PM(3);
                    if (kind == 2) {
                        sts128(adM, p0, p1, p2, p3);
                        bar_arrive(4, 384);
                        sta128(adM + roff0, p0, p1, p2, p3, bar + B_SM + roff0);
                        sta128(adM + roff1, p0, p1, p2, p3, bar + B_SM + roff1);
                    } else {
                        stsm4t(adM, p0, p1, p2, p3);
                        bar_arrive(4, 384);
                    }
                } else {
                    uint4 q[3], k[3][2];
                    mbar_wait(bar + B_EP, t & 1);
#pragma unroll
                    for (int m = 0; m < LDP; m++) {
                        q[m] = ldsm4(sb + O_QX + m * 2048 + warp * 512 + lq);
                        k[m][0] = ldsm4(sb + O_KX + m * 2048 + L * 1024 + l16); k[m][1] = ldsm4(sb + O_KX + m * 2048 + L * 1024 + 512 + l16);
                    }
                    wg_wait<0>();
                    TR(1);
                    stsm4t(adM, PM(0), PM(1), PM(2), PM(3));
                    bar_arrive(4, 384);
                    sched_fence(gridDim.y, 6);
#pragma unroll
                    for (int m = LDP; m < 3; m++) {
                        q[m] = ldsm4(sb + O_QX + m * 2048 + warp * 512 + lq);
                        k[m][0] = ldsm4(sb + O_KX + m * 2048 + L * 1024 + l16); k[m][1] = ldsm4(sb + O_KX + m * 2048 + L * 1024 + 512 + l16);
                    }
                    float s[5][4];
                    {
                        float y[4] = {0, 0, 0, 0};
#pragma unroll
                        for (int n = 0; n < 5; n++) s[n][0] = s[n][1] = s[n][2] = s[n][3] = 0.f;
#pragma unroll
                        for (int m = 0; m < 3; m++) {
                            mma16(s[0], q[m].x, q[m].y, q[m].z, q[m].w, k[m][0].x, k[m][0].y); mma16(s[1], q[m].x, q[m].y, q[m].z, q[m].w, k[m][0].z, k[m][0].w);
                            mma16(s[2], q[m].x, q[m].y, q[m].z, q[m].w, k[m][1].x, k[m][1].y); mma16(s[3], q[m].x, q[m].y, q[m].z, q[m].w, k[m][1].z, k[m][1].w);
                        }
                        auto send = [&]() {
                            uint32_t w0 = pk(s[0][0], s[0][1]), w1 = pk(s[0][2], s[0][3]), w2 = pk(s[1][0], s[1][1]), w3 = pk(s[1][2], s[1][3]);
                            sta128(st + l16 + 5120 + roff0, w0, w1, w2, w3, bar + B_ST + roff0);
                            sta128(st + l16 + roff1, w0, w1, w2, w3, bar + B_ST + roff1);
                            w0 = pk(s[2][0], s[2][1]); w1 = pk(s[2][2], s[2][3]); w2 = pk(s[3][0], s[3][1]); w3 = pk(s[3][2], s[3][3]);
                            sta128p(st + l16 + 5120 + 512 + roff0, w0, w1, w2, w3, bar + B_ST + roff0, qh);
                            sta128p(st + l16 + 512 + roff1, w0, w1, w2, w3, bar + B_ST + roff1, qh);
                        };
                        sched_fence(gridDim.y, 7);
                        bar_sync(5, 256);
                        const uint4 k01 = ldsm4(sb + O_KM + L * 256 + l16 + (l16 & 256));
                        const uint2 k2 = ldsm2(sb + O_KM + 1024 + L * 256 + l16);
                        if (SND == 0) send();
                        mma16(s[4], q[0].x, q[0].y, q[0].z, q[0].w, k01.x, k01.y);
                        mma16(y, q[1].x, q[1].y, q[1].z, q[1].w, k01.z, k01.w);
                        mma16(s[4], q[2].x, q[2].y, q[2].z, q[2].w, k2.x, k2.y);
#pragma unroll
                        for (int j = 0; j < 4; j++) s[4][j] += y[j];
                        const uint32_t w0 = pk(s[4][0], s[4][1]), w1 = pk(s[4][2], s[4][3]);
                        if (NGAP > 0) bar_arrive(10, 256);
                        sta64(st + l8 + 5120 + 1024 + roff0, w0, w1, bar + B_ST + roff0);
                        sta64(st + l8 + 1024 + roff1, w0, w1, bar + B_ST + roff1);
                        if (SND == 1) send();
                        TR(2);
                        const int lim = 16 * qh + (int)(l16 >> 6) - (int)((l16 >> 3) & 6);
#pragma unroll
                        for (int n = 0; n < 4; n++)
#pragma unroll
                            for (int j = 0; j < 4; j++) if (!(n == 0 && j >= 2) && 8 * (n - (j >> 1)) + (j & 1) > lim) s[n][j] = -1e30f;
#pragma unroll
                        for (int n = 0; n < 4; n++) asm volatile("" : "+f"(s[n][0]), "+f"(s[n][1]), "+f"(s[n][2]), "+f"(s[n][3]));
                    }
                    uint4 v0[3], v1[3]; uint2 vm[3];
                    const uint32_t vad = sb + O_VX + 3 * r * 2048 + L * 1024 + l16;
#pragma unroll
                    for (int m = 0; m < 3; m++) v0[m] = lds128(vad + m * 2048);
                    const uint32_t otag = ring_tag(t, EP);
                    uint32_t ident = IDENT;
                    asm volatile("" : "+r"(ident));
                    mbar_wait(bar + B_SM, t & 1);
                    mbar_wait(bar + B_ST, t & 1);
                    TR(3);
                    float mx0, mx1;
                    {
                        const uint4 u = lds128(st + l16), v = lds128(st + 512 + l16); const uint2 w = lds64(st + 1024 + l8);
                        const uint4 x = lds128(st + 5120 + l16), y = lds128(st + 5120 + 512 + l16); const uint2 z = lds64(st + 5120 + 1024 + l8);
                        mma8(s[0], u.x, u.y, ident); mma8(s[1], u.z, u.w, ident); mma8(s[2], v.x, v.y, ident); mma8(s[3], v.z, v.w, ident); mma8(s[4], w.x, w.y, ident);
                        mma8(s[0], x.x, x.y, ident); mma8(s[1], x.z, x.w, ident); mma8(s[2], y.x, y.y, ident); mma8(s[3], y.z, y.w, ident); mma8(s[4], z.x, z.y, ident);
                        mx0 = fmaxf(fmaxf(fmaxf(s[0][0], s[0][1]), fmaxf(s[1][0], s[1][1])), fmaxf(fmaxf(s[2][0], s[2][1]), fmaxf(s[3][0], s[3][1])));
                        mx1 = fmaxf(fmaxf(fmaxf(s[0][2], s[0][3]), fmaxf(s[1][2], s[1][3])), fmaxf(fmaxf(s[2][2], s[2][3]), fmaxf(s[3][2], s[3][3])));
                        mx0 = fmaxf(mx0, fmaxf(s[4][0], s[4][1])); mx1 = fmaxf(mx1, fmaxf(s[4][2], s[4][3]));
                    }
#pragma unroll
                    for (int o = 1; o < 4; o <<= 1) { const float2 z = shfl2(mx0, mx1, o); mx0 = fmaxf(mx0, z.x); mx1 = fmaxf(mx1, z.y); }
                    mx0 *= -SC; mx1 *= -SC;
                    float l[4] = {0, 0, 0, 0};
                    uint32_t p[10];
#pragma unroll
                    for (int n = 0; n < 5; n++) {
                        const float e0 = ex2(fmaf(s[n][0], SC, mx0)), e1 = ex2(fmaf(s[n][1], SC, mx0));
                        const float e2 = ex2(fmaf(s[n][2], SC, mx1)), e3 = ex2(fmaf(s[n][3], SC, mx1));
                        p[2 * n] = pk(e0, e1); p[2 * n + 1] = pk(e2, e3);
                        mma8(l, p[2 * n], p[2 * n + 1], 0x3f803f80);
                    }
#pragma unroll
                    for (int m = 0; m < 3; m++) vm[m] = lds64(sb + O_VM + (3 * r + m) * 512 + l16 + L * 8);
                    sched_fence(gridDim.y, 5);
                    const float l0 = rcp(l[0]), l1 = rcp(l[2]);
                    float o[6][4];
#pragma unroll
                    for (int m = 0; m < 6; m++) o[m][0] = o[m][1] = o[m][2] = o[m][3] = 0.f;
#pragma unroll
                    for (int m = 0; m < 3; m++) { mma8(o[2 * m], p[0], p[1], v0[m].x); mma8(o[2 * m + 1], p[0], p[1], v0[m].y); }
#pragma unroll
                    for (int m = 0; m < 3; m++) { mma8(o[2 * m], p[2], p[3], v0[m].z); mma8(o[2 * m + 1], p[2], p[3], v0[m].w); v1[m] = lds128(vad + m * 2048 + 512); }
#pragma unroll
                    for (int m = 0; m < 3; m++) { mma8(o[2 * m], p[8], p[9], vm[m].x); mma8(o[2 * m + 1], p[8], p[9], vm[m].y); }
#pragma unroll
                    for (int m = 0; m < 3; m++) { mma8(o[2 * m], p[4], p[5], v1[m].x); mma8(o[2 * m + 1], p[4], p[5], v1[m].y); }
#pragma unroll
                    for (int m = 0; m < 3; m++) { mma8(o[2 * m], p[6], p[7], v1[m].z); mma8(o[2 * m + 1], p[6], p[7], v1[m].w); }
                    sched_fence(gridDim.y, 8);
                    if (t + 1 < NT) bar_arrive(11, 384);
#pragma unroll
                    for (int m = 0; m < 3; m++)
                        sts128(sb + O_OS + warp * 512 + m * 2048 + l16, (pk(o[2 * m][0] * l0, o[2 * m][1] * l0) & ~1u) | otag, pk(o[2 * m][2] * l1, o[2 * m][3] * l1),
                               pk(o[2 * m + 1][0] * l0, o[2 * m + 1][1] * l0), pk(o[2 * m + 1][2] * l1, o[2 * m + 1][3] * l1));
                    TR(4);
                }
            }
            if (t + 1 >= NT) break;
            {
                float d[32];
                if (warp < 4) { if (t < 0) mbar_wait(bar + B_X, 0); bar_sync(7, 256); }
                else {
                    if (warp == 7) {
                        const int u = t + 1;
                        if (t >= 0) { mbar_wait(bar + B_EP, t & 1); mbar_wait(bar + B_VX, t & 1); }
                        if (__shfl_sync(~0u, lds_acq(bar + 8), 0) != u) cnt_wait(g_cnt + (C_X + u) * 8, 64 * (EP + 1));
                        else delay(DLYX);
                        fence_async_global();
                        TRG(u, 0);
                        const bool a0 = u < NSEG, a1 = u >= LAG;
                        mbar_expect(bar + B_X, ((int)a0 + (int)a1) * 36864, l16 == 0);
                        const uint32_t off = r * 24576 + (l16 << 9) + (a0 ? 0 : 4096);
                        asm volatile("{.reg .pred p; setp.lt.u32 p, %5, %6;\n"
                            "@p cp.async.bulk.shared::cluster.global.mbarrier::complete_tx::bytes.multicast::cluster [%0], [%1], %4, [%2], %3;}"
                            :: "r"(sb + O_H + off), "l"(reinterpret_cast<const char*>(g_xt + u * 4608) + off), "r"(bar + B_X), "h"((uint16_t)7),
                               "r"(a0 && a1 ? 24576 : 4096), "r"(l16), "r"(a0 && a1 ? 16 : 48) : "memory");
                        TR(2);
                    }
                    mbar_wait(bar + B_X, (t + 1) & 1);
                    TR(3);
                    if (t >= 0) bar_sync(NGAP > 0 ? 10 : 11, NGAP > 0 ? 256 : 384);
                }
                wg_fence();
                TR(6);
#pragma unroll
                for (int kk = 0; kk < 36; kk++) {
                    if (NGAP > 0 && kk == NGAP) asm volatile("{.reg .pred p; setp.ne.u32 p, %0, 0; @p bar.sync 11, 384;}" :: "r"((uint32_t)(warp >= 4 && t >= 0)) : "memory");
                    const uint64_t db = mkdesc(hlo + ((kk >> 2) * 8192 + (kk & 3) * 32) / 16, DESC_HI);
                    if (IS_SS(kk)) wgmma_ss64(d, mkdesc(wlo + (kk / SSP) * 256, 16), db, 1);
                    else wgmma_rs64(d, a[AI(kk)], a[AI(kk) + 1], a[AI(kk) + 2], a[AI(kk) + 3], db, kk > 0);
                }
                wg_commit();
                TR(5);
                mbar_wait(bar + B_WIN, (t + 1) & 1);
                wg_wait<0>();
                TR(7);
                uint32_t p[16];
#pragma unroll
                for (int u = 0; u < 16; u++) p[u] = pk(d[2 * u], d[2 * u + 1]);
                if (kind == 2) {
#pragma unroll
                    for (int u = 0; u < 4; u++) sts128(adX + u * 512, p[4 * u], p[4 * u + 1], p[4 * u + 2], p[4 * u + 3]);
                } else {
#pragma unroll
                    for (int u = 0; u < 4; u++) stsm4t(adX + u * 512, p[4 * u], p[4 * u + 1], p[4 * u + 2], p[4 * u + 3]);
                }
                __syncwarp();
                asm volatile("{.reg .pred p; setp.eq.u32 p, %1, 0; @p mbarrier.arrive.shared.b64 _, [%0];}" :: "r"(bar + B_EP), "r"(l16) : "memory");
                TR(8);
            }
        }
        if (warp < 4) bar_arrive(7, 160); else if (NGAP > 0) bar_sync(10, 256);
        cluster_sync();
    } else {
        asm volatile("setmaxnreg.dec.sync.aligned.u32 " RW ";");
        const int w = warp - 8, t2 = tid - 256;
        if (t2 == 0) {
            mbar_init(bar + B_X, 1); sts32(bar + 8, ~0u); mbar_init(bar + B_WIN, 3);
            mbar_init(bar + B_VX, 1); mbar_init(bar + B_SM, 1); mbar_init(bar + B_ST, 1); mbar_init(bar + B_EP, 8);
            asm volatile("fence.mbarrier_init.release.cluster;" ::: "memory");
        }
        char* const ex = reinterpret_cast<char*>((reinterpret_cast<uintptr_t>(g_ex) + 0x1fffff) & ~(uintptr_t)0x1fffff);
        char* rbase = ex; uint32_t side = 0;
        {
            uint32_t m0[5][4];
#pragma unroll
            for (int i = 0; i < 5; i++) {
                const unsigned short* m = reinterpret_cast<const unsigned short*>(mem0) + min(i * 128 + t2, DM - 1);
#pragma unroll
                for (int j = 0; j < 4; j++) m0[i][j] = m[2 * j * DM] | (m[(2 * j + 1) * DM] << 16);
            }
            if (w == 3) { bar_sync(15, 288); cnt_add(g_cnt + C_W * 8, lane); TR1(1); }
            else {
                if (w < 2) {
                    unsigned* pp = reinterpret_cast<unsigned*>(ex + inbox_off(b) + 16384 + w * 4096 + 2048);
                    uint32_t best = ~0u, v = 0;
                    if (lane == 0) {
#pragma unroll 1
                        for (int i = 0; i < 5; i++) {
                            const uint32_t c0 = clk();
                            v = atomicAdd(pp + (v >> 31), 0);
                            asm volatile("" :: "r"(v) : "memory");
                            sts32(bar + 80, v);
                            best = min(best, clk() - c0);
                        }
                        sts32(bar + 72 + w * 4, best);
                    }
                }
                bar_sync(8, 96);
                const uint32_t xs = PLACE ? lds32(bar + 76) < lds32(bar + 72) : 0, ep = EP;
                side = PLACE ? xs ^ page_par(inbox_off(b)) : 0;
                rbase = ex + inbox_off(b) + xs * 4096;
                const uint32_t inv = (ep * (NT - 1)) & 1;
#pragma unroll
                for (int i = 0; i < 4; i++) stg128(rbase + (w == 2 ? 16384 : w * 2048) + i * 512 + lane * 16, inv, 0, 0, 0);
                __threadfence();
                bar_sync(8, 96);
                if (t2 == 0) stg_word(g_side + b, (ep + 1) * 2 + xs, true);
                TR1(4);
            }
            delay_until(t_start, DLYW);
#pragma unroll 4
            for (int i = t2; i < 128 * 24; i += 128) {
                const int e = (i >> 3) & 127, G = i >> 10, q = i & 7;
                cp16(sb + O_WO + G * 16384 + e * 128 + ((q ^ (e & 7) ^ ((h >> 1) & 1)) << 4), Wo + (size_t)(h * 128 + e) * DM + G * 192 + r * 64 + q * 8);
            }
            bar_sync(9, 384);
#pragma unroll
            for (int i = 0; i < 5; i++) {
                const int k = min(i * 128 + t2, DM - 1);
                const uint32_t ad = sb + O_MB + (k >> 3) * 256 + (k & 7) * 16;
                sts128(ad, m0[i][0], m0[i][1], m0[i][2], m0[i][3]); sts128(ad + 128, m0[i][0], m0[i][1], m0[i][2], m0[i][3]);
            }
            fence_async_smem();
        }
        auto arm = [&]() {
            const uint32_t ln = l16 >> 4;
            mbar_expect(bar + B_VX + (ln & 3) * 8, ln == 0 ? nv_remote * 2048 : ln == 1 ? nv_remote * 512 + 2560 : 8192, ln < 3);
        };
        if (w == 3) arm();
        cluster_sync();
        TR1(3);
        const int L = w >> 1, hf = w & 1;
        const uint32_t rd = hf ? roff1 : roff0;
        const uint32_t rzero = gridDim.y + 100;
#define WOAD (sb + O_WO + ((l16 & 0x100) << 2) + ((l16 & 0x70) << 3) + (((w * 32) | ((l16 >> 3) & 16)) ^ (l16 & 0x70)))

        auto store_o = [&](int u) {
            asm volatile("{.reg .pred p; setp.eq.u32 p, %3, 0;\n"
                "@p cp.async.bulk.global.shared::cta.bulk_group [%0], [%1], %2;\n cp.async.bulk.commit_group;}"
                :: "l"(g_o + ((u & (RING - 1)) * 256 + h * 8 + 3 * r) * 128), "r"(sb + O_OS), "r"(nq * 2048), "r"(l16) : "memory");
            cnt_hint(g_cnt + (C_O + u * 8 + (h >> 2)) * 8, l16);
            TRG(u, 2);
        };
        bar_arrive(7, 256);
        if (w < 3) {
            bar_arrive(1 + w, 160); bar_arrive(12 + w, 160);
        } else {
            mbar_arrive_all3(bar + B_WIN, l16 >> 4);

        }
        cp_wait_all();
        bar_sync(6, 128);
        uint32_t poff;
        {
            const int rb = r * 32 + w * 8 + (lane >> 2);
            const uint32_t want = EP + 1;
            uint32_t v;
            for (int n = 0; __any_sync(~0u, ((v = ldg_word(g_side + rb)) >> 1) != want); n++) fault_if(n > POLL_LIMIT, n);
            __threadfence();
            poff = inbox_off(rb) + (v & 1) * 4096 + h * 64 + (lane & 3) * 16;
        }
        side = __shfl_sync(~0u, side, 0);
        const uint32_t roff = __shfl_sync(~0u, (uint32_t)(rbase - ex), 0) + (w == 2 ? 16384 : (w & 1) * 2048);
        uint4 a0[8];
#pragma unroll
        for (int kk = 0; kk < 8; kk++) a0[kk] = ldsm4t(WOAD + kk * 2048);
#pragma unroll 1
        for (int t = 0;; t++) {
            TR_ON(t);
            OPQ();
            mbar_wait(bar + B_EP, t & 1);
            if (w == 3) {
                fence_async_smem();
                const uint32_t ad = sb + O_VX + r * 4096;
                asm volatile("{.reg .pred p; setp.eq.u32 p, %5, 0;\n"
                    "@p cp.async.bulk.shared::cluster.shared::cta.mbarrier::complete_tx::bytes [%0], [%2], %6, [%3];\n"
                    "@p cp.async.bulk.shared::cluster.shared::cta.mbarrier::complete_tx::bytes [%1], [%2], %6, [%4];}"
                    :: "r"(ad + roff0), "r"(ad + roff1), "r"(ad), "r"(bar + B_VX + roff0), "r"(bar + B_VX + roff1), "r"(l16), "r"(16384 - 4096 * nq) : "memory");
                TR(7);
            }
            uint4 kx[3][2], vx[4][2];
            const uint32_t lp = LSWAP;
#pragma unroll
            for (int m = 0; m < 3; m++) {
                kx[m][0] = ldsm4(sb + O_KX + m * 2048 + L * 1024 + lp);
                kx[m][1] = ldsm4(sb + O_KX + m * 2048 + L * 1024 + 512 + lp);
            }
            if (w == 3) asm volatile("cp.async.bulk.wait_group.read 0;" ::: "memory");
            mbar_wait(bar + B_VX, t & 1);
            TR(0);
            bar_sync(4, 384);
            float s0[4] = {0, 0, 0, 0}, s1[4] = {0, 0, 0, 0}, sm[4] = {0, 0, 0, 0};
            {
                const uint4 q01 = ldsm4(sb + O_QM + L * 256 + l16 + (l16 & 256));
                const uint2 q2 = ldsm2(sb + O_QM + 1024 + L * 256 + l16);
                uint4 km_[3];
#pragma unroll
                for (int m = 0; m < 3; m++) km_[m] = ldsm4(sb + O_KM + m * 512 + (lp ^ (L << 8)));
                bar_arrive(5, 256);
                mma16(s0, kx[0][0].x, kx[0][0].y, kx[0][0].z, kx[0][0].w, q01.x, q01.y);
                mma16(s1, kx[0][1].x, kx[0][1].y, kx[0][1].z, kx[0][1].w, q01.x, q01.y);
                mma16(sm, km_[0].x, km_[0].y, km_[0].z, km_[0].w, q01.x, q01.y);
                mma16(s0, kx[1][0].x, kx[1][0].y, kx[1][0].z, kx[1][0].w, q01.z, q01.w);
                mma16(s1, kx[1][1].x, kx[1][1].y, kx[1][1].z, kx[1][1].w, q01.z, q01.w);
                mma16(sm, km_[1].x, km_[1].y, km_[1].z, km_[1].w, q01.z, q01.w);
                mma16(s0, kx[2][0].x, kx[2][0].y, kx[2][0].z, kx[2][0].w, q2.x, q2.y);
                mma16(s1, kx[2][1].x, kx[2][1].y, kx[2][1].z, kx[2][1].w, q2.x, q2.y);
                mma16(sm, km_[2].x, km_[2].y, km_[2].z, km_[2].w, q2.x, q2.y);
                const uint32_t ad = sb + O_SM + (1 - hf) * 1280 + L * 640 + rd;
                sta128(ad + l16, pk(s0[0], s0[1]), pk(s0[2], s0[3]), pk(s1[0], s1[1]), pk(s1[2], s1[3]), bar + B_SM + rd);
                sta32(ad + 512 + (l16 >> 2), pk(sm[0], sm[1]), bar + B_SM + rd);
            }
            TR(1);
            if (t + 1 == NT) break;
#pragma unroll
            for (int m = 0; m < 8; m++) vx[m >> 1][m & 1] = lds128(sb + O_VX + (hf * 4 + (m >> 1)) * 2048 + L * 1024 + (m & 1) * 512 + l16);
            const uint32_t tag = (t + EP * (NT - 1) + 1) & 1;
            uint32_t ident = IDENT;
            asm volatile("" : "+r"(ident));
            mbar_wait(bar + B_SM, t & 1);
            TR(2);
            {
                const uint32_t ad = sb + O_SM + L * 640;
                const uint4 u = lds128(ad + l16), v = lds128(ad + 1280 + l16);
                const uint32_t x = lds32(ad + 512 + (l16 >> 2)), y = lds32(ad + 1280 + 512 + (l16 >> 2));
                mma8(s0, u.x, u.y, ident); mma8(s1, u.z, u.w, ident); mma8(s0, v.x, v.y, ident); mma8(s1, v.z, v.w, ident);
                sm[0] += bf_lo(x) + bf_lo(y); sm[1] += bf_hi(x) + bf_hi(y);
            }
            uint2 vm[4];
#pragma unroll
            for (int m = 0; m < 4; m++) vm[m] = lds64(sb + O_VM + (hf * 4 + m) * 512 + l16 + L * 8);
            float mx0 = fmaxf(fmaxf(fmaxf(s0[0], s0[2]), fmaxf(s1[0], s1[2])), sm[0]);
            float mx1 = fmaxf(fmaxf(fmaxf(s0[1], s0[3]), fmaxf(s1[1], s1[3])), sm[1]);
#pragma unroll
            for (int o = 4; o < 32; o <<= 1) { mx0 = fmaxf(mx0, __shfl_xor_sync(~0u, mx0, o)); mx1 = fmaxf(mx1, __shfl_xor_sync(~0u, mx1, o)); }
            mx0 *= -SC; mx1 *= -SC;
            s0[0] = ex2(fmaf(s0[0], SC, mx0)); s0[1] = ex2(fmaf(s0[1], SC, mx1));
            s0[2] = ex2(fmaf(s0[2], SC, mx0)); s0[3] = ex2(fmaf(s0[3], SC, mx1));
            const uint32_t pb0 = movm(pk(s0[0], s0[1])), pb1 = movm(pk(s0[2], s0[3]));
            s1[0] = ex2(fmaf(s1[0], SC, mx0)); s1[1] = ex2(fmaf(s1[1], SC, mx1));
            s1[2] = ex2(fmaf(s1[2], SC, mx0)); s1[3] = ex2(fmaf(s1[3], SC, mx1));
            const uint32_t pb2 = movm(pk(s1[0], s1[1])), pb3 = movm(pk(s1[2], s1[3]));
            sm[0] = ex2(fmaf(sm[0], SC, mx0)); sm[1] = ex2(fmaf(sm[1], SC, mx1));
            const uint32_t pm = movm(pk(sm[0], sm[1]));
            float o[4][4], l[4] = {0, 0, 0, 0};
            const uint32_t one = 0x3f803f80;
            mma8(l, one, one, pb0); mma8(l, one, one, pb1);
#pragma unroll
            for (int m = 0; m < 4; m++) { o[m][0] = o[m][1] = o[m][2] = o[m][3] = 0.f; mma16(o[m], vx[m][0].x, vx[m][0].y, vx[m][0].z, vx[m][0].w, pb0, pb1); }
            mma8(l, one, one, pb2); mma8(l, one, one, pb3);
#pragma unroll
            for (int m = 0; m < 4; m++) mma16(o[m], vx[m][1].x, vx[m][1].y, vx[m][1].z, vx[m][1].w, pb2, pb3);
            mma8(l, one, one, pm);
#pragma unroll
            for (int m = 0; m < 4; m++) mma8(o[m], vm[m].x, vm[m].y, pm);
            const float l0 = rcp(l[0]), l1 = rcp(l[1]);
#pragma unroll
            for (int m = 0; m < 4; m += 2)
                stsm4t(sb + O_OX + (hf * 4 + m) * 512 + (L ^ ((h >> 2) & 1)) * 256   + ((l16 & 0x100) << 1) + (l16 & 0xf0),
                       pk(o[m][0] * l0, o[m][1] * l1), pk(o[m][2] * l0, o[m][3] * l1), pk(o[m + 1][0] * l0, o[m + 1][1] * l1), pk(o[m + 1][2] * l0, o[m + 1][3] * l1));
            TR(3);
            char* const pdst = ex + poff;
            const char* const rsrc = ex + roff + l16;
            uint4 v[4] = {};
            bar_sync(6, 128);
            {
                uint4 bo[8], a1[8], z;
                const uint32_t wad = WOAD;
#pragma unroll
                for (int kk = 0; kk < 8; kk++) bo[kk] = ldsm4(sb + O_OX + kk * 512 + l16);
#pragma unroll
                for (int G = 0; G < 3; G++) {
                    float e[4][4];
#pragma unroll
                    for (int q = 0; q < 4; q++) e[q][0] = e[q][1] = e[q][2] = e[q][3] = 0.f;
#pragma unroll
                    for (int kk = 0; kk < 8; kk++) {
                        const uint4 f = G == 0 ? a0[kk] : a1[kk];
                        mma16(e[(kk & 1) * 2], f.x, f.y, f.z, f.w, bo[kk].x, bo[kk].y);
                        mma16(e[(kk & 1) * 2 + 1], f.x, f.y, f.z, f.w, bo[kk].z, bo[kk].w);
                        if (G == 2 && kk == EK) {
#pragma unroll
                            for (int i = 0; i < 4; i++) { v[i].x = ~tag; ldg_pkt_if(v[i], rsrc + i * 512, w < EARLY); }
                            sched_fence(rzero, 5);
                            bar_arrive(11, 384);
                        }
                        if (G == 1) a1[kk] = ldsm4t(wad + 32768 + kk * 2048);
                        if (G == 0 && kk == FK) {
                            sched_fence(rzero, 2);
#pragma unroll
                            for (int j = 0; j < 8; j++) a1[j] = ldsm4t(wad + 16384 + j * 2048);
                        }
                    }
                    if (G > 0) asm volatile("{.reg .pred p; setp.eq.u32 p, %5, 0; @p st.shared.v4.u32 [%0], {%1,%2,%3,%4};}" :: "r"(__float_as_uint(e[0][0])), "r"(z.x), "r"(z.y), "r"(z.z), "r"(z.w), "r"(rzero));
                    z = make_uint4((pk(e[0][0] + e[2][0], e[0][1] + e[2][1]) & ~1u) | tag, pk(e[0][2] + e[2][2], e[0][3] + e[2][3]),
                                   pk(e[1][0] + e[3][0], e[1][1] + e[3][1]), pk(e[1][2] + e[3][2], e[1][3] + e[3][3]));
                    stg_pkt(pdst + (G == 2 ? 16384 : G * 2048), z.x, z.y, z.z, z.w);
                    if (G == 0) { TR(9); TRD(t, 0); }
                    if (G < 2) sched_fence(rzero, 3 + G);
                }
            }
            TR(4);
            if (w < 3) {
                bar_arrive(7, 256);
                OPQ();
                const uint32_t tagm = tag;
                uint32_t m0v = 0;
                if (t + 1 <= LAG) {
                    const unsigned short* m = reinterpret_cast<const unsigned short*>(mem0) + ((l16 >> 3) & 6) * DM + 192 * w + 16 * (b >> 3) + (b & 7) + ((l16 >> 4) & 8);
                    m0v = m[0] | (m[DM] << 16);
                }
                delay(DLY1);
                for (int n = 0; __any_sync(~0u, lop_bad(lop_bad(0, v[0].x, v[1].x, tagm), v[2].x, v[3].x, tagm) & 1); n++) {
#pragma unroll
                    for (int i = 0; i < 4; i++) v[i] = ldg_pkt(rsrc + i * 512);
                    fault_if(n > POLL_LIMIT, n);
                }
                TR(5); TRD(t, 1);
                float s[8];
                s[4] = (bf_lo(v[0].z) + bf_lo(v[1].z)) + (bf_lo(v[2].z) + bf_lo(v[3].z)); s[5] = (bf_hi(v[0].z) + bf_hi(v[1].z)) + (bf_hi(v[2].z) + bf_hi(v[3].z));
                s[6] = (bf_lo(v[0].w) + bf_lo(v[1].w)) + (bf_lo(v[2].w) + bf_lo(v[3].w)); s[7] = (bf_hi(v[0].w) + bf_hi(v[1].w)) + (bf_hi(v[2].w) + bf_hi(v[3].w));
                s[2] = (bf_lo(v[0].y) + bf_lo(v[1].y)) + (bf_lo(v[2].y) + bf_lo(v[3].y)); s[3] = (bf_hi(v[0].y) + bf_hi(v[1].y)) + (bf_hi(v[2].y) + bf_hi(v[3].y));
                s[0] = (bf_lo(v[0].x) + bf_lo(v[1].x)) + (bf_lo(v[2].x) + bf_lo(v[3].x)); s[1] = (bf_hi(v[0].x) + bf_hi(v[1].x)) + (bf_hi(v[2].x) + bf_hi(v[3].x));
#pragma unroll
                for (int j = 0; j < 4; j++) s[j] += __shfl_xor_sync(~0u, s[j + 4], 16);
#pragma unroll
                for (int j = 0; j < 2; j++) s[j] += __shfl_xor_sync(~0u, s[j + 2], 8);
#pragma unroll
                for (int j = 0; j < 2; j++) s[j] += __shfl_xor_sync(~0u, s[j], 4);
                char* const mem_w = ex + mem_off(w, 0);
                uint32_t res = t + 1 <= LAG && l16 >= 256 ? m0v : pk(s[0], s[1]);
                if ((l16 & 48) == 0) res = (res & ~1u) | tag;
                stg_word(mem_w + (mem_off(0, b >> 3) - mem_off(0, 0)) + (b & 7) * 16 + (((l16 & 64) << 6) + ((l16 & 128) << 1) + ((l16 & 256) >> 1) + ((l16 >> 2) & 12)), res, true);
                if (w + 5 == XST) bar_arrive(8, 64);
                TR(6); TRD(t, 2);
                delay(DLY2);
                const char* src = mem_w + (side ^ page_par(0x180000)) * 4096 + l16;
                const uint32_t gdst = sb + O_MB + w * 6144 + l16;
                uint4 x[12];
#pragma unroll
                for (int i = 0; i < 12; i++) x[i] = ldg_pkt(src + (mem_off(0, i) - mem_off(0, 0)));
                for (int n = 0;; n++) {
                    uint32_t bad = 0;
#pragma unroll
                    for (int i = 0; i < 12; i += 2) bad = lop_bad(bad, x[i].x, x[i + 1].x, tagm);
                    if (!__any_sync(~0u, bad & 1)) break;
#pragma unroll
                    for (int i = 0; i < 12; i++) ldg_pkt_retry(x[i], src + (mem_off(0, i) - mem_off(0, 0)), tagm);
                    fault_if(n > POLL_LIMIT, n);
                }
#pragma unroll
                for (int i = 0; i < 12; i++) sts128(gdst + i * 512, x[i].x, x[i].y, x[i].z, x[i].w);
                TR(7); TRD(t, 3);
                fence_async_smem();
                bar_arrive(12 + w, 160);
                bar_arrive(1 + w, 160);
                TR(8);
            } else {
                mbar_wait(bar + B_X, (t + 1) & 1);
                bar_sync(7, 256);
                fence_async_smem();
                arm();
                __syncwarp();
                mbar_arrive_all3(bar + B_WIN, l16 >> 4);
                if (XST > 4) bar_sync(8, 64);
                delay(DLYO);
                store_o(t);
                cnt_poll(g_cnt + (C_X + t + 2) * 8, 64 * (EP + 1), bar + B_EP, (t + 1) & 1, bar + 8, t + 2);
                TR(5);
            }
        }
        if (w == 3) { bar_sync(7, 160); fence_async_smem(); store_o(NT - 1); asm volatile("cp.async.bulk.wait_group 0;" ::: "memory"); }
        cluster_sync();
    }
    TR_DUMP(b);
}

#define VP 12
#define VC 19
#define VG 12
#define HB 3
#define HA 2
#define HW 0
namespace ka {
constexpr int O_WA = 196608;
constexpr int A_KB = 21504;
constexpr int O_RING = 194560;
constexpr int O_BAR = 230400;
constexpr int SMEM = O_BAR + 256 + 1024;
constexpr float SC = 0.23570226039551584f * 1.4426950408889634f;
}

template <int NP, int KB = 4096>
DEVI void row_task(const uint4* res, const uint4* part, uint4* xout, char* img, int pos, int lane, uint32_t tag) {
    const bool on = lane < 24;
    const int ln = on ? lane : 0;
    uint4 rv[3], pv[NP > 0 ? NP * 3 : 1];
#pragma unroll
    for (int i = 0; i < 3; i++) rv[i] = ldg128(res + i * 24 + ln);
#pragma unroll
    for (int i = 0; i < NP * 3; i++) pv[i] = ldg_pkt(part + i * 24 + ln);
    if (NP > 0) validate<NP * 3>(pv, part + ln, 384, tag);
#pragma unroll
    for (int q = 0; q < NP * 3 / 2; q++) {
        const uint4 y = pv[q + NP * 3 / 2];
        pv[q] = make_uint4(add2(pv[q].x, y.x), add2(pv[q].y, y.y), add2(pv[q].z, y.z), add2(pv[q].w, y.w));
    }
    float x[24];
#pragma unroll
    for (int i = 0; i < 3; i++) {
        x[8 * i] = bf_lo(rv[i].x); x[8 * i + 1] = bf_hi(rv[i].x); x[8 * i + 2] = bf_lo(rv[i].y); x[8 * i + 3] = bf_hi(rv[i].y);
        x[8 * i + 4] = bf_lo(rv[i].z); x[8 * i + 5] = bf_hi(rv[i].z); x[8 * i + 6] = bf_lo(rv[i].w); x[8 * i + 7] = bf_hi(rv[i].w);
    }
    if (NP > 0) {
#pragma unroll
        for (int q = 0; q < NP * 3 / 2; q++) {
            const int i = q % 3;
            x[8 * i] += bf_lo(pv[q].x); x[8 * i + 1] += bf_hi(pv[q].x); x[8 * i + 2] += bf_lo(pv[q].y); x[8 * i + 3] += bf_hi(pv[q].y);
            x[8 * i + 4] += bf_lo(pv[q].z); x[8 * i + 5] += bf_hi(pv[q].z); x[8 * i + 6] += bf_lo(pv[q].w); x[8 * i + 7] += bf_hi(pv[q].w);
        }
#pragma unroll
        for (int i = 0; i < 3; i++) {
            uint32_t w[4];
#pragma unroll
            for (int j = 0; j < 4; j++) { w[j] = pk(x[8 * i + 2 * j], x[8 * i + 2 * j + 1]); x[8 * i + 2 * j] = bf_lo(w[j]); x[8 * i + 2 * j + 1] = bf_hi(w[j]); }
            stg128p(xout + i * 24 + ln, w[0], w[1], w[2], w[3], on);
        }
    }
    if (img) {
        float s = 0.f;
#pragma unroll
        for (int j = 0; j < 24; j++) s += x[j];
        if (!on) s = 0.f;
#pragma unroll
        for (int o = 1; o < 32; o <<= 1) s += __shfl_xor_sync(~0u, s, o);
        const float mean = s * (1.f / DM);
        float v = 0.f;
#pragma unroll
        for (int j = 0; j < 24; j++) { x[j] -= mean; v = fmaf(x[j], x[j], v); }
        if (!on) v = 0.f;
#pragma unroll
        for (int o = 1; o < 32; o <<= 1) v += __shfl_xor_sync(~0u, v, o);
        const float rs = rsqrtf(v * (1.f / DM) + 1e-5f);
        char* dst = img + (ln >> 3) * KB + pos * 128 + (((ln ^ pos) & 7) << 4);
#pragma unroll
        for (int i = 0; i < 3; i++)
            stg128p(dst + i * (3 * KB), pk(x[8 * i] * rs, x[8 * i + 1] * rs), pk(x[8 * i + 2] * rs, x[8 * i + 3] * rs),
                    pk(x[8 * i + 4] * rs, x[8 * i + 5] * rs), pk(x[8 * i + 6] * rs, x[8 * i + 7] * rs), on);
    }
}

DEVI void rows_a(const uint4* xin, int f, int i, int lane, uint32_t ep, int warp) {
    for (int u = 0; u < LAG; u++) cnt_hint(g_cnt + (C_X + u + (f ? 0 : NSEG)) * 8, lane);
#pragma unroll 1
    for (int seg = 0; seg < NSEG; seg++) {
        const int j = seg + f * LAGA, u = seg + f * LAG, row = seg * 32 + i;
        hint_wait(g_cnt + (C_WA + j * 4 + f * 2 + (i & 1)) * 8, 24 * (ep + 1));
        TRG(u, 0);
        row_task<4, 8192>((f ? g_x + 2048 * 72 : xin) + row * 72, g_pa + ((j & (RING - 1)) * 64 + f * 32 + i) * 288,
                    g_x + (f * 4096 + row) * 72, reinterpret_cast<char*>(g_xt + u * 4608 + f * 256), i, lane, ring_tag<NTA>(j, ep));
        TRG(u, 1);
        cnt_add(g_cnt + (C_X + u) * 8, lane);
        TRG(u, 2);
    }
}

__global__ void __launch_bounds__(384, 1)
k_aux(const __nv_bfloat16* __restrict__ x0, const __nv_bfloat16* __restrict__ wqkv, const __nv_bfloat16* __restrict__ wo,
      const __nv_bfloat16* __restrict__ Wo, __nv_bfloat16* __restrict__ out) {
    using namespace ka;
    extern __shared__ unsigned char smem_raw[];
    const uint32_t sb = (smem_u32(smem_raw) + 1023) & ~1023u;
    const int tid = threadIdx.x, lane = tid & 31, warp = __shfl_sync(~0u, tid >> 5, 0), g = lane >> 2, c = lane & 3;
    const int b = blockIdx.x;
    const uint32_t bar = sb + O_BAR;
    const uint32_t ep = __shfl_sync(~0u, ldg32(&g_epoch), 0);

    TRG(79, 0);
    const uint4* xin = reinterpret_cast<const uint4*>(x0);
    if (warp >= 8 || b == 35) {
        asm volatile("setmaxnreg.dec.sync.aligned.u32 128;");
        const int rw = b < 24 ? (warp - 8) * 24 + b : b < 35 ? (warp - 8) * 11 + b - 24 : 128 + 2 * warp;
        if (b < 24 || b == 35 || rw < 32) {
#pragma unroll 1
            for (int row = b < 24 ? rw + 32 : rw; row < 2048; row += (row & 1) ? 23 : 1) {
                if (lane == 0 && b == 35 && row < 2024) prefetch_l2(xin + (row + 24) * 72, 1152);
                row_task<0>(xin + row * 72, nullptr, nullptr, reinterpret_cast<char*>(g_xa + (row >> 5) * 4608), (row & 1) * 16 + ((row & 31) >> 1), lane, 0);
                if (b < 35) { cnt_add(g_cnt + (C_N0 + (row >> 5)) * 8, lane); break; }
                if (row & 1) cnt_add<2>(g_cnt + (C_N0 + (row >> 5)) * 8, lane);
            }
        }
        if (rw < 32) {
            const int f = b < 24, i = rw;
#pragma unroll 1
            for (int seg = 0; seg < NSEG; seg++) {
                const int u = seg + f * LAG, row = seg * 32 + i;
                hint_wait(g_cnt + (C_WB + u * 4 + f * 2 + (i >> 4)) * 8, 24 * (ep + 1));
                TRG(u, 0);
                row_task<8>(g_x + (f * 4096 + row) * 72, g_pb + ((u & (RING - 1)) * 64 + f * 32 + i) * 576,
                            f ? reinterpret_cast<uint4*>(out) + row * 72 : g_x + (2048 + row) * 72,
                            f ? nullptr : reinterpret_cast<char*>(g_xa + (seg + LAGA) * 4608 + 2304), (i & 1) * 16 + (i >> 1), lane, ring_tag(u, ep));
                TRG(u, 1);
                cnt_add(g_cnt + (C_RB + f * NSEG + seg) * 8, lane);
                TRG(u, 2);
            }
            if (f && rw == 31) {
                asm volatile("griddepcontrol.wait;" ::: "memory");
                if (lane == 0) g_epoch = ep + 1;
            }
        } else if (rw < 64 && b < 24) rows_a(xin, 0, rw - 32, lane, ep, warp);
        return;
    }

    if (b < 24) {
        if (warp >= 4) {
            const int kq = b / 6, nq = b % 6;
            uint4 v[17];
#pragma unroll
            for (int q = 0; q < 17; q++) {
                const int it = q * 4 + warp - 4, kr = (it / 3) * 8 + g, s = kq * 11 + (kr >> 4), a = s >> 2, j = s & 3, e = kr & 15;
                const int head = 3 * a + (j < 3 ? j : e >> 1), row = head * 18 + (j < 3 ? e : 16 + (e & 1));
                v[q] = make_uint4(0, 0, 0, 0);
                if (it < 66 && head < 32 && (j < 3 || e < 6)) v[q] = *reinterpret_cast<const uint4*>(wo + row * DM + nq * 96 + (it % 3) * 32 + c * 8);
            }
#pragma unroll
            for (int q = 0; q < 17; q++) {
                const int it = q * 4 + warp - 4;
                const uint32_t ad = sb + O_WA + (it % 3) * 4 * 2816 + (it / 3) * 128 + lane * 4;
                if (it < 66) { sts32(ad, v[q].x); sts32(ad + 2816, v[q].y); sts32(ad + 2 * 2816, v[q].z); sts32(ad + 3 * 2816, v[q].w); }
            }
        } else {
            const int kg = b / 3, ng = b % 3;
            delay(DLYB);
#pragma unroll 1
            for (int bt = 0; bt < 4; bt++) {
                uint4 v[24];
#pragma unroll
                for (int q = 0; q < 24; q++)
                    v[q] = *reinterpret_cast<const uint4*>(Wo + (size_t)(kg * 512 + (bt * 4 + q / 6) * 32 + warp * 8 + g) * DM + ng * 192 + (q % 6) * 32 + c * 8);
#pragma unroll
                for (int q = 0; q < 24; q++) {
                    const uint32_t ad = sb + (q % 6) * 4 * 8192 + ((bt * 4 + q / 6) * 4 + warp) * 128 + lane * 4;
                    sts32(ad, v[q].x); sts32(ad + 8192, v[q].y); sts32(ad + 2 * 8192, v[q].z); sts32(ad + 3 * 8192, v[q].w);
                }
            }
        }
        fence_async_smem();
        bar_sync(2 + (warp >> 2), 128);
    } else {
        for (int i = tid; i < 2048; i += 256) sts128(sb + O_RING + i * 16, 0, 0, 0, 0);
        if (tid < 17) mbar_init(bar + tid * 8, tid >= 4 && tid < 8 ? 4 : 1);
        fence_async_smem();
        bar_sync(1, 256);
    }
    TRG(79, 1);
    const int wq = warp & 3;

    if (warp < 4) {
        asm volatile("setmaxnreg.inc.sync.aligned.u32 256;");
        if (b < 24) {
            const int kg = b / 3, ng = b % 3;
            const uint32_t blo = ((sb >> 4) & 0x3fff) | (8u << 16);
            uint4 a[32];
            uint32_t seen = 0;
            bool pre = false;
#pragma unroll 1
            for (int u = 0; u < NT; u++) {
                const uint32_t tag = ring_tag(u, ep);
                const uint4* src = g_o + (((u & (RING - 1)) * 256 + kg * 32) * 4 + wq) * 32 + lane;
                if (!pre) {
                    if (!__all_sync(~0u, seen >= 12 * (ep + 1))) hint_wait(g_cnt + (C_O + u * 8 + kg) * 8, 12 * (ep + 1));
#pragma unroll
                    for (int i = 0; i < VG; i++) a[i] = ldg_pkt(src + i * 128);
                }
                TRG(u, 0);
                float d[96];
                validate<VG>(a, src, 2048, tag);
                if (!pre) {
#pragma unroll
                    for (int i = VG; i < VP; i++) a[i] = ldg_pkt(src + i * 128);
                }
#pragma unroll
                for (int i = VP; i < 32; i++) a[i] = ldg_pkt(src + i * 128);
                wg_fence();
#pragma unroll
                for (int i = 0; i < 32; i++) {
                    if (i == VG) { validate<32 - VG>(a + VG, src + VG * 128, 2048, tag); wg_fence(); }
                    wgmma_rs192t(d, a[i].x, a[i].y, a[i].z, a[i].w, mkdesc(blo + i * 16, 512), i > 0);
                    if (i == VC - 1 || i == 23 || i == 31) wg_commit();
                }
                const unsigned* cn = g_cnt + (C_O + min(u + 1, NT - 1) * 8 + kg) * 8;
                const uint4* nx = g_o + ((((u + 1) & (RING - 1)) * 256 + kg * 32) * 4 + wq) * 32 + lane;
                auto look = [&]() {
                    pre = __all_sync(~0u, seen >= 12 * (ep + 1));
                    if (pre) {
#pragma unroll
                        for (int i = 0; i < VP; i++) a[i] = ldg_pkt(nx + i * 128);
                    } else seen = ldg_word(cn);
                };
                wg_wait<2>();
                seen = ldg_word(cn);
                wg_wait<1>();
                look();
                wg_wait<0>();
                if (!pre) look();
                TRG(u, 1);
                uint4* dst = g_pb + (((u & (RING - 1)) * 64 + wq * 16 + g) * 8 + kg) * 72 + ng * 24 + c;
#pragma unroll
                for (int m = 0; m < 6; m++) {
                    if (m == HB) cnt_hint(g_cnt + (C_WB + u * 4 + wq) * 8, lane);
                    stg128(dst + 4 * m, (pk(d[16 * m], d[16 * m + 1]) & ~1u) | tag, pk(d[16 * m + 4], d[16 * m + 5]), pk(d[16 * m + 8], d[16 * m + 9]), pk(d[16 * m + 12], d[16 * m + 13]));
                    stg128(dst + 4 * m + 8 * 576, (pk(d[16 * m + 2], d[16 * m + 3]) & ~1u) | tag, pk(d[16 * m + 6], d[16 * m + 7]), pk(d[16 * m + 10], d[16 * m + 11]), pk(d[16 * m + 14], d[16 * m + 15]));
                }
                TRG(u, 3);
            }
        } else {
            const int a = b - 24, f = wq >> 1;
            const uint32_t blo = ((sb >> 4) & 0x3fff) | (8u << 16), alo = (((sb + O_RING) >> 4) & 0x3fff) | (1u << 16);
            const bool m0 = 2 * c <= g, m1 = 2 * c + 1 <= g;
            const uint32_t M = (m0 ? 0xffffu : 0u) | (m1 ? 0xffff0000u : 0u);
            uint32_t kh[7], vh[7];
#pragma unroll
            for (int i = 0; i < 7; i++) kh[i] = vh[i] = 0;
            int it = 0;
#pragma unroll 1
            for (int u = 0; u < NTA; u++) {
                float d[84];
#pragma unroll 1
                for (int kb = 0; kb < 9; kb++, it++) {
                    mbar_wait(bar + (it & 3) * 8, (it >> 2) & 1);
                    if (u == 0) mbar_wait(bar + 64 + kb * 8, 0);
                    if (kb == 0) TRG(u, 0);
                    wg_fence();
#pragma unroll
                    for (int q = 0; q < 4; q++)
                        wgmma_ss168t(d, mkdesc(alo + (it & 3) * 512 + q * 2, km::DESC_HI), mkdesc(blo + kb * (A_KB >> 4) + q * 16, 64), kb + q > 0);
                    wg_commit();
                    wg_wait<1>();
                    mbar_arrive(bar + 32 + ((it - 1) & 3) * 8, lane == 0 && kb > 0);
                }
                wg_wait<0>();
                mbar_arrive(bar + 32 + ((it - 1) & 3) * 8, lane == 0);
                TRG(u, 1);
                const bool first = u == f * LAGA;
                const uint32_t tag = ring_tag<NTA>(u, ep);
                const uint32_t qt0 = pk(d[72], d[73]), qt1 = pk(d[74], d[75]), kt0 = pk(d[76], d[77]), kt1 = pk(d[78], d[79]);
                const uint32_t vt0 = movm(pk(d[80], d[81])), vt1 = movm(pk(d[82], d[83]));
                float ot[4] = {0, 0, 0, 0};
                uint4* dst = g_oa + (((u & (RING - 1)) * 4 + wq) * 44 + a * 4) * 32 + lane;
#pragma unroll
                for (int h = 0; h < 3; h++) {
                    const float* q = d + 8 * h; const float* k = d + 24 + 8 * h; const float* v = d + 48 + 8 * h;
                    const uint32_t q0 = pk(q[0], q[1]), q1 = pk(q[2], q[3]), q2 = pk(q[4], q[5]), q3 = pk(q[6], q[7]);
                    const uint32_t k0 = pk(k[0], k[1]), k1 = pk(k[4], k[5]), k2 = pk(k[2], k[3]), k3 = pk(k[6], k[7]);
                    const uint32_t v0 = movm(pk(v[0], v[1])), v1 = movm(pk(v[2], v[3])), v2 = movm(pk(v[4], v[5])), v3 = movm(pk(v[6], v[7]));
                    const uint32_t t0 = c == h ? qt0 : 0, t1 = c == h ? qt1 : 0;
                    float sp[4] = {0, 0, 0, 0}, sl[4] = {0, 0, 0, 0}, sh[4] = {0, 0, 0, 0};
                    mma16(sp, q0, q1, q2, q3, kh[2 * h], kh[2 * h + 1]); mma16(sl, q0, q1, q2, q3, k0, k1); mma16(sh, q0, q1, q2, q3, k2, k3);
                    mma8(sp, t0, t1, kh[6]); mma8(sl, t0, t1, kt0); mma8(sh, t0, t1, kt1);
                    float x0_ = m0 ? sl[0] : first ? -INFINITY : sp[0], x1_ = m1 ? sl[1] : first ? -INFINITY : sp[1];
                    float y0_ = m0 ? sh[2] : sl[2], y1_ = m1 ? sh[3] : sl[3];
                    float mx = fmaxf(x0_, x1_), my = fmaxf(y0_, y1_);
#pragma unroll
                    for (int o = 1; o < 4; o <<= 1) { mx = fmaxf(mx, __shfl_xor_sync(~0u, mx, o)); my = fmaxf(my, __shfl_xor_sync(~0u, my, o)); }
                    mx *= -SC; my *= -SC;
                    x0_ = ex2(fmaf(x0_, SC, mx)); x1_ = ex2(fmaf(x1_, SC, mx)); y0_ = ex2(fmaf(y0_, SC, my)); y1_ = ex2(fmaf(y1_, SC, my));
                    float lx = x0_ + x1_, ly = y0_ + y1_;
#pragma unroll
                    for (int o = 1; o < 4; o <<= 1) { lx += __shfl_xor_sync(~0u, lx, o); ly += __shfl_xor_sync(~0u, ly, o); }
                    lx = rcp(lx); ly = rcp(ly);
                    const uint32_t px = pk(x0_ * lx, x1_ * lx), py = pk(y0_ * ly, y1_ * ly);
                    const uint32_t hm = (g >> 1) == h ? ~0u : 0u;
                    float o0[4] = {0, 0, 0, 0}, o1[4] = {0, 0, 0, 0};
                    mma16(o0, px & M, py & ~M, 0, py & M, v0, v1); mma16(o1, px & M, py & ~M, 0, py & M, v2, v3);
                    mma16(ot, px & M, py & ~M, 0, py & M, vt0 & hm, vt1 & hm);
                    mma8(o0, px & ~M, 0, vh[2 * h]); mma8(o1, px & ~M, 0, vh[2 * h + 1]); mma8(ot, px & ~M, 0, vh[6] & hm);
                    if (h == HA) cnt_hint(g_cnt + (C_A + u * 4 + wq) * 8, lane);
                    stg128(dst + h * 32, (pk(o0[0], o0[1]) & ~1u) | tag, pk(o0[2], o0[3]), pk(o1[0], o1[1]), pk(o1[2], o1[3]));
                    kh[2 * h] = k2; kh[2 * h + 1] = k3; vh[2 * h] = v1; vh[2 * h + 1] = v3;
                }
                kh[6] = kt1; vh[6] = vt1;
                stg128(dst + 96, (pk(ot[0], ot[1]) & ~1u) | tag, pk(ot[2], ot[3]), 0, 0);
                TRG(u, 2);
            }
        }
    } else {
        asm volatile("setmaxnreg.dec.sync.aligned.u32 120;");
        if (b < 24) {
            const int kq = b / 6, nq = b % 6;
            const uint32_t blo = (((sb + O_WA) >> 4) & 0x3fff) | (8u << 16);
#pragma unroll 1
            for (int u = 0; u < NTA; u++) {
                hint_wait(g_cnt + (C_A + u * 4 + wq) * 8, 11 * (ep + 1));
                const uint32_t tag = ring_tag<NTA>(u, ep);
                TRG(u, 0);
                const uint4* src = g_oa + (((u & (RING - 1)) * 4 + wq) * 44 + kq * 11) * 32 + lane;
                uint4 a[11];
                float d[48];
#pragma unroll
                for (int i = 0; i < 11; i++) a[i] = ldg_pkt(src + i * 32);
                validate<11>(a, src, 512, tag);
                wg_fence();
#pragma unroll
                for (int i = 0; i < 11; i++) wgmma_rs96t(d, a[i].x, a[i].y, a[i].z, a[i].w, mkdesc(blo + i * 16, 176), i > 0);
                wg_commit();
                wg_wait<0>();
                TRG(u, 1);
                uint4* dst = g_pa + (((u & (RING - 1)) * 64 + (wq >> 1) * 32 + 2 * g + (wq & 1)) * 4 + kq) * 72 + nq * 12 + c;
#pragma unroll
                for (int m = 0; m < 3; m++) {
                    if (m == HW) cnt_hint(g_cnt + (C_WA + u * 4 + wq) * 8, lane);
                    stg128(dst + 4 * m, (pk(d[16 * m], d[16 * m + 1]) & ~1u) | tag, pk(d[16 * m + 4], d[16 * m + 5]), pk(d[16 * m + 8], d[16 * m + 9]), pk(d[16 * m + 12], d[16 * m + 13]));
                    stg128(dst + 4 * m + 16 * 288, (pk(d[16 * m + 2], d[16 * m + 3]) & ~1u) | tag, pk(d[16 * m + 6], d[16 * m + 7]), pk(d[16 * m + 10], d[16 * m + 11]), pk(d[16 * m + 14], d[16 * m + 15]));
                }
                TRG(u, 3);
            }
        } else if (warp == 4) {
            mbar_expect(bar + 64 + lane * 8, A_KB, lane < 9);
            int it = 0;
#pragma unroll 1
            for (int u = 0; u < NTA; u++) {
                if (u == 0) { cnt_wait(g_cnt + C_W * 8, 96 * (ep + 1)); TRG(78, 0); }
                if (u < NSEG) cnt_wait(g_cnt + (C_N0 + u) * 8, 32 * (ep + 1));
                if (u > LAGA + LAG) cnt_wait(g_cnt + (C_RB + NSEG + u - LAGA - LAG - 1) * 8, 32 * (ep + 1));
                if (u >= LAGA) cnt_wait(g_cnt + (C_RB + u - LAGA) * 8, 32 * (ep + 1));
                TRG(u, 0);
                asm volatile("fence.proxy.async.global;" ::: "memory");
                const bool on = lane == 0 ? u < NSEG : lane == 1 && u >= LAGA;
#pragma unroll 1
                for (int kb = 0; kb < 9; kb++, it++) {
                    if (it >= 4) mbar_wait(bar + 32 + (it & 3) * 8, ((it >> 2) - 1) & 1);
                    mbar_expect(bar + (it & 3) * 8, u < NSEG && u >= LAGA ? 8192 : 4096, lane == 0);
                    asm volatile("{.reg .pred p; setp.ne.u32 p, %3, 0; @p cp.async.bulk.shared::cluster.global.mbarrier::complete_tx::bytes [%0], [%1], 4096, [%2];}"
                        :: "r"(sb + O_RING + (it & 3) * 8192 + (lane & 1) * 4096), "l"(g_xa + u * 4608 + (lane & 1) * 2304 + kb * 256), "r"(bar + (it & 3) * 8), "r"((uint32_t)on) : "memory");
                    if (u == 0) asm volatile("{.reg .pred p; setp.ne.u32 p, %4, 0; @p cp.async.bulk.shared::cluster.global.mbarrier::complete_tx::bytes [%0], [%1], %3, [%2];}"
                        :: "r"(sb + lane * A_KB), "l"(g_wa + ((b - 24) * 9 + lane) * (A_KB / 16)), "r"(bar + 64 + lane * 8), "n"(A_KB),
                           "r"((uint32_t)(lane < 9 && kb == (lane < 4 ? lane : lane < 6 ? 3 : lane - 2))) : "memory");
                }
            }
        } else if ((warp - 5) * 11 + b - 24 < 32) rows_a(xin, 1, (warp - 5) * 11 + b - 24, lane, ep, warp);
    }
}

extern "C" void kernel_launch(void* const* d_in, const int* in_sizes, int n_in, void* d_out, int out_size) {
    const __nv_bfloat16* x = (const __nv_bfloat16*)d_in[0];
    const __nv_bfloat16* wqkv = (const __nv_bfloat16*)d_in[1];
    const __nv_bfloat16* wo = (const __nv_bfloat16*)d_in[2];
    const __nv_bfloat16* mem0 = (const __nv_bfloat16*)d_in[4];
    const __nv_bfloat16* Wq = (const __nv_bfloat16*)d_in[5];
    const __nv_bfloat16* Wk = (const __nv_bfloat16*)d_in[6];
    const __nv_bfloat16* Wv = (const __nv_bfloat16*)d_in[7];
    const __nv_bfloat16* Wo = (const __nv_bfloat16*)d_in[8];
    cudaFuncSetAttribute(k_main, cudaFuncAttributeMaxDynamicSharedMemorySize, km::SMEM);
    cudaFuncSetAttribute(k_aux, cudaFuncAttributeMaxDynamicSharedMemorySize, ka::SMEM);
    cudaStream_t s = cudaStreamPerThread;
    k_main<<<96, 384, km::SMEM, s>>>(x, wqkv, wo, mem0, Wq, Wk, Wv, Wo);
    cudaLaunchConfig_t cfg = {};
    cudaLaunchAttribute at[1];
    at[0].id = cudaLaunchAttributeProgrammaticStreamSerialization;
    at[0].val.programmaticStreamSerializationAllowed = 1;
    cfg.stream = s; cfg.attrs = at; cfg.numAttrs = 1;
    cfg.gridDim = dim3(36); cfg.blockDim = dim3(384); cfg.dynamicSmemBytes = ka::SMEM;
    cudaLaunchKernelEx(&cfg, k_aux, x, wqkv, wo, Wo, (__nv_bfloat16*)d_out);
}
```

```cpp
#include <cuda_runtime.h>
#include <cuda_bf16.h>
#include <stdint.h>

#define LAG 7
constexpr int NSEG = 64;
constexpr int NT = NSEG + LAG;
#define AHEAD 1
constexpr int LAGA = LAG + AHEAD;
constexpr int NTA = NSEG + LAGA;
#define RING_ 8
constexpr int RING = RING_;
constexpr int DM = 576;

__device__ __align__(1024) uint4 g_xt[NT * 2 * 9 * 256];
__device__ __align__(1024) uint4 g_o[RING * 4 * 256 * 32];
__device__ __align__(1024) uint4 g_ex[2 * 131072];
__device__ unsigned g_side[96];
__device__ __align__(1024) uint4 g_pb[RING * 64 * 8 * 72];
__device__ __align__(1024) uint4 g_pa[RING * 64 * 4 * 72];
__device__ __align__(1024) uint4 g_oa[RING * 4 * 44 * 32];
__device__ __align__(1024) uint4 g_xa[NTA * 2 * 9 * 256];
__device__ __align__(1024) uint4 g_wa[11 * 9 * 21 * 64];
__device__ __align__(1024) uint4 g_x[3 * 2048 * 72];

constexpr int C_X = 0;
constexpr int C_O = C_X + NT;
constexpr int C_WB = C_O + NT * 8;
constexpr int C_RB = C_WB + NT * 4;
constexpr int C_A = C_RB + 2 * NSEG;
constexpr int C_WA = C_A + NTA * 4;
constexpr int C_N0 = C_WA + NTA * 4;
constexpr int C_W = C_N0 + NSEG;
constexpr int C_DONE = C_W + 1;
constexpr int C_TOTAL = C_DONE + 1;
__device__ __align__(1024) unsigned g_cnt[C_TOTAL * 8];
__device__ unsigned g_epoch;

struct Tune { uint32_t v[10]; };
#define TR(i)
#define TR1(i)
#define TR_ON(t)
#define TR_INIT(base)
#define TR_DUMP(slot)
#define TRG(t, i)
constexpr int TR_BYTES = 0;

#define DEVI __device__ __forceinline__
DEVI uint32_t smem_u32(const void* p) { return (uint32_t)__cvta_generic_to_shared(p); }
DEVI uint32_t pk(float lo, float hi) { uint32_t r; asm("cvt.rn.bf16x2.f32 %0, %1, %2;" : "=r"(r) : "f"(hi), "f"(lo)); return r; }
DEVI float bf_lo(uint32_t u) { return __uint_as_float(u << 16); }
DEVI float bf_hi(uint32_t u) { return __uint_as_float(u & 0xffff0000u); }
DEVI uint32_t add2(uint32_t a, uint32_t b) { uint32_t d; asm("add.rn.bf16x2 %0, %1, %2;" : "=r"(d) : "r"(a), "r"(b)); return d; }
DEVI uint32_t movm(uint32_t a) { uint32_t d; asm volatile("movmatrix.sync.aligned.m8n8.trans.b16 %0, %1;" : "=r"(d) : "r"(a)); return d; }
DEVI float2 shfl2(float a, float b, int o) {
    float2 r; asm volatile("shfl.sync.bfly.b32 %0, %2, %4, 31, -1; shfl.sync.bfly.b32 %1, %3, %4, 31, -1;" : "=&f"(r.x), "=f"(r.y) : "f"(a), "f"(b), "r"(o)); return r;
}
DEVI float ex2(float x) { float y; asm("ex2.approx.ftz.f32 %0, %1;" : "=f"(y) : "f"(x)); return y; }
DEVI float rcp(float x) { float y; asm("rcp.approx.ftz.f32 %0, %1;" : "=f"(y) : "f"(x)); return y; }
DEVI void mma16(float (&d)[4], uint32_t a0, uint32_t a1, uint32_t a2, uint32_t a3, uint32_t b0, uint32_t b1) {
    asm volatile("mma.sync.aligned.m16n8k16.row.col.f32.bf16.bf16.f32 {%0,%1,%2,%3}, {%4,%5,%6,%7}, {%8,%9}, {%0,%1,%2,%3};"
        : "+f"(d[0]), "+f"(d[1]), "+f"(d[2]), "+f"(d[3]) : "r"(a0), "r"(a1), "r"(a2), "r"(a3), "r"(b0), "r"(b1));
}
DEVI void mma8(float (&d)[4], uint32_t a0, uint32_t a1, uint32_t b0) {
    asm volatile("mma.sync.aligned.m16n8k8.row.col.f32.bf16.bf16.f32 {%0,%1,%2,%3}, {%4,%5}, {%6}, {%0,%1,%2,%3};"
        : "+f"(d[0]), "+f"(d[1]), "+f"(d[2]), "+f"(d[3]) : "r"(a0), "r"(a1), "r"(b0));
}
DEVI uint4 lds128(uint32_t a) { uint4 v; asm volatile("ld.shared.v4.u32 {%0,%1,%2,%3}, [%4];" : "=r"(v.x), "=r"(v.y), "=r"(v.z), "=r"(v.w) : "r"(a) : "memory"); return v; }
DEVI uint2 lds64(uint32_t a) { uint2 v; asm volatile("ld.shared.v2.u32 {%0,%1}, [%2];" : "=r"(v.x), "=r"(v.y) : "r"(a) : "memory"); return v; }
DEVI uint32_t lds32(uint32_t a) { uint32_t v; asm volatile("ld.shared.u32 %0, [%1];" : "=r"(v) : "r"(a) : "memory"); return v; }
DEVI uint32_t lds32v(uint32_t a) { uint32_t v; asm volatile("ld.volatile.shared.u32 %0, [%1];" : "=r"(v) : "r"(a) : "memory"); return v; }
DEVI uint4 lds128v(uint32_t a) { uint4 v; asm volatile("ld.volatile.shared.v4.u32 {%0,%1,%2,%3}, [%4];" : "=r"(v.x), "=r"(v.y), "=r"(v.z), "=r"(v.w) : "r"(a) : "memory"); return v; }
DEVI uint32_t lds16(uint32_t a) { uint32_t v; asm volatile("ld.shared.u16 %0, [%1];" : "=r"(v) : "r"(a) : "memory"); return v; }
DEVI uint4 ldsm4(uint32_t a) { uint4 v; asm volatile("ldmatrix.sync.aligned.m8n8.x4.shared.b16 {%0,%1,%2,%3}, [%4];" : "=r"(v.x), "=r"(v.y), "=r"(v.z), "=r"(v.w) : "r"(a) : "memory"); return v; }
DEVI uint4 ldsm4p(uint32_t a, bool pred) {
    uint4 v; asm volatile("{.reg .pred p; setp.ne.u32 p, %5, 0; @p ldmatrix.sync.aligned.m8n8.x4.shared.b16 {%0,%1,%2,%3}, [%4];}" : "=r"(v.x), "=r"(v.y), "=r"(v.z), "=r"(v.w) : "r"(a), "r"((uint32_t)pred) : "memory"); return v;
}
DEVI uint4 ldsm4t(uint32_t a) { uint4 v; asm volatile("ldmatrix.sync.aligned.m8n8.x4.trans.shared.b16 {%0,%1,%2,%3}, [%4];" : "=r"(v.x), "=r"(v.y), "=r"(v.z), "=r"(v.w) : "r"(a) : "memory"); return v; }
DEVI uint2 ldsm2(uint32_t a) { uint2 v; asm volatile("ldmatrix.sync.aligned.m8n8.x2.shared.b16 {%0,%1}, [%2];" : "=r"(v.x), "=r"(v.y) : "r"(a) : "memory"); return v; }
DEVI void stsm4t(uint32_t a, uint32_t x, uint32_t y, uint32_t z, uint32_t w) { asm volatile("stmatrix.sync.aligned.m8n8.x4.trans.shared.b16 [%0], {%1,%2,%3,%4};" :: "r"(a), "r"(x), "r"(y), "r"(z), "r"(w) : "memory"); }
DEVI void sts128(uint32_t a, uint32_t x, uint32_t y, uint32_t z, uint32_t w) { asm volatile("st.shared.v4.u32 [%0], {%1,%2,%3,%4};" :: "r"(a), "r"(x), "r"(y), "r"(z), "r"(w) : "memory"); }
DEVI void sts64(uint32_t a, uint32_t x, uint32_t y) { asm volatile("st.shared.v2.u32 [%0], {%1,%2};" :: "r"(a), "r"(x), "r"(y) : "memory"); }
DEVI void sts32(uint32_t a, uint32_t x) { asm volatile("st.shared.u32 [%0], %1;" :: "r"(a), "r"(x) : "memory"); }
DEVI void sts32p(uint32_t a, uint32_t x, bool pred) { asm volatile("{.reg .pred p; setp.ne.u32 p, %2, 0; @p st.shared.u32 [%0], %1;}" :: "r"(a), "r"(x), "r"((uint32_t)pred) : "memory"); }
DEVI void sta128(uint32_t a, uint32_t x, uint32_t y, uint32_t z, uint32_t w, uint32_t bar) {
    asm volatile("st.async.weak.shared::cluster.mbarrier::complete_tx::bytes.v4.b32 [%0], {%1,%2,%3,%4}, [%5];" :: "r"(a), "r"(x), "r"(y), "r"(z), "r"(w), "r"(bar) : "memory");
}
DEVI void sta128p(uint32_t a, uint32_t x, uint32_t y, uint32_t z, uint32_t w, uint32_t bar, bool pred) {
    asm volatile("{.reg .pred p; setp.ne.u32 p, %6, 0; @p st.async.weak.shared::cluster.mbarrier::complete_tx::bytes.v4.b32 [%0], {%1,%2,%3,%4}, [%5];}" :: "r"(a), "r"(x), "r"(y), "r"(z), "r"(w), "r"(bar), "r"((uint32_t)pred) : "memory");
}
DEVI void sta64(uint32_t a, uint32_t x, uint32_t y, uint32_t bar) {
    asm volatile("st.async.weak.shared::cluster.mbarrier::complete_tx::bytes.v2.b32 [%0], {%1,%2}, [%3];" :: "r"(a), "r"(x), "r"(y), "r"(bar) : "memory");
}
DEVI void sta32(uint32_t a, uint32_t x, uint32_t bar) {
    asm volatile("st.async.weak.shared::cluster.mbarrier::complete_tx::bytes.b32 [%0], %1, [%2];" :: "r"(a), "r"(x), "r"(bar) : "memory");
}
DEVI uint4 ldg_pkt(const void* p) {
    uint4 v;
    asm volatile("ld.relaxed.gpu.global.v4.u32 {%0,%1,%2,%3}, [%4];" : "=r"(v.x), "=r"(v.y), "=r"(v.z), "=r"(v.w) : "l"(p) : "memory");
    return v;
}
DEVI void ldg_pkt_if(uint4& v, const void* p, bool pred) {
    asm volatile("{.reg .pred p; setp.ne.u32 p, %5, 0; @p ld.relaxed.gpu.global.v4.u32 {%0,%1,%2,%3}, [%4];}"
        : "+r"(v.x), "+r"(v.y), "+r"(v.z), "+r"(v.w) : "l"(p), "r"((uint32_t)pred) : "memory");
}
DEVI void ldg_pkt_retry(uint4& v, const void* p, uint32_t tag) {
    asm volatile("{.reg .pred p; .reg .b32 t; lop3.b32 t, %0, %5, 1, 0x28; setp.ne.u32 p, t, 0; @p ld.relaxed.gpu.global.v4.u32 {%0,%1,%2,%3}, [%4];}"
        : "+r"(v.x), "+r"(v.y), "+r"(v.z), "+r"(v.w) : "l"(p), "r"(tag) : "memory");
}
DEVI void stg_pkt(void* p, uint32_t x, uint32_t y, uint32_t z, uint32_t w) {
    asm volatile("st.relaxed.gpu.global.v4.u32 [%0], {%1,%2,%3,%4};" :: "l"(p), "r"(x), "r"(y), "r"(z), "r"(w) : "memory");
}
DEVI uint32_t ldg_word(const void* p) { uint32_t v; asm volatile("ld.relaxed.gpu.global.u32 %0, [%1];" : "=r"(v) : "l"(p) : "memory"); return v; }
DEVI void stg_word(void* p, uint32_t x, bool pred) {
    asm volatile("{.reg .pred p; setp.ne.u32 p, %2, 0; @p st.relaxed.gpu.global.u32 [%0], %1;}" :: "l"(p), "r"(x), "r"((uint32_t)pred) : "memory");
}
DEVI uint2 ldg64nc(const void* p) { uint2 v; asm volatile("ld.global.nc.L1::no_allocate.v2.u32 {%0,%1}, [%2];" : "=r"(v.x), "=r"(v.y) : "l"(p)); return v; }
DEVI void prefetch_l2(const void* p, uint32_t bytes) { asm volatile("cp.async.bulk.prefetch.L2.global [%0], %1;" :: "l"(p), "r"(bytes) : "memory"); }
DEVI uint4 ldg128(const void* p) { uint4 v; asm volatile("ld.global.cg.v4.u32 {%0,%1,%2,%3}, [%4];" : "=r"(v.x), "=r"(v.y), "=r"(v.z), "=r"(v.w) : "l"(p) : "memory"); return v; }
DEVI uint2 ldg64(const void* p) { uint2 v; asm volatile("ld.global.cg.v2.u32 {%0,%1}, [%2];" : "=r"(v.x), "=r"(v.y) : "l"(p) : "memory"); return v; }
DEVI uint32_t ldg32(const void* p) { uint32_t v; asm volatile("ld.global.cg.u32 %0, [%1];" : "=r"(v) : "l"(p) : "memory"); return v; }
DEVI void stg128(void* p, uint32_t x, uint32_t y, uint32_t z, uint32_t w) { asm volatile("st.global.cg.v4.u32 [%0], {%1,%2,%3,%4};" :: "l"(p), "r"(x), "r"(y), "r"(z), "r"(w) : "memory"); }
DEVI void stg128p(void* p, uint32_t x, uint32_t y, uint32_t z, uint32_t w, bool pred) { asm volatile("{.reg .pred p; setp.ne.u32 p, %5, 0; @p st.global.cg.v4.u32 [%0], {%1,%2,%3,%4};}" :: "l"(p), "r"(x), "r"(y), "r"(z), "r"(w), "r"((uint32_t)pred) : "memory"); }
DEVI void stg64(void* p, uint32_t x, uint32_t y) { asm volatile("st.global.cg.v2.u32 [%0], {%1,%2};" :: "l"(p), "r"(x), "r"(y) : "memory"); }
DEVI void stg32(void* p, uint32_t x) { asm volatile("st.global.cg.u32 [%0], %1;" :: "l"(p), "r"(x) : "memory"); }
DEVI void cp16(uint32_t dst, const void* src) { asm volatile("cp.async.cg.shared.global [%0], [%1], 16;" :: "r"(dst), "l"(src) : "memory"); }
DEVI void cp16_if(uint32_t dst, const void* src, bool pred) { asm volatile("{.reg .pred p; setp.ne.u32 p, %2, 0; @p cp.async.cg.shared.global [%0], [%1], 16;}" :: "r"(dst), "l"(src), "r"((uint32_t)pred) : "memory"); }
DEVI void cp_commit() { asm volatile("cp.async.commit_group;" ::: "memory"); }
DEVI void cp4(uint32_t dst, const void* src) { asm volatile("cp.async.ca.shared.global [%0], [%1], 4;" :: "r"(dst), "l"(src) : "memory"); }
template <int N> DEVI void cp_wait() { asm volatile("cp.async.wait_group %0;" :: "n"(N) : "memory"); }
DEVI void cp_wait_all() { asm volatile("cp.async.wait_all;" ::: "memory"); }
DEVI void bar_sync(int id, int n) { asm volatile("bar.sync %0, %1;" :: "r"(id), "r"(n) : "memory"); }
DEVI void bar_arrive(int id, int n) { asm volatile("bar.arrive %0, %1;" :: "r"(id), "r"(n) : "memory"); }
DEVI void fence_async_smem() { asm volatile("fence.proxy.async.shared::cta;" ::: "memory"); }
DEVI void fence_async_global() { asm volatile("fence.proxy.async.global;" ::: "memory"); }
DEVI void mbar_init(uint32_t b, int n) { asm volatile("mbarrier.init.shared.b64 [%0], %1;" :: "r"(b), "r"(n) : "memory"); }
DEVI void mbar_expect(uint32_t b, uint32_t bytes, bool pred) {
    asm volatile("{.reg .pred p; setp.ne.u32 p, %2, 0; @p mbarrier.arrive.expect_tx.shared.b64 _, [%0], %1;}" :: "r"(b), "r"(bytes), "r"((uint32_t)pred) : "memory");
}
DEVI void mbar_arrive(uint32_t b, bool pred) { asm volatile("{.reg .pred p; setp.ne.u32 p, %1, 0; @p mbarrier.arrive.shared.b64 _, [%0];}" :: "r"(b), "r"((uint32_t)pred) : "memory"); }
DEVI void mbar_arrive_all3(uint32_t b, uint32_t lane) {
    asm volatile("{.reg .pred p; .reg .u32 a; setp.lt.u32 p, %1, 3; @p mapa.shared::cluster.u32 a, %0, %1; @p mbarrier.arrive.relaxed.cluster.shared::cluster.b64 _, [a];}" :: "r"(b), "r"(lane) : "memory");
}
#define FAULT "or.b32 n, n, 1; st.volatile.shared.u32 [n], n;\n"
#define LIM1 "400000"
#define LIM2 "2000000"
DEVI void fault_if(bool p, uint32_t n) { asm volatile("{.reg .pred p; setp.ne.u32 p, %0, 0; @p st.volatile.shared.u32 [%1], %1;}" :: "r"((uint32_t)p), "r"(n | 1) : "memory"); }
DEVI void mbar_wait(uint32_t b, uint32_t parity) {
    asm volatile("{.reg .pred p; .reg .u32 n;\n"
        "mbarrier.try_wait.parity.shared::cta.b64 p, [%0], %1;\n"
        "@p bra.uni D%=;\n"
        "mov.u32 n, 0;\n"
        "W%=: mbarrier.try_wait.parity.shared::cta.b64 p, [%0], %1;\n"
        "@p bra.uni D%=;\n"
        "add.u32 n, n, 1; setp.lt.u32 p, n, " LIM1 "; @p bra.uni W%=;\n"
        FAULT
        "D%=:}" :: "r"(b), "r"(parity) : "memory");
}
constexpr int POLL_LIMIT = 2000000;
DEVI void cnt_wait(const unsigned* c, unsigned target) {
    asm volatile("{.reg .pred p; .reg .u32 n, v;\n"
        "ld.acquire.gpu.global.u32 v, [%0];\n"
        "setp.ge.u32 p, v, %1; vote.sync.all.pred p, p, 0xffffffff; @p bra.uni D%=;\n"
        "mov.u32 n, 0;\n"
        "W%=: ld.acquire.gpu.global.u32 v, [%0];\n"
        "setp.ge.u32 p, v, %1; vote.sync.all.pred p, p, 0xffffffff; @p bra.uni D%=;\n"
        "add.u32 n, n, 1; setp.lt.u32 p, n, " LIM2 "; @p bra.uni W%=;\n"
        FAULT
        "D%=:}" :: "l"(c), "r"(target) : "memory");
}
DEVI void hint_wait(const unsigned* c, unsigned target) {
    asm volatile("{.reg .pred p; .reg .u32 n, v;\n"
        "ld.relaxed.gpu.global.u32 v, [%0];\n"
        "setp.ge.u32 p, v, %1; vote.sync.all.pred p, p, 0xffffffff; @p bra.uni D%=;\n"
        "mov.u32 n, 0;\n"
        "W%=: ld.relaxed.gpu.global.u32 v, [%0];\n"
        "setp.ge.u32 p, v, %1; vote.sync.all.pred p, p, 0xffffffff; @p bra.uni D%=;\n"
        "add.u32 n, n, 1; setp.lt.u32 p, n, " LIM2 "; @p bra.uni W%=;\n"
        FAULT
        "D%=:}" :: "l"(c), "r"(target) : "memory");
}
DEVI void cnt_poll(const unsigned* c, unsigned target, uint32_t b, uint32_t parity, uint32_t flag, uint32_t val) {
    asm volatile("{.reg .pred p, q; .reg .u32 n, v;\n"
        "mov.u32 n, 0;\n"
        "W%=: ld.acquire.gpu.global.u32 v, [%0];\n"
        "setp.ge.u32 q, v, %1; @q st.release.cta.shared.u32 [%4], %5;\n"
        "mbarrier.test_wait.parity.shared::cta.b64 p, [%2], %3;\n"
        "add.u32 n, n, 1; setp.gt.or.u32 p, n, 1000, p; or.pred p, p, q; vote.sync.any.pred p, p, 0xffffffff; @!p bra.uni W%=;\n"
        "}" :: "l"(c), "r"(target), "r"(b), "r"(parity), "r"(flag), "r"(val) : "memory");
}
DEVI uint32_t lds_acq(uint32_t a) { uint32_t v; asm volatile("ld.acquire.cta.shared.u32 %0, [%1];" : "=r"(v) : "r"(a) : "memory"); return v; }
template <int N = 1> DEVI void cnt_add(unsigned* c, int lane) {
    asm volatile("{.reg .pred p; setp.eq.u32 p, %1, 0; fence.acq_rel.gpu; bar.warp.sync 0xffffffff; @p red.relaxed.gpu.global.add.u32 [%0], %2;}" :: "l"(c + lane), "r"(lane), "n"(N) : "memory");
}
DEVI void cnt_hint(unsigned* c, int lane) {
    asm volatile("{.reg .pred p; setp.eq.u32 p, %1, 0; @p red.relaxed.gpu.global.add.u32 [%0], 1;}" :: "l"(c + lane), "r"(lane) : "memory");
}
template <int N = NT> DEVI uint32_t ring_tag(unsigned u, uint32_t ep) { return (u / RING + ep * ((N - 1 - u % RING) / RING + 1) + 1) & 1; }
static_assert(RING >= LAGA && RING > LAG, "ring too short");
DEVI uint32_t lop_bad(uint32_t acc, uint32_t x, uint32_t y, uint32_t tag) {
    uint32_t d; asm("{.reg .b32 t; lop3.b32 t, %2, %3, %4, 0x7e; or.b32 %0, t, %1;}" : "=r"(d) : "r"(acc), "r"(x), "r"(y), "r"(tag)); return d;
}
template <int N> DEVI void validate(uint4* v, const void* p, int step, uint32_t tag) {
    for (int n = 0;; n++) {
        uint32_t bad = 0;
#pragma unroll
        for (int i = 0; i < N; i += 2) bad = lop_bad(bad, v[i].x, v[i + 1 < N ? i + 1 : i].x, tag);
        if (!__any_sync(~0u, bad & 1)) break;
#pragma unroll
        for (int i = 0; i < N; i++) ldg_pkt_retry(v[i], static_cast<const char*>(p) + i * step, tag);
        fault_if(n > POLL_LIMIT, n);
    }
}
DEVI uint32_t page_par(uint32_t off) { return __popc((off >> 12) & 0xb2) & 1; }
DEVI uint32_t inbox_off(int b) { return (b >> 1) * 32768 + (b & 1) * 8192; }
DEVI uint32_t mem_off(int w, int i) { return 0x180000 + w * 1024 + (i & 1) * 512 + (i & 3) * 16384 + (i < 4 ? 0 : i < 8 ? 0x30000 : 0x40000); }
DEVI void sched_fence(uint32_t zero, uint32_t id) { asm volatile("{.reg .pred p; setp.ne.u32 p, %0, %1; @p bra.uni D%=; exit; D%=:}" :: "r"(zero), "r"(id) : "memory"); }
DEVI uint32_t clk() { uint32_t c; asm volatile("mov.u32 %0, %%clock;" : "=r"(c) :: "memory"); return c; }
DEVI void delay(uint32_t n) {
    if (n) asm volatile("{.reg .pred p; .reg .u32 c, e; mov.u32 e, %%clock;\n W%=: mov.u32 c, %%clock; sub.u32 c, c, e; setp.lt.u32 p, c, %0; @p bra.uni W%=;}" :: "r"(n) : "memory");
}
DEVI void pause(uint32_t n) {
    asm volatile("{.reg .pred p; .reg .f32 x; .reg .s32 c; cvt.rn.f32.u32 x, %0;\n"
        "W%=: add.f32 x, x, 0fBF800000; mul.f32 x, x, x; sqrt.approx.ftz.f32 x, x; setp.gt.f32 p, x, 0f3F000000; @p bra.uni W%=;\n"
        "setp.lt.f32 p, x, 0fC1000000; @p st.volatile.shared.f32 [%0], x;}" :: "r"(n) : "memory");
}
DEVI void delay_until(uint32_t t0, uint32_t n) {
    asm volatile("{.reg .pred p; .reg .u32 c;\n W%=: mov.u32 c, %%clock; sub.u32 c, c, %1; setp.lt.u32 p, c, %0; @p bra.uni W%=;}" :: "r"(n), "r"(t0) : "memory");
}
DEVI void wg_fence() { asm volatile("wgmma.fence.sync.aligned;" ::: "memory"); }
DEVI void wg_commit() { asm volatile("wgmma.commit_group.sync.aligned;" ::: "memory"); }
template <int N> DEVI void wg_wait() { asm volatile("wgmma.wait_group.sync.aligned %0;" :: "n"(N) : "memory"); }
DEVI uint64_t mkdesc(uint32_t lo, uint32_t hi) { uint64_t d; asm("mov.b64 %0, {%1,%2};" : "=l"(d) : "r"(lo), "r"(hi)); return d; }
DEVI void cluster_arrive() { asm volatile("barrier.cluster.arrive.relaxed.aligned;" ::: "memory"); }
DEVI void cluster_wait() { asm volatile("barrier.cluster.wait.aligned;" ::: "memory"); }
DEVI void cluster_sync() { asm volatile("barrier.cluster.arrive.aligned;\n barrier.cluster.wait.aligned;" ::: "memory"); }
DEVI void wgmma_ss16t(float (&d)[8], uint64_t da, uint64_t db, int acc) {
    asm volatile("{.reg .pred p; setp.ne.b32 p, %10, 0;\n"
        "wgmma.mma_async.sync.aligned.m64n16k16.f32.bf16.bf16 {%0,%1,%2,%3,%4,%5,%6,%7}, %8, %9, p, 1, 1, 0, 1;}"
        : "+f"(d[0]), "+f"(d[1]), "+f"(d[2]), "+f"(d[3]), "+f"(d[4]), "+f"(d[5]), "+f"(d[6]), "+f"(d[7])
        : "l"(da), "l"(db), "r"(acc));
}
DEVI void wgmma_ss16a(float (&d)[8], uint64_t da, uint64_t db, int acc) {
    asm volatile("{.reg .pred p; setp.ne.b32 p, %10, 0;\n"
        "wgmma.mma_async.sync.aligned.m64n16k16.f32.bf16.bf16 {%0,%1,%2,%3,%4,%5,%6,%7}, %8, %9, p, 1, 1, 1, 0;}"
        : "+f"(d[0]), "+f"(d[1]), "+f"(d[2]), "+f"(d[3]), "+f"(d[4]), "+f"(d[5]), "+f"(d[6]), "+f"(d[7])
        : "l"(da), "l"(db), "r"(acc));
}
DEVI void wgmma_ss64(float (&d)[32], uint64_t da, uint64_t db, int acc) {
    asm volatile("{.reg .pred p; setp.ne.b32 p, %34, 0;\n"
        "wgmma.mma_async.sync.aligned.m64n64k16.f32.bf16.bf16 {%0,%1,%2,%3,%4,%5,%6,%7,%8,%9,%10,%11,%12,%13,%14,%15,%16,%17,%18,%19,%20,%21,%22,%23,%24,%25,%26,%27,%28,%29,%30,%31}, %32, %33, p, 1, 1, 0, 0;}"
        : "+f"(d[0]), "+f"(d[1]), "+f"(d[2]), "+f"(d[3]), "+f"(d[4]), "+f"(d[5]), "+f"(d[6]), "+f"(d[7]), "+f"(d[8]), "+f"(d[9]), "+f"(d[10]), "+f"(d[11]), "+f"(d[12]), "+f"(d[13]), "+f"(d[14]), "+f"(d[15]), "+f"(d[16]), "+f"(d[17]), "+f"(d[18]), "+f"(d[19]), "+f"(d[20]), "+f"(d[21]), "+f"(d[22]), "+f"(d[23]), "+f"(d[24]), "+f"(d[25]), "+f"(d[26]), "+f"(d[27]), "+f"(d[28]), "+f"(d[29]), "+f"(d[30]), "+f"(d[31])
        : "l"(da), "l"(db), "r"(acc));
}
DEVI void wgmma_rs16t(float (&d)[8], uint32_t a0, uint32_t a1, uint32_t a2, uint32_t a3, uint64_t db, int acc) {
    asm volatile("{.reg .pred p; setp.ne.b32 p, %13, 0;\n"
        "wgmma.mma_async.sync.aligned.m64n16k16.f32.bf16.bf16 {%0,%1,%2,%3,%4,%5,%6,%7}, {%8,%9,%10,%11}, %12, p, 1, 1, 1;}"
        : "+f"(d[0]), "+f"(d[1]), "+f"(d[2]), "+f"(d[3]), "+f"(d[4]), "+f"(d[5]), "+f"(d[6]), "+f"(d[7])
        : "r"(a0), "r"(a1), "r"(a2), "r"(a3), "l"(db), "r"(acc));
}
DEVI void wgmma_rs64(float (&d)[32], uint32_t a0, uint32_t a1, uint32_t a2, uint32_t a3, uint64_t db, int acc) {
    asm volatile("{.reg .pred p; setp.ne.b32 p, %37, 0;\n"
        "wgmma.mma_async.sync.aligned.m64n64k16.f32.bf16.bf16 {%0,%1,%2,%3,%4,%5,%6,%7,%8,%9,%10,%11,%12,%13,%14,%15,%16,%17,%18,%19,%20,%21,%22,%23,%24,%25,%26,%27,%28,%29,%30,%31}, {%32,%33,%34,%35}, %36, p, 1, 1, 0;}"
        : "+f"(d[0]), "+f"(d[1]), "+f"(d[2]), "+f"(d[3]), "+f"(d[4]), "+f"(d[5]), "+f"(d[6]), "+f"(d[7]), "+f"(d[8]), "+f"(d[9]), "+f"(d[10]), "+f"(d[11]), "+f"(d[12]), "+f"(d[13]), "+f"(d[14]), "+f"(d[15]), "+f"(d[16]), "+f"(d[17]), "+f"(d[18]), "+f"(d[19]), "+f"(d[20]), "+f"(d[21]), "+f"(d[22]), "+f"(d[23]), "+f"(d[24]), "+f"(d[25]), "+f"(d[26]), "+f"(d[27]), "+f"(d[28]), "+f"(d[29]), "+f"(d[30]), "+f"(d[31])
        : "r"(a0), "r"(a1), "r"(a2), "r"(a3), "l"(db), "r"(acc));
}
DEVI void wgmma_ss168t(float (&d)[84], uint64_t da, uint64_t db, int acc) {
    asm volatile("{.reg .pred p; setp.ne.b32 p, %86, 0;\n"
        "wgmma.mma_async.sync.aligned.m64n168k16.f32.bf16.bf16 {%0,%1,%2,%3,%4,%5,%6,%7,%8,%9,%10,%11,%12,%13,%14,%15,%16,%17,%18,%19,%20,%21,%22,%23,%24,%25,%26,%27,%28,%29,%30,%31,%32,%33,%34,%35,%36,%37,%38,%39,%40,%41,%42,%43,%44,%45,%46,%47,%48,%49,%50,%51,%52,%53,%54,%55,%56,%57,%58,%59,%60,%61,%62,%63,%64,%65,%66,%67,%68,%69,%70,%71,%72,%73,%74,%75,%76,%77,%78,%79,%80,%81,%82,%83}, %84, %85, p, 1, 1, 0, 1;}"
        : "+f"(d[0]), "+f"(d[1]), "+f"(d[2]), "+f"(d[3]), "+f"(d[4]), "+f"(d[5]), "+f"(d[6]), "+f"(d[7]), "+f"(d[8]), "+f"(d[9]), "+f"(d[10]), "+f"(d[11]), "+f"(d[12]), "+f"(d[13]), "+f"(d[14]), "+f"(d[15]), "+f"(d[16]), "+f"(d[17]), "+f"(d[18]), "+f"(d[19]), "+f"(d[20]), "+f"(d[21]), "+f"(d[22]), "+f"(d[23]), "+f"(d[24]), "+f"(d[25]), "+f"(d[26]), "+f"(d[27]), "+f"(d[28]), "+f"(d[29]), "+f"(d[30]), "+f"(d[31]), "+f"(d[32]), "+f"(d[33]), "+f"(d[34]), "+f"(d[35]), "+f"(d[36]), "+f"(d[37]), "+f"(d[38]), "+f"(d[39]), "+f"(d[40]), "+f"(d[41]), "+f"(d[42]), "+f"(d[43]), "+f"(d[44]), "+f"(d[45]), "+f"(d[46]), "+f"(d[47]), "+f"(d[48]), "+f"(d[49]), "+f"(d[50]), "+f"(d[51]), "+f"(d[52]), "+f"(d[53]), "+f"(d[54]), "+f"(d[55]), "+f"(d[56]), "+f"(d[57]), "+f"(d[58]), "+f"(d[59]), "+f"(d[60]), "+f"(d[61]), "+f"(d[62]), "+f"(d[63]), "+f"(d[64]), "+f"(d[65]), "+f"(d[66]), "+f"(d[67]), "+f"(d[68]), "+f"(d[69]), "+f"(d[70]), "+f"(d[71]), "+f"(d[72]), "+f"(d[73]), "+f"(d[74]), "+f"(d[75]), "+f"(d[76]), "+f"(d[77]), "+f"(d[78]), "+f"(d[79]), "+f"(d[80]), "+f"(d[81]), "+f"(d[82]), "+f"(d[83])
        : "l"(da), "l"(db), "r"(acc));
}
DEVI void wgmma_rs96t(float (&d)[48], uint32_t a0, uint32_t a1, uint32_t a2, uint32_t a3, uint64_t db, int acc) {
    asm volatile("{.reg .pred p; setp.ne.b32 p, %53, 0;\n"
        "wgmma.mma_async.sync.aligned.m64n96k16.f32.bf16.bf16 {%0,%1,%2,%3,%4,%5,%6,%7,%8,%9,%10,%11,%12,%13,%14,%15,%16,%17,%18,%19,%20,%21,%22,%23,%24,%25,%26,%27,%28,%29,%30,%31,%32,%33,%34,%35,%36,%37,%38,%39,%40,%41,%42,%43,%44,%45,%46,%47}, {%48,%49,%50,%51}, %52, p, 1, 1, 1;}"
        : "+f"(d[0]), "+f"(d[1]), "+f"(d[2]), "+f"(d[3]), "+f"(d[4]), "+f"(d[5]), "+f"(d[6]), "+f"(d[7]), "+f"(d[8]), "+f"(d[9]), "+f"(d[10]), "+f"(d[11]), "+f"(d[12]), "+f"(d[13]), "+f"(d[14]), "+f"(d[15]), "+f"(d[16]), "+f"(d[17]), "+f"(d[18]), "+f"(d[19]), "+f"(d[20]), "+f"(d[21]), "+f"(d[22]), "+f"(d[23]), "+f"(d[24]), "+f"(d[25]), "+f"(d[26]), "+f"(d[27]), "+f"(d[28]), "+f"(d[29]), "+f"(d[30]), "+f"(d[31]), "+f"(d[32]), "+f"(d[33]), "+f"(d[34]), "+f"(d[35]), "+f"(d[36]), "+f"(d[37]), "+f"(d[38]), "+f"(d[39]), "+f"(d[40]), "+f"(d[41]), "+f"(d[42]), "+f"(d[43]), "+f"(d[44]), "+f"(d[45]), "+f"(d[46]), "+f"(d[47])
        : "r"(a0), "r"(a1), "r"(a2), "r"(a3), "l"(db), "r"(acc));
}
DEVI void wgmma_rs192t(float (&d)[96], uint32_t a0, uint32_t a1, uint32_t a2, uint32_t a3, uint64_t db, int acc) {
    asm volatile("{.reg .pred p; setp.ne.b32 p, %101, 0;\n"
        "wgmma.mma_async.sync.aligned.m64n192k16.f32.bf16.bf16 {%0,%1,%2,%3,%4,%5,%6,%7,%8,%9,%10,%11,%12,%13,%14,%15,%16,%17,%18,%19,%20,%21,%22,%23,%24,%25,%26,%27,%28,%29,%30,%31,%32,%33,%34,%35,%36,%37,%38,%39,%40,%41,%42,%43,%44,%45,%46,%47,%48,%49,%50,%51,%52,%53,%54,%55,%56,%57,%58,%59,%60,%61,%62,%63,%64,%65,%66,%67,%68,%69,%70,%71,%72,%73,%74,%75,%76,%77,%78,%79,%80,%81,%82,%83,%84,%85,%86,%87,%88,%89,%90,%91,%92,%93,%94,%95}, {%96,%97,%98,%99}, %100, p, 1, 1, 1;}"
        : "+f"(d[0]), "+f"(d[1]), "+f"(d[2]), "+f"(d[3]), "+f"(d[4]), "+f"(d[5]), "+f"(d[6]), "+f"(d[7]), "+f"(d[8]), "+f"(d[9]), "+f"(d[10]), "+f"(d[11]), "+f"(d[12]), "+f"(d[13]), "+f"(d[14]), "+f"(d[15]), "+f"(d[16]), "+f"(d[17]), "+f"(d[18]), "+f"(d[19]), "+f"(d[20]), "+f"(d[21]), "+f"(d[22]), "+f"(d[23]), "+f"(d[24]), "+f"(d[25]), "+f"(d[26]), "+f"(d[27]), "+f"(d[28]), "+f"(d[29]), "+f"(d[30]), "+f"(d[31]), "+f"(d[32]), "+f"(d[33]), "+f"(d[34]), "+f"(d[35]), "+f"(d[36]), "+f"(d[37]), "+f"(d[38]), "+f"(d[39]), "+f"(d[40]), "+f"(d[41]), "+f"(d[42]), "+f"(d[43]), "+f"(d[44]), "+f"(d[45]), "+f"(d[46]), "+f"(d[47]), "+f"(d[48]), "+f"(d[49]), "+f"(d[50]), "+f"(d[51]), "+f"(d[52]), "+f"(d[53]), "+f"(d[54]), "+f"(d[55]), "+f"(d[56]), "+f"(d[57]), "+f"(d[58]), "+f"(d[59]), "+f"(d[60]), "+f"(d[61]), "+f"(d[62]), "+f"(d[63]), "+f"(d[64]), "+f"(d[65]), "+f"(d[66]), "+f"(d[67]), "+f"(d[68]), "+f"(d[69]), "+f"(d[70]), "+f"(d[71]), "+f"(d[72]), "+f"(d[73]), "+f"(d[74]), "+f"(d[75]), "+f"(d[76]), "+f"(d[77]), "+f"(d[78]), "+f"(d[79]), "+f"(d[80]), "+f"(d[81]), "+f"(d[82]), "+f"(d[83]), "+f"(d[84]), "+f"(d[85]), "+f"(d[86]), "+f"(d[87]), "+f"(d[88]), "+f"(d[89]), "+f"(d[90]), "+f"(d[91]), "+f"(d[92]), "+f"(d[93]), "+f"(d[94]), "+f"(d[95])
        : "r"(a0), "r"(a1), "r"(a2), "r"(a3), "l"(db), "r"(acc));
}

#define TRD(t, i)
namespace km {
#define NSS 6
#define RG "184"
#define RW "136"
#define NFL 2
#define EK 7
#define FK 4
#define LDP 3
#define SND 1
constexpr int O_H = 0;
constexpr int O_MB = 73728;
constexpr int O_VX = 96768;
constexpr int O_KX = 113152;
constexpr int O_QX = 119296;
constexpr int O_VM = 125440;
constexpr int O_KM = 129536;
constexpr int O_QM = 131072;
constexpr int O_SM = 132608;
constexpr int O_ST = 135168;
constexpr int O_OX = 145408;
constexpr int O_WO = 149504;
constexpr int O_OS = O_WO;
constexpr int O_WS = O_WO + 49152;
constexpr int O_RL = 110592;
constexpr int O_BAR = O_WS + NSS * 4096;
constexpr int SMEM = O_BAR + 128 + 1024 + TR_BYTES;
enum { B_X = 0, B_WIN = 16, B_VX = 24, B_SM = 32, B_ST = 40, B_EP = 56 };
#define DLY1 (tune.v[0] + tune.v[4] * w)
#define DLY2 tune.v[1]
#define EARLY tune.v[2]
#define DLYO tune.v[3]
#define DLY0 tune.v[5]
#define DLYX tune.v[6]
#define DLYW tune.v[8]
#define DLYB tune.v[9]
constexpr uint32_t DESC_HI = (1024 >> 4) | (1u << 30);
constexpr float SC = 0.08838834764831845f * 1.4426950408889634f;
}

__global__ void __cluster_dims__(3, 1, 1) __launch_bounds__(384, 1)
k_main(const __nv_bfloat16* __restrict__ x0, const __nv_bfloat16* __restrict__ wqkv, const __nv_bfloat16* __restrict__ wo,
       const __nv_bfloat16* __restrict__ mem0, const __nv_bfloat16* __restrict__ Wq, const __nv_bfloat16* __restrict__ Wk,
       const __nv_bfloat16* __restrict__ Wv, const __nv_bfloat16* __restrict__ Wo, const Tune tune) {
    using namespace km;
    extern __shared__ unsigned char smem_raw[];
    const uint32_t sb = (smem_u32(smem_raw) + 1023) & ~1023u;
    const int tid = threadIdx.x, lane = tid & 31, warp = __shfl_sync(~0u, tid >> 5, 0);
    uint32_t l16 = __shfl_sync(~0u, lane * 16, lane);
#define OPQ() asm volatile("" : "+r"(l16))
    const int b = blockIdx.x, h = b / 3, r = b % 3;
    const int nq = r == 2 ? 2 : 3;
    const uint32_t bar = sb + O_BAR;
    asm volatile("griddepcontrol.launch_dependents;");
    const uint32_t t_start = clk();
    if (warp == 0 && b < 72) {
        if (lane == 0) { mbar_init(bar + 96, 1); fence_async_smem(); mbar_expect(bar + 96, 8 * 3456, true); }
        __syncwarp();
        if (lane < 8) asm volatile("cp.async.bulk.shared::cluster.global.mbarrier::complete_tx::bytes [%0], [%1], 3456, [%2];" :: "r"(sb + O_RL + lane * 3472), "l"(wqkv + (b * 8 + lane) * 1728), "r"(bar + 96) : "memory");
    }
    if (tid == 352) {
        prefetch_l2(x0 + b * (2 * DM), 2 * 1152); prefetch_l2(wo + b * (6 * DM), 6 * 1152);
    }
    if (tid == 320) sts32(bar + 64, ldg32(&g_epoch));
#define EP lds32(bar + 64)
    TR_INIT(bar + 128);
    TRG(79, 0);
    uint32_t roff0, roff1;
    {
        uint32_t y0, y1;
        asm("mapa.shared::cluster.u32 %0, %1, %2;" : "=r"(y0) : "r"(sb), "r"((r + 1) % 3));
        asm("mapa.shared::cluster.u32 %0, %1, %2;" : "=r"(y1) : "r"(sb), "r"((r + 2) % 3));
        roff0 = y0 - sb; roff1 = y1 - sb;
    }
#define IDENT (((l16 >> 7) == ((l16 >> 4) & 3) ? 0x3f80u : 0u) << ((l16 >> 2) & 16))
#define LSWAP ((l16 & 0x70) | ((l16 & 0x80) << 1) | ((l16 & 0x100) >> 1))
    const uint32_t nv_remote = 8 - (8 - 2 * nq);

    auto fetch_tile = [&](int u) {
        fence_async_global();
        TRG(u, 0);
        const bool a0 = u < NSEG, a1 = u >= LAG;
        mbar_expect(bar + B_X, ((int)a0 + (int)a1) * 36864, l16 == 0);
        const uint32_t off = r * 24576 + (l16 << 9) + (a0 ? 0 : 4096);
        asm volatile("{.reg .pred p; setp.lt.u32 p, %5, %6;\n"
            "@p cp.async.bulk.shared::cluster.global.mbarrier::complete_tx::bytes.multicast::cluster [%0], [%1], %4, [%2], %3;}"
            :: "r"(sb + O_H + off), "l"(reinterpret_cast<const char*>(g_xt + u * 4608) + off), "r"(bar + B_X), "h"((uint16_t)7),
               "r"(a0 && a1 ? 24576 : 4096), "r"(l16), "r"(a0 && a1 ? 16 : 48) : "memory");
    };

    int warp_ = warp;
    asm volatile("" : "+r"(warp_));
    if (warp_ < 8) {
        const int ci = tid & 15, slot = ci >> 1, d0 = tid >> 4;
        const __nv_bfloat16* src = slot < nq ? Wq + (3 * r + slot) * 16 : slot < 2 * nq ? Wk + (3 * r + slot - nq) * 16 : Wv + (2 * r + slot - 2 * nq) * 16;
        src += h * 128 + (ci & 1) * 8 + d0 * 4096;
        if (b < 72) {
            bar_sync(10, 256);
            mbar_wait(bar + 96, 0);
            TR1(4);
#pragma unroll 2
            for (int ag = tid >> 3; ag < 231; ag += 32) {
                const int a = ag / 21, gr = ag % 21, tl = gr >= 18;
                const int head = 3 * a + (tl ? 0 : (gr % 6) >> 1), nw = tl ? min(3, 32 - head) : head < 32 ? 4 : 0;
                const uint32_t p = sb + O_RL + (tid & 7) * 3472 + (tl ? gr - 18 : gr / 6) * 1152 + head * 36 + (tl ? 32 : (gr & 1) * 16), step = tl ? 36 : 4;
                uint32_t v[4];
#pragma unroll
                for (int i = 0; i < 4; i++) { v[i] = lds32(p + i * step); if (i >= nw) v[i] = 0; }
                stg128(g_wa + ((a * 9 + (b >> 3)) * 21 + gr) * 64 + (b & 7) * 8 + (tid & 7), v[0], v[1], v[2], v[3]);
            }
        }
        {
            bar_arrive(15, 288);
            TR1(5);
            delay_until(t_start, DLY0);
            uint32_t dst = sb + d0 * 256 + ((ci ^ (d0 & 7)) << 4);
#pragma unroll 1
            for (int q = 0; q < 12; q++, dst += 12288, src += 3 * 65536) {
#pragma unroll
                for (int i = 0; i < 3; i++) cp16(dst + i * 4096, src + i * 65536);
                cp_commit();
                cp_wait<NFL - 1>();
                if (q == 7) bar_sync(10, 256);
            }
            cp_wait_all();
            bar_sync(10, 256);
        }
        TR1(1);
    }
    if (warp < 8) {
        asm volatile("setmaxnreg.inc.sync.aligned.u32 " RG ";");
        constexpr int SSP = 36 / NSS;
#define IS_SS(kk) ((kk) % SSP == 3)
#define AI(kk) (4 * ((kk) - ((kk) + SSP - 4) / SSP))
        uint32_t a[144 - 4 * NSS];
        {
            const int mi = lane >> 3;
            const uint32_t ad = sb + ((mi >> 1) * 8 + (lane & 7)) * 256 + (((warp * 2 + (mi & 1)) ^ (lane & 7)) << 4);
#pragma unroll
            for (int kk = 0; kk < 36; kk++) {
                const uint4 f = ldsm4t(ad + kk * 4096);
                if (IS_SS(kk)) {
                    const uint32_t o0 = sb + O_WS + (kk / SSP) * 4096 + warp * 512 + lane * 4;
                    sts32(o0, f.x); sts32(o0 + 256, f.y); sts32(o0 + 128, f.z); sts32(o0 + 384, f.w);
                } else { a[AI(kk)] = f.x; a[AI(kk) + 1] = f.y; a[AI(kk) + 2] = f.z; a[AI(kk) + 3] = f.w; }
            }
            TR1(2);
            bar_sync(9, 384);
#pragma unroll
            for (int i = 0; i < 9; i++) sts128(sb + O_H + i * 8192 + 4096 + tid * 16, 0, 0, 0, 0);
#pragma unroll
            for (int i = 0; i < 8; i++) if (i * 256 + tid < (O_OX - O_KX) / 16) sts128(sb + O_KX + i * 4096 + tid * 16, 0, 0, 0, 0);
            fence_async_smem();
            cluster_sync();
        }
        TR1(3);
        const int kind = warp < nq ? 0 : warp < 2 * nq ? 1 : 2;
        const int sl = kind == 0 ? warp : kind == 1 ? warp - nq : 2 * r + warp - 2 * nq;
        const uint32_t adX0 = sb + (kind == 0 ? O_QX : kind == 1 ? O_KX : O_VX) + sl * 2048;
        const uint32_t adM0 = sb + (kind == 0 ? O_QM : kind == 1 ? O_KM : O_VM) + sl * 512;
        const uint32_t hlo = (((sb + O_H) >> 4) & 0x3fff) | (1u << 16);
        const uint32_t mlo = (((sb + O_MB) >> 4) & 0x3fff) | (16u << 16);
        const uint32_t wlo = (((sb + O_WS + (warp >> 2) * 2048) >> 4) & 0x3fff) | (8u << 16);
        const int L = (warp >> 1) & 1, qh = warp & 1;
        const uint32_t st = sb + O_ST + warp * 1280;

#pragma unroll 1
        for (int t = -1;; t++) {
            TR_ON(t);
            OPQ();
            const uint32_t adX = adX0 + l16, adM = adM0 + l16, l8 = l16 >> 1;
            const uint32_t lq = LSWAP;
            if (t >= 0) {
                float d0[8], d1[8];
                {
#pragma unroll
                    for (int G = 0; G < 3; G++) {
                        if (warp < 4) bar_sync(1 + G, 160); else bar_sync(12 + G, 160);
                        if (G == 0) wg_fence();
#pragma unroll
                        for (int q = 0; q < 12; q++) {
                            const int kk = 12 * G + q;
                            const uint64_t db = mkdesc(mlo + kk * 32, 8);
                            if (IS_SS(kk)) wgmma_ss16t((kk & 1) ? d1 : d0, mkdesc(wlo + (kk / SSP) * 256, 16), db, 1);
                            else wgmma_rs16t((kk & 1) ? d1 : d0, a[AI(kk)], a[AI(kk) + 1], a[AI(kk) + 2], a[AI(kk) + 3], db, kk >= 2);
                            if (kk == 0) TR(0);
                        }
                    }
                    wg_commit();
                }
#define PM(i) pk(d0[2 * (i)] + d1[2 * (i)], d0[2 * (i) + 1] + d1[2 * (i) + 1])
                if (warp >= 4) {
                    wg_wait<0>();
                    TR(1);
                    const uint32_t p0 = PM(0), p1 = PM(1), p2 = PM(2), p3 = PM(3);
                    if (kind == 2) {
                        sts128(adM, p0, p1, p2, p3);
                        bar_arrive(4, 384);
                        sta128(adM + roff0, p0, p1, p2, p3, bar + B_SM + roff0);
                        sta128(adM + roff1, p0, p1, p2, p3, bar + B_SM + roff1);
                    } else {
                        stsm4t(adM, p0, p1, p2, p3);
                        bar_arrive(4, 384);
                    }
                } else {
                    uint4 q[3], k[3][2];
                    mbar_wait(bar + B_EP, t & 1);
#pragma unroll
                    for (int m = 0; m < LDP; m++) {
                        q[m] = ldsm4(sb + O_QX + m * 2048 + warp * 512 + lq);
                        k[m][0] = ldsm4(sb + O_KX + m * 2048 + L * 1024 + l16); k[m][1] = ldsm4(sb + O_KX + m * 2048 + L * 1024 + 512 + l16);
                    }
                    wg_wait<0>();
                    TR(1);
                    stsm4t(adM, PM(0), PM(1), PM(2), PM(3));
                    bar_arrive(4, 384);
                    sched_fence(gridDim.y, 6);
#pragma unroll
                    for (int m = LDP; m < 3; m++) {
                        q[m] = ldsm4(sb + O_QX + m * 2048 + warp * 512 + lq);
                        k[m][0] = ldsm4(sb + O_KX + m * 2048 + L * 1024 + l16); k[m][1] = ldsm4(sb + O_KX + m * 2048 + L * 1024 + 512 + l16);
                    }
                    float s[5][4];
                    {
                        float y[4] = {0, 0, 0, 0};
#pragma unroll
                        for (int n = 0; n < 5; n++) s[n][0] = s[n][1] = s[n][2] = s[n][3] = 0.f;
#pragma unroll
                        for (int m = 0; m < 3; m++) {
                            mma16(s[0], q[m].x, q[m].y, q[m].z, q[m].w, k[m][0].x, k[m][0].y); mma16(s[1], q[m].x, q[m].y, q[m].z, q[m].w, k[m][0].z, k[m][0].w);
                            mma16(s[2], q[m].x, q[m].y, q[m].z, q[m].w, k[m][1].x, k[m][1].y); mma16(s[3], q[m].x, q[m].y, q[m].z, q[m].w, k[m][1].z, k[m][1].w);
                        }
                        auto send = [&]() {
                            uint32_t w0 = pk(s[0][0], s[0][1]), w1 = pk(s[0][2], s[0][3]), w2 = pk(s[1][0], s[1][1]), w3 = pk(s[1][2], s[1][3]);
                            sta128(st + l16 + 5120 + roff0, w0, w1, w2, w3, bar + B_ST + roff0);
                            sta128(st + l16 + roff1, w0, w1, w2, w3, bar + B_ST + roff1);
                            w0 = pk(s[2][0], s[2][1]); w1 = pk(s[2][2], s[2][3]); w2 = pk(s[3][0], s[3][1]); w3 = pk(s[3][2], s[3][3]);
                            sta128p(st + l16 + 5120 + 512 + roff0, w0, w1, w2, w3, bar + B_ST + roff0, qh);
                            sta128p(st + l16 + 512 + roff1, w0, w1, w2, w3, bar + B_ST + roff1, qh);
                        };
                        sched_fence(gridDim.y, 7);
                        bar_sync(5, 256);
                        const uint4 k01 = ldsm4(sb + O_KM + L * 256 + l16 + (l16 & 256));
                        const uint2 k2 = ldsm2(sb + O_KM + 1024 + L * 256 + l16);
                        if (SND == 0) send();
                        mma16(s[4], q[0].x, q[0].y, q[0].z, q[0].w, k01.x, k01.y);
                        mma16(y, q[1].x, q[1].y, q[1].z, q[1].w, k01.z, k01.w);
                        mma16(s[4], q[2].x, q[2].y, q[2].z, q[2].w, k2.x, k2.y);
#pragma unroll
                        for (int j = 0; j < 4; j++) s[4][j] += y[j];
                        const uint32_t w0 = pk(s[4][0], s[4][1]), w1 = pk(s[4][2], s[4][3]);
                        sta64(st + l8 + 5120 + 1024 + roff0, w0, w1, bar + B_ST + roff0);
                        sta64(st + l8 + 1024 + roff1, w0, w1, bar + B_ST + roff1);
                        if (SND == 1) send();
                        TR(2);
                        const int lim = 16 * qh + (int)(l16 >> 6) - (int)((l16 >> 3) & 6);
#pragma unroll
                        for (int n = 0; n < 4; n++)
#pragma unroll
                            for (int j = 0; j < 4; j++) if (!(n == 0 && j >= 2) && 8 * (n - (j >> 1)) + (j & 1) > lim) s[n][j] = -1e30f;
#pragma unroll
                        for (int n = 0; n < 4; n++) asm volatile("" : "+f"(s[n][0]), "+f"(s[n][1]), "+f"(s[n][2]), "+f"(s[n][3]));
                    }
                    uint4 v0[3], v1[3]; uint2 vm[3];
                    const uint32_t vad = sb + O_VX + 3 * r * 2048 + L * 1024 + l16;
#pragma unroll
                    for (int m = 0; m < 3; m++) v0[m] = lds128(vad + m * 2048);
                    const uint32_t otag = ring_tag(t, EP);
                    uint32_t ident = IDENT;
                    asm volatile("" : "+r"(ident));
                    mbar_wait(bar + B_SM, t & 1);
                    mbar_wait(bar + B_ST, t & 1);
                    TR(3);
                    float mx0, mx1;
                    {
                        const uint4 u = lds128(st + l16), v = lds128(st + 512 + l16); const uint2 w = lds64(st + 1024 + l8);
                        const uint4 x = lds128(st + 5120 + l16), y = lds128(st + 5120 + 512 + l16); const uint2 z = lds64(st + 5120 + 1024 + l8);
                        mma8(s[0], u.x, u.y, ident); mma8(s[1], u.z, u.w, ident); mma8(s[2], v.x, v.y, ident); mma8(s[3], v.z, v.w, ident); mma8(s[4], w.x, w.y, ident);
                        mma8(s[0], x.x, x.y, ident); mma8(s[1], x.z, x.w, ident); mma8(s[2], y.x, y.y, ident); mma8(s[3], y.z, y.w, ident); mma8(s[4], z.x, z.y, ident);
                        mx0 = fmaxf(fmaxf(fmaxf(s[0][0], s[0][1]), fmaxf(s[1][0], s[1][1])), fmaxf(fmaxf(s[2][0], s[2][1]), fmaxf(s[3][0], s[3][1])));
                        mx1 = fmaxf(fmaxf(fmaxf(s[0][2], s[0][3]), fmaxf(s[1][2], s[1][3])), fmaxf(fmaxf(s[2][2], s[2][3]), fmaxf(s[3][2], s[3][3])));
                        mx0 = fmaxf(mx0, fmaxf(s[4][0], s[4][1])); mx1 = fmaxf(mx1, fmaxf(s[4][2], s[4][3]));
                    }
#pragma unroll
                    for (int o = 1; o < 4; o <<= 1) { const float2 z = shfl2(mx0, mx1, o); mx0 = fmaxf(mx0, z.x); mx1 = fmaxf(mx1, z.y); }
                    mx0 *= -SC; mx1 *= -SC;
                    float l[4] = {0, 0, 0, 0};
                    uint32_t p[10];
#pragma unroll
                    for (int n = 0; n < 5; n++) {
                        const float e0 = ex2(fmaf(s[n][0], SC, mx0)), e1 = ex2(fmaf(s[n][1], SC, mx0));
                        const float e2 = ex2(fmaf(s[n][2], SC, mx1)), e3 = ex2(fmaf(s[n][3], SC, mx1));
                        p[2 * n] = pk(e0, e1); p[2 * n + 1] = pk(e2, e3);
                        mma8(l, p[2 * n], p[2 * n + 1], 0x3f803f80);
                    }
#pragma unroll
                    for (int m = 0; m < 3; m++) vm[m] = lds64(sb + O_VM + (3 * r + m) * 512 + l16 + L * 8);
                    sched_fence(gridDim.y, 5);
                    const float l0 = rcp(l[0]), l1 = rcp(l[2]);
                    float o[6][4];
#pragma unroll
                    for (int m = 0; m < 6; m++) o[m][0] = o[m][1] = o[m][2] = o[m][3] = 0.f;
#pragma unroll
                    for (int m = 0; m < 3; m++) { mma8(o[2 * m], p[0], p[1], v0[m].x); mma8(o[2 * m + 1], p[0], p[1], v0[m].y); }
#pragma unroll
                    for (int m = 0; m < 3; m++) { mma8(o[2 * m], p[2], p[3], v0[m].z); mma8(o[2 * m + 1], p[2], p[3], v0[m].w); v1[m] = lds128(vad + m * 2048 + 512); }
#pragma unroll
                    for (int m = 0; m < 3; m++) { mma8(o[2 * m], p[8], p[9], vm[m].x); mma8(o[2 * m + 1], p[8], p[9], vm[m].y); }
#pragma unroll
                    for (int m = 0; m < 3; m++) { mma8(o[2 * m], p[4], p[5], v1[m].x); mma8(o[2 * m + 1], p[4], p[5], v1[m].y); }
#pragma unroll
                    for (int m = 0; m < 3; m++) { mma8(o[2 * m], p[6], p[7], v1[m].z); mma8(o[2 * m + 1], p[6], p[7], v1[m].w); }
                    sched_fence(gridDim.y, 8);
                    if (t + 1 < NT) bar_arrive(11, 384);
#pragma unroll
                    for (int m = 0; m < 3; m++)
                        sts128(sb + O_OS + warp * 512 + m * 2048 + l16, (pk(o[2 * m][0] * l0, o[2 * m][1] * l0) & ~1u) | otag, pk(o[2 * m][2] * l1, o[2 * m][3] * l1),
                               pk(o[2 * m + 1][0] * l0, o[2 * m + 1][1] * l0), pk(o[2 * m + 1][2] * l1, o[2 * m + 1][3] * l1));
                    TR(4);
                }
            }
            if (t + 1 >= NT) break;
            {
                float d[32];
                if (warp < 4) { if (t < 0) mbar_wait(bar + B_X, 0); bar_sync(7, 256); }
                else {
                    if (warp == 7) {
                        if (t >= 0) { mbar_wait(bar + B_EP, t & 1); mbar_wait(bar + B_VX, t & 1); }
                        if (__shfl_sync(~0u, lds_acq(bar + 8), 0) != t + 1) cnt_wait(g_cnt + (C_X + t + 1) * 8, 64 * (EP + 1));
                        else if (DLYX) pause(DLYX);
                        fetch_tile(t + 1);
                        TR(2);
                    }
                    mbar_wait(bar + B_X, (t + 1) & 1);
                    TR(3);
                    if (t >= 0) bar_sync(11, 384);
                }
                wg_fence();
                TR(6);
#pragma unroll
                for (int kk = 0; kk < 36; kk++) {
                    const uint64_t db = mkdesc(hlo + ((kk >> 2) * 8192 + (kk & 3) * 32) / 16, DESC_HI);
                    if (IS_SS(kk)) wgmma_ss64(d, mkdesc(wlo + (kk / SSP) * 256, 16), db, 1);
                    else wgmma_rs64(d, a[AI(kk)], a[AI(kk) + 1], a[AI(kk) + 2], a[AI(kk) + 3], db, kk > 0);
                }
                wg_commit();
                TR(5);
                mbar_wait(bar + B_WIN, (t + 1) & 1);
                wg_wait<0>();
                TR(7);
                uint32_t p[16];
#pragma unroll
                for (int u = 0; u < 16; u++) p[u] = pk(d[2 * u], d[2 * u + 1]);
                if (kind == 2) {
#pragma unroll
                    for (int u = 0; u < 4; u++) sts128(adX + u * 512, p[4 * u], p[4 * u + 1], p[4 * u + 2], p[4 * u + 3]);
                } else {
#pragma unroll
                    for (int u = 0; u < 4; u++) stsm4t(adX + u * 512, p[4 * u], p[4 * u + 1], p[4 * u + 2], p[4 * u + 3]);
                }
                __syncwarp();
                asm volatile("{.reg .pred p; setp.eq.u32 p, %1, 0; @p mbarrier.arrive.shared.b64 _, [%0];}" :: "r"(bar + B_EP), "r"(l16) : "memory");
                TR(8);
            }
        }
        if (warp < 4) bar_arrive(7, 160);
        cluster_sync();
    } else {
        asm volatile("setmaxnreg.dec.sync.aligned.u32 " RW ";");
        const int w = warp - 8, t2 = tid - 256;
        if (t2 == 0) {
            mbar_init(bar + B_X, 1); sts32(bar + 8, ~0u); mbar_init(bar + B_WIN, 3);
            mbar_init(bar + B_VX, 1); mbar_init(bar + B_SM, 1); mbar_init(bar + B_ST, 1); mbar_init(bar + B_EP, 8);
            asm volatile("fence.mbarrier_init.release.cluster;" ::: "memory");
        }
        char* const ex = reinterpret_cast<char*>((reinterpret_cast<uintptr_t>(g_ex) + 0x1fffff) & ~(uintptr_t)0x1fffff);
        char* rbase = ex; uint32_t side = 0;
        {
            uint32_t m0[5][4];
#pragma unroll
            for (int i = 0; i < 5; i++) {
                const unsigned short* m = reinterpret_cast<const unsigned short*>(mem0) + min(i * 128 + t2, DM - 1);
#pragma unroll
                for (int j = 0; j < 4; j++) m0[i][j] = m[2 * j * DM] | (m[(2 * j + 1) * DM] << 16);
            }
            if (w == 3) { bar_sync(15, 288); cnt_add(g_cnt + C_W * 8, lane); TR1(1); }
            else {
                if (w < 2) {
                    unsigned* pp = reinterpret_cast<unsigned*>(ex + inbox_off(b) + 16384 + w * 4096 + 2048);
                    uint32_t best = ~0u, v = 0;
                    if (lane == 0) {
#pragma unroll 1
                        for (int i = 0; i < 5; i++) {
                            const uint32_t c0 = clk();
                            v = atomicAdd(pp + (v >> 31), 0);
                            asm volatile("" :: "r"(v) : "memory");
                            sts32(bar + 80, v);
                            best = min(best, clk() - c0);
                        }
                        sts32(bar + 72 + w * 4, best);
                    }
                }
                bar_sync(8, 96);
                const uint32_t xs = lds32(bar + 76) < lds32(bar + 72), ep = EP;
                side = xs ^ page_par(inbox_off(b));
                rbase = ex + inbox_off(b) + xs * 4096;
                const uint32_t inv = (ep * (NT - 1)) & 1;
#pragma unroll
                for (int i = 0; i < 4; i++) stg128(rbase + (w == 2 ? 16384 : w * 2048) + i * 512 + lane * 16, inv, 0, 0, 0);
                __threadfence();
                bar_sync(8, 96);
                if (t2 == 0) stg_word(g_side + b, (ep + 1) * 2 + xs, true);
                TR1(4);
            }
            delay_until(t_start, DLYW);
#pragma unroll 4
            for (int i = t2; i < 128 * 24; i += 128) {
                const int e = (i >> 3) & 127, G = i >> 10, q = i & 7;
                cp16(sb + O_WO + G * 16384 + e * 128 + ((q ^ (e & 7) ^ ((h >> 1) & 1)) << 4), Wo + (size_t)(h * 128 + e) * DM + G * 192 + r * 64 + q * 8);
            }
            bar_sync(9, 384);
#pragma unroll
            for (int i = 0; i < 5; i++) {
                const int k = min(i * 128 + t2, DM - 1);
                const uint32_t ad = sb + O_MB + (k >> 3) * 256 + (k & 7) * 16;
                sts128(ad, m0[i][0], m0[i][1], m0[i][2], m0[i][3]); sts128(ad + 128, m0[i][0], m0[i][1], m0[i][2], m0[i][3]);
            }
            fence_async_smem();
        }
        auto arm = [&]() {
            const uint32_t ln = l16 >> 4;
            mbar_expect(bar + B_VX + (ln & 3) * 8, ln == 0 ? nv_remote * 2048 : ln == 1 ? nv_remote * 512 + 2560 : 8192, ln < 3);
        };
        if (w == 3) arm();
        cluster_sync();
        TR1(3);
        const int L = w >> 1, hf = w & 1;
        const uint32_t rd = hf ? roff1 : roff0;
        const uint32_t rzero = gridDim.y + 100;
#define WOAD (sb + O_WO + ((l16 & 0x100) << 2) + ((l16 & 0x70) << 3) + (((w * 32) | ((l16 >> 3) & 16)) ^ (l16 & 0x70)))

        auto store_o = [&](int u) {
            asm volatile("{.reg .pred p; setp.eq.u32 p, %3, 0;\n"
                "@p cp.async.bulk.global.shared::cta.bulk_group [%0], [%1], %2;\n cp.async.bulk.commit_group;}"
                :: "l"(g_o + ((u & (RING - 1)) * 256 + h * 8 + 3 * r) * 128), "r"(sb + O_OS), "r"(nq * 2048), "r"(l16) : "memory");
            cnt_hint(g_cnt + (C_O + u * 8 + (h >> 2)) * 8, l16);
            TRG(u, 2);
        };
        bar_arrive(7, 256);
        if (w < 3) {
            bar_arrive(1 + w, 160); bar_arrive(12 + w, 160);
        } else {
            mbar_arrive_all3(bar + B_WIN, l16 >> 4);

        }
        cp_wait_all();
        bar_sync(6, 128);
        uint32_t poff;
        {
            const int rb = r * 32 + w * 8 + (lane >> 2);
            const uint32_t want = EP + 1;
            uint32_t v;
            for (int n = 0; __any_sync(~0u, ((v = ldg_word(g_side + rb)) >> 1) != want); n++) fault_if(n > POLL_LIMIT, n);
            __threadfence();
            poff = inbox_off(rb) + (v & 1) * 4096 + h * 64 + (lane & 3) * 16;
        }
        side = __shfl_sync(~0u, side, 0);
        const uint32_t roff = __shfl_sync(~0u, (uint32_t)(rbase - ex), 0) + (w == 2 ? 16384 : (w & 1) * 2048);
        uint4 a0[8];
#pragma unroll
        for (int kk = 0; kk < 8; kk++) a0[kk] = ldsm4t(WOAD + kk * 2048);
#pragma unroll 1
        for (int t = 0;; t++) {
            TR_ON(t);
            OPQ();
            mbar_wait(bar + B_EP, t & 1);
            if (w == 3) {
                fence_async_smem();
                const uint32_t ad = sb + O_VX + r * 4096;
                asm volatile("{.reg .pred p; setp.eq.u32 p, %5, 0;\n"
                    "@p cp.async.bulk.shared::cluster.shared::cta.mbarrier::complete_tx::bytes [%0], [%2], %6, [%3];\n"
                    "@p cp.async.bulk.shared::cluster.shared::cta.mbarrier::complete_tx::bytes [%1], [%2], %6, [%4];}"
                    :: "r"(ad + roff0), "r"(ad + roff1), "r"(ad), "r"(bar + B_VX + roff0), "r"(bar + B_VX + roff1), "r"(l16), "r"(16384 - 4096 * nq) : "memory");
                TR(7);
            }
            uint4 kx[3][2], vx[4][2];
            const uint32_t lp = LSWAP;
#pragma unroll
            for (int m = 0; m < 3; m++) {
                kx[m][0] = ldsm4(sb + O_KX + m * 2048 + L * 1024 + lp);
                kx[m][1] = ldsm4(sb + O_KX + m * 2048 + L * 1024 + 512 + lp);
            }
            if (w == 3) asm volatile("cp.async.bulk.wait_group.read 0;" ::: "memory");
            mbar_wait(bar + B_VX, t & 1);
            TR(0);
            bar_sync(4, 384);
            float s0[4] = {0, 0, 0, 0}, s1[4] = {0, 0, 0, 0}, sm[4] = {0, 0, 0, 0};
            {
                const uint4 q01 = ldsm4(sb + O_QM + L * 256 + l16 + (l16 & 256));
                const uint2 q2 = ldsm2(sb + O_QM + 1024 + L * 256 + l16);
                uint4 km_[3];
#pragma unroll
                for (int m = 0; m < 3; m++) km_[m] = ldsm4(sb + O_KM + m * 512 + (lp ^ (L << 8)));
                mma16(s0, kx[0][0].x, kx[0][0].y, kx[0][0].z, kx[0][0].w, q01.x, q01.y);
                mma16(s1, kx[0][1].x, kx[0][1].y, kx[0][1].z, kx[0][1].w, q01.x, q01.y);
                mma16(sm, km_[0].x, km_[0].y, km_[0].z, km_[0].w, q01.x, q01.y);
                mma16(s0, kx[1][0].x, kx[1][0].y, kx[1][0].z, kx[1][0].w, q01.z, q01.w);
                mma16(s1, kx[1][1].x, kx[1][1].y, kx[1][1].z, kx[1][1].w, q01.z, q01.w);
                mma16(sm, km_[1].x, km_[1].y, km_[1].z, km_[1].w, q01.z, q01.w);
                bar_arrive(5 + (__float_as_uint(s0[0]) & (rzero - 101)), 256);
                mma16(s0, kx[2][0].x, kx[2][0].y, kx[2][0].z, kx[2][0].w, q2.x, q2.y);
                mma16(s1, kx[2][1].x, kx[2][1].y, kx[2][1].z, kx[2][1].w, q2.x, q2.y);
                mma16(sm, km_[2].x, km_[2].y, km_[2].z, km_[2].w, q2.x, q2.y);
                const uint32_t ad = sb + O_SM + (1 - hf) * 1280 + L * 640 + rd;
                sta128(ad + l16, pk(s0[0], s0[1]), pk(s0[2], s0[3]), pk(s1[0], s1[1]), pk(s1[2], s1[3]), bar + B_SM + rd);
                sta32(ad + 512 + (l16 >> 2), pk(sm[0], sm[1]), bar + B_SM + rd);
            }
            TR(1);
            if (t + 1 == NT) break;
#pragma unroll
            for (int m = 0; m < 8; m++) vx[m >> 1][m & 1] = lds128(sb + O_VX + (hf * 4 + (m >> 1)) * 2048 + L * 1024 + (m & 1) * 512 + l16);
            const uint32_t tag = (t + EP * (NT - 1) + 1) & 1;
            uint32_t ident = IDENT;
            asm volatile("" : "+r"(ident));
            mbar_wait(bar + B_SM, t & 1);
            TR(2);
            {
                const uint32_t ad = sb + O_SM + L * 640;
                const uint4 u = lds128(ad + l16), v = lds128(ad + 1280 + l16);
                const uint32_t x = lds32(ad + 512 + (l16 >> 2)), y = lds32(ad + 1280 + 512 + (l16 >> 2));
                mma8(s0, u.x, u.y, ident); mma8(s1, u.z, u.w, ident); mma8(s0, v.x, v.y, ident); mma8(s1, v.z, v.w, ident);
                sm[0] += bf_lo(x) + bf_lo(y); sm[1] += bf_hi(x) + bf_hi(y);
            }
            uint2 vm[4];
#pragma unroll
            for (int m = 0; m < 4; m++) vm[m] = lds64(sb + O_VM + (hf * 4 + m) * 512 + l16 + L * 8);
            float mx0 = fmaxf(fmaxf(fmaxf(s0[0], s0[2]), fmaxf(s1[0], s1[2])), sm[0]);
            float mx1 = fmaxf(fmaxf(fmaxf(s0[1], s0[3]), fmaxf(s1[1], s1[3])), sm[1]);
#pragma unroll
            for (int o = 4; o < 32; o <<= 1) { mx0 = fmaxf(mx0, __shfl_xor_sync(~0u, mx0, o)); mx1 = fmaxf(mx1, __shfl_xor_sync(~0u, mx1, o)); }
            mx0 *= -SC; mx1 *= -SC;
            s0[0] = ex2(fmaf(s0[0], SC, mx0)); s0[1] = ex2(fmaf(s0[1], SC, mx1));
            s0[2] = ex2(fmaf(s0[2], SC, mx0)); s0[3] = ex2(fmaf(s0[3], SC, mx1));
            const uint32_t pb0 = movm(pk(s0[0], s0[1])), pb1 = movm(pk(s0[2], s0[3]));
            s1[0] = ex2(fmaf(s1[0], SC, mx0)); s1[1] = ex2(fmaf(s1[1], SC, mx1));
            s1[2] = ex2(fmaf(s1[2], SC, mx0)); s1[3] = ex2(fmaf(s1[3], SC, mx1));
            const uint32_t pb2 = movm(pk(s1[0], s1[1])), pb3 = movm(pk(s1[2], s1[3]));
            sm[0] = ex2(fmaf(sm[0], SC, mx0)); sm[1] = ex2(fmaf(sm[1], SC, mx1));
            const uint32_t pm = movm(pk(sm[0], sm[1]));
            float o[4][4], l[4] = {0, 0, 0, 0};
            const uint32_t one = 0x3f803f80;
            mma8(l, one, one, pb0); mma8(l, one, one, pb1);
#pragma unroll
            for (int m = 0; m < 4; m++) { o[m][0] = o[m][1] = o[m][2] = o[m][3] = 0.f; mma16(o[m], vx[m][0].x, vx[m][0].y, vx[m][0].z, vx[m][0].w, pb0, pb1); }
            mma8(l, one, one, pb2); mma8(l, one, one, pb3);
#pragma unroll
            for (int m = 0; m < 4; m++) mma16(o[m], vx[m][1].x, vx[m][1].y, vx[m][1].z, vx[m][1].w, pb2, pb3);
            mma8(l, one, one, pm);
#pragma unroll
            for (int m = 0; m < 4; m++) mma8(o[m], vm[m].x, vm[m].y, pm);
            const float l0 = rcp(l[0]), l1 = rcp(l[1]);
#pragma unroll
            for (int m = 0; m < 4; m += 2)
                stsm4t(sb + O_OX + (hf * 4 + m) * 512 + (L ^ ((h >> 2) & 1)) * 256   + ((l16 & 0x100) << 1) + (l16 & 0xf0),
                       pk(o[m][0] * l0, o[m][1] * l1), pk(o[m][2] * l0, o[m][3] * l1), pk(o[m + 1][0] * l0, o[m + 1][1] * l1), pk(o[m + 1][2] * l0, o[m + 1][3] * l1));
            TR(3);
            char* const pdst = ex + poff;
            const char* const rsrc = ex + roff + l16;
            uint4 v[4] = {};
            bar_sync(6, 128);
            {
                uint4 bo[8], a1[8], z;
                const uint32_t wad = WOAD;
#pragma unroll
                for (int kk = 0; kk < 8; kk++) bo[kk] = ldsm4(sb + O_OX + kk * 512 + l16);
#pragma unroll
                for (int G = 0; G < 3; G++) {
                    float e[4][4];
#pragma unroll
                    for (int q = 0; q < 4; q++) e[q][0] = e[q][1] = e[q][2] = e[q][3] = 0.f;
#pragma unroll
                    for (int kk = 0; kk < 8; kk++) {
                        const uint4 f = G == 0 ? a0[kk] : a1[kk];
                        mma16(e[(kk & 1) * 2], f.x, f.y, f.z, f.w, bo[kk].x, bo[kk].y);
                        mma16(e[(kk & 1) * 2 + 1], f.x, f.y, f.z, f.w, bo[kk].z, bo[kk].w);
                        if (G == 2 && kk == EK) {
#pragma unroll
                            for (int i = 0; i < 4; i++) { v[i].x = ~tag; ldg_pkt_if(v[i], rsrc + i * 512, w < EARLY); }
                            sched_fence(rzero, 5);
                            bar_arrive(11, 384);
                        }
                        if (G == 1) a1[kk] = ldsm4t(wad + 32768 + kk * 2048);
                        if (G == 0 && kk == FK) {
                            sched_fence(rzero, 2);
#pragma unroll
                            for (int j = 0; j < 8; j++) a1[j] = ldsm4t(wad + 16384 + j * 2048);
                        }
                    }
                    if (G > 0) asm volatile("{.reg .pred p; setp.eq.u32 p, %5, 0; @p st.shared.v4.u32 [%0], {%1,%2,%3,%4};}" :: "r"(__float_as_uint(e[0][0])), "r"(z.x), "r"(z.y), "r"(z.z), "r"(z.w), "r"(rzero));
                    z = make_uint4((pk(e[0][0] + e[2][0], e[0][1] + e[2][1]) & ~1u) | tag, pk(e[0][2] + e[2][2], e[0][3] + e[2][3]),
                                   pk(e[1][0] + e[3][0], e[1][1] + e[3][1]), pk(e[1][2] + e[3][2], e[1][3] + e[3][3]));
                    stg_pkt(pdst + (G == 2 ? 16384 : G * 2048), z.x, z.y, z.z, z.w);
                    if (G == 0) { TR(9); TRD(t, 0); }
                    if (G < 2) sched_fence(rzero, 3 + G);
                }
            }
            TR(4);
            if (w < 3) {
                bar_arrive(7, 256);
                OPQ();
                const uint32_t tagm = tag;
                uint32_t m0v = 0;
                if (t + 1 <= LAG) {
                    const unsigned short* m = reinterpret_cast<const unsigned short*>(mem0) + ((l16 >> 3) & 6) * DM + 192 * w + 16 * (b >> 3) + (b & 7) + ((l16 >> 4) & 8);
                    m0v = m[0] | (m[DM] << 16);
                }
                if (DLY1) pause(DLY1);
                for (int n = 0; __any_sync(~0u, lop_bad(lop_bad(0, v[0].x, v[1].x, tagm), v[2].x, v[3].x, tagm) & 1); n++) {
#pragma unroll
                    for (int i = 0; i < 4; i++) v[i] = ldg_pkt(rsrc + i * 512);
                    fault_if(n > POLL_LIMIT, n);
                }
                TR(5); TRD(t, 1);
                float s[8];
                s[4] = (bf_lo(v[0].z) + bf_lo(v[1].z)) + (bf_lo(v[2].z) + bf_lo(v[3].z)); s[5] = (bf_hi(v[0].z) + bf_hi(v[1].z)) + (bf_hi(v[2].z) + bf_hi(v[3].z));
                s[6] = (bf_lo(v[0].w) + bf_lo(v[1].w)) + (bf_lo(v[2].w) + bf_lo(v[3].w)); s[7] = (bf_hi(v[0].w) + bf_hi(v[1].w)) + (bf_hi(v[2].w) + bf_hi(v[3].w));
                s[2] = (bf_lo(v[0].y) + bf_lo(v[1].y)) + (bf_lo(v[2].y) + bf_lo(v[3].y)); s[3] = (bf_hi(v[0].y) + bf_hi(v[1].y)) + (bf_hi(v[2].y) + bf_hi(v[3].y));
                s[0] = (bf_lo(v[0].x) + bf_lo(v[1].x)) + (bf_lo(v[2].x) + bf_lo(v[3].x)); s[1] = (bf_hi(v[0].x) + bf_hi(v[1].x)) + (bf_hi(v[2].x) + bf_hi(v[3].x));
#pragma unroll
                for (int j = 0; j < 4; j++) s[j] += __shfl_xor_sync(~0u, s[j + 4], 16);
#pragma unroll
                for (int j = 0; j < 2; j++) s[j] += __shfl_xor_sync(~0u, s[j + 2], 8);
#pragma unroll
                for (int j = 0; j < 2; j++) s[j] += __shfl_xor_sync(~0u, s[j], 4);
                char* const mem_w = ex + mem_off(w, 0);
                uint32_t res = t + 1 <= LAG && l16 >= 256 ? m0v : pk(s[0], s[1]);
                if ((l16 & 48) == 0) res = (res & ~1u) | tag;
                char* const pub = mem_w + (mem_off(0, b >> 3) - mem_off(0, 0)) + (b & 7) * 16 + (((l16 & 64) << 6) + ((l16 & 128) << 1) + ((l16 & 256) >> 1) + ((l16 >> 2) & 12));
                stg_word(pub, res, true);
                TR(6); TRD(t, 2);
                pause(DLY2);
                const char* src = mem_w + (side ^ page_par(0x180000)) * 4096 + l16;
                const uint32_t gdst = sb + O_MB + w * 6144 + l16;
                uint4 x[12];
#pragma unroll
                for (int i = 0; i < 12; i++) x[i] = ldg_pkt(src + (mem_off(0, i) - mem_off(0, 0)));
                for (int n = 0;; n++) {
                    uint32_t bad = 0;
#pragma unroll
                    for (int i = 0; i < 12; i += 2) bad = lop_bad(bad, x[i].x, x[i + 1].x, tagm);
                    if (!__any_sync(~0u, bad & 1)) break;
#pragma unroll
                    for (int i = 0; i < 12; i++) ldg_pkt_retry(x[i], src + (mem_off(0, i) - mem_off(0, 0)), tagm);
                    fault_if(n > POLL_LIMIT, n);
                }
#pragma unroll
                for (int i = 0; i < 12; i++) sts128(gdst + i * 512, x[i].x, x[i].y, x[i].z, x[i].w);
                TR(7); TRD(t, 3);
                fence_async_smem();
                bar_arrive(12 + w, 160);
                bar_arrive(1 + w, 160);
                TR(8);
            } else {
                mbar_wait(bar + B_X, (t + 1) & 1);
                bar_sync(7, 256);
                fence_async_smem();
                arm();
                __syncwarp();
                mbar_arrive_all3(bar + B_WIN, l16 >> 4);
                if (DLYO) pause(DLYO);
                store_o(t);
                cnt_poll(g_cnt + (C_X + t + 2) * 8, 64 * (EP + 1), bar + B_EP, (t + 1) & 1, bar + 8, t + 2);
                TR(5);
            }
        }
        if (w == 3) { bar_sync(7, 160); fence_async_smem(); store_o(NT - 1); asm volatile("cp.async.bulk.wait_group 0;" ::: "memory"); }
        cluster_sync();
    }
    TR_DUMP(b);
}

#define VP 12
#define VC 19
#define VG 12
#define HB 3
#define HA 2
#define HW 0
namespace ka {
constexpr int O_WA = 196608;
constexpr int A_KB = 21504;
constexpr int O_RING = 194560;
constexpr int O_BAR = 230400;
constexpr int SMEM = O_BAR + 256 + 1024;
constexpr float SC = 0.23570226039551584f * 1.4426950408889634f;
}

template <int NP, int KB = 4096>
DEVI void row_task(const uint4* res, const uint4* part, uint4* xout, char* img, int pos, int lane, uint32_t tag) {
    const bool on = lane < 24;
    const int ln = on ? lane : 0;
    uint4 rv[3], pv[NP > 0 ? NP * 3 : 1];
#pragma unroll
    for (int i = 0; i < 3; i++) rv[i] = ldg128(res + i * 24 + ln);
#pragma unroll
    for (int i = 0; i < NP * 3; i++) pv[i] = ldg_pkt(part + i * 24 + ln);
    if (NP > 0) validate<NP * 3>(pv, part + ln, 384, tag);
#pragma unroll
    for (int q = 0; q < NP * 3 / 2; q++) {
        const uint4 y = pv[q + NP * 3 / 2];
        pv[q] = make_uint4(add2(pv[q].x, y.x), add2(pv[q].y, y.y), add2(pv[q].z, y.z), add2(pv[q].w, y.w));
    }
    float x[24];
#pragma unroll
    for (int i = 0; i < 3; i++) {
        x[8 * i] = bf_lo(rv[i].x); x[8 * i + 1] = bf_hi(rv[i].x); x[8 * i + 2] = bf_lo(rv[i].y); x[8 * i + 3] = bf_hi(rv[i].y);
        x[8 * i + 4] = bf_lo(rv[i].z); x[8 * i + 5] = bf_hi(rv[i].z); x[8 * i + 6] = bf_lo(rv[i].w); x[8 * i + 7] = bf_hi(rv[i].w);
    }
    if (NP > 0) {
#pragma unroll
        for (int q = 0; q < NP * 3 / 2; q++) {
            const int i = q % 3;
            x[8 * i] += bf_lo(pv[q].x); x[8 * i + 1] += bf_hi(pv[q].x); x[8 * i + 2] += bf_lo(pv[q].y); x[8 * i + 3] += bf_hi(pv[q].y);
            x[8 * i + 4] += bf_lo(pv[q].z); x[8 * i + 5] += bf_hi(pv[q].z); x[8 * i + 6] += bf_lo(pv[q].w); x[8 * i + 7] += bf_hi(pv[q].w);
        }
#pragma unroll
        for (int i = 0; i < 3; i++) {
            uint32_t w[4];
#pragma unroll
            for (int j = 0; j < 4; j++) { w[j] = pk(x[8 * i + 2 * j], x[8 * i + 2 * j + 1]); x[8 * i + 2 * j] = bf_lo(w[j]); x[8 * i + 2 * j + 1] = bf_hi(w[j]); }
            stg128p(xout + i * 24 + ln, w[0], w[1], w[2], w[3], on);
        }
    }
    if (img) {
        const float x0 = __shfl_sync(~0u, x[0], 0);
        float s4[4] = {0, 0, 0, 0}, v4[4] = {0, 0, 0, 0};
#pragma unroll
        for (int j = 0; j < 24; j++) { x[j] -= x0; s4[j & 3] += x[j]; v4[j & 3] = fmaf(x[j], x[j], v4[j & 3]); }
        float s = on ? (s4[0] + s4[1]) + (s4[2] + s4[3]) : 0.f, v = on ? (v4[0] + v4[1]) + (v4[2] + v4[3]) : 0.f;
#pragma unroll
        for (int o = 1; o < 32; o <<= 1) { const float2 z = shfl2(s, v, o); s += z.x; v += z.y; }
        const float mean = s * (1.f / DM);
        const float rs = rsqrtf(fmaxf(fmaf(-mean, mean, v * (1.f / DM)), 0.f) + 1e-5f), sh = -mean * rs;
#pragma unroll
        for (int j = 0; j < 24; j++) x[j] = fmaf(x[j], rs, sh);
        char* dst = img + (ln >> 3) * KB + pos * 128 + (((ln ^ pos) & 7) << 4);
#pragma unroll
        for (int i = 0; i < 3; i++)
            stg128p(dst + i * (3 * KB), pk(x[8 * i], x[8 * i + 1]), pk(x[8 * i + 2], x[8 * i + 3]),
                    pk(x[8 * i + 4], x[8 * i + 5]), pk(x[8 * i + 6], x[8 * i + 7]), on);
    }
}

DEVI void rows_a(const uint4* xin, int f, int i, int lane, uint32_t ep, int warp) {
    for (int u = 0; u < LAG; u++) cnt_hint(g_cnt + (C_X + u + (f ? 0 : NSEG)) * 8, lane);
#pragma unroll 1
    for (int seg = 0; seg < NSEG; seg++) {
        const int j = seg + f * LAGA, u = seg + f * LAG, row = seg * 32 + i;
        hint_wait(g_cnt + (C_WA + j * 4 + f * 2 + (i & 1)) * 8, 24 * (ep + 1));
        TRG(u, 0);
        row_task<4, 8192>((f ? g_x + 2048 * 72 : xin) + row * 72, g_pa + ((j & (RING - 1)) * 64 + f * 32 + i) * 288,
                    g_x + (f * 4096 + row) * 72, reinterpret_cast<char*>(g_xt + u * 4608 + f * 256), i, lane, ring_tag<NTA>(j, ep));
        TRG(u, 1);
        cnt_add(g_cnt + (C_X + u) * 8, lane);
        TRG(u, 2);
    }
}

__global__ void __launch_bounds__(384, 1)
k_aux(const __nv_bfloat16* __restrict__ x0, const __nv_bfloat16* __restrict__ wqkv, const __nv_bfloat16* __restrict__ wo,
      const __nv_bfloat16* __restrict__ Wo, __nv_bfloat16* __restrict__ out, const Tune tune) {
    using namespace ka;
    extern __shared__ unsigned char smem_raw[];
    const uint32_t sb = (smem_u32(smem_raw) + 1023) & ~1023u;
    const int tid = threadIdx.x, lane = tid & 31, warp = __shfl_sync(~0u, tid >> 5, 0), g = lane >> 2, c = lane & 3;
    const int b = blockIdx.x;
    const uint32_t bar = sb + O_BAR;
    const uint32_t ep = __shfl_sync(~0u, ldg32(&g_epoch), 0);

    TRG(79, 0);
    const uint4* xin = reinterpret_cast<const uint4*>(x0);
    if (warp >= 8 || b == 35) {
        asm volatile("setmaxnreg.dec.sync.aligned.u32 128;");
        const int rw = b < 24 ? (warp - 8) * 24 + b : b < 35 ? (warp - 8) * 11 + b - 24 : 128 + 2 * warp;
        if (b < 24 || b == 35 || rw < 32) {
#pragma unroll 1
            for (int row = b < 24 ? rw + 32 : rw; row < 2048; row += (row & 1) ? 23 : 1) {
                if (lane == 0 && b == 35 && row < 2024) prefetch_l2(xin + (row + 24) * 72, 1152);
                row_task<0>(xin + row * 72, nullptr, nullptr, reinterpret_cast<char*>(g_xa + (row >> 5) * 4608), (row & 1) * 16 + ((row & 31) >> 1), lane, 0);
                if (b < 35) { cnt_add(g_cnt + (C_N0 + (row >> 5)) * 8, lane); break; }
                if (row & 1) cnt_add<2>(g_cnt + (C_N0 + (row >> 5)) * 8, lane);
            }
        }
        if (rw < 32) {
            const int f = b < 24, i = rw;
#pragma unroll 1
            for (int seg = 0; seg < NSEG; seg++) {
                const int u = seg + f * LAG, row = seg * 32 + i;
                hint_wait(g_cnt + (C_WB + u * 4 + f * 2 + (i >> 4)) * 8, 24 * (ep + 1));
                TRG(u, 0);
                row_task<8>(g_x + (f * 4096 + row) * 72, g_pb + ((u & (RING - 1)) * 64 + f * 32 + i) * 576,
                            f ? reinterpret_cast<uint4*>(out) + row * 72 : g_x + (2048 + row) * 72,
                            f ? nullptr : reinterpret_cast<char*>(g_xa + (seg + LAGA) * 4608 + 2304), (i & 1) * 16 + (i >> 1), lane, ring_tag(u, ep));
                TRG(u, 1);
                cnt_add(g_cnt + (C_RB + f * NSEG + seg) * 8, lane);
                TRG(u, 2);
            }
            if (f && rw == 31) {
                asm volatile("griddepcontrol.wait;" ::: "memory");
                if (lane == 0) g_epoch = ep + 1;
            }
        } else if (rw < 64 && b < 24) rows_a(xin, 0, rw - 32, lane, ep, warp);
        return;
    }

    if (b < 24) {
        if (warp >= 4) {
            const int kq = b / 6, nq = b % 6;
            uint4 v[17];
#pragma unroll
            for (int q = 0; q < 17; q++) {
                const int it = q * 4 + warp - 4, kr = (it / 3) * 8 + g, s = kq * 11 + (kr >> 4), a = s >> 2, j = s & 3, e = kr & 15;
                const int head = 3 * a + (j < 3 ? j : e >> 1), row = head * 18 + (j < 3 ? e : 16 + (e & 1));
                v[q] = make_uint4(0, 0, 0, 0);
                if (it < 66 && head < 32 && (j < 3 || e < 6)) v[q] = *reinterpret_cast<const uint4*>(wo + row * DM + nq * 96 + (it % 3) * 32 + c * 8);
            }
#pragma unroll
            for (int q = 0; q < 17; q++) {
                const int it = q * 4 + warp - 4;
                const uint32_t ad = sb + O_WA + (it % 3) * 4 * 2816 + (it / 3) * 128 + lane * 4;
                if (it < 66) { sts32(ad, v[q].x); sts32(ad + 2816, v[q].y); sts32(ad + 2 * 2816, v[q].z); sts32(ad + 3 * 2816, v[q].w); }
            }
        } else {
            const int kg = b / 3, ng = b % 3;
            delay(DLYB);
#pragma unroll 1
            for (int bt = 0; bt < 4; bt++) {
                uint4 v[24];
#pragma unroll
                for (int q = 0; q < 24; q++)
                    v[q] = *reinterpret_cast<const uint4*>(Wo + (size_t)(kg * 512 + (bt * 4 + q / 6) * 32 + warp * 8 + g) * DM + ng * 192 + (q % 6) * 32 + c * 8);
#pragma unroll
                for (int q = 0; q < 24; q++) {
                    const uint32_t ad = sb + (q % 6) * 4 * 8192 + ((bt * 4 + q / 6) * 4 + warp) * 128 + lane * 4;
                    sts32(ad, v[q].x); sts32(ad + 8192, v[q].y); sts32(ad + 2 * 8192, v[q].z); sts32(ad + 3 * 8192, v[q].w);
                }
            }
        }
        fence_async_smem();
        bar_sync(2 + (warp >> 2), 128);
    } else {
        for (int i = tid; i < 2048; i += 256) sts128(sb + O_RING + i * 16, 0, 0, 0, 0);
        if (tid < 17) mbar_init(bar + tid * 8, tid >= 4 && tid < 8 ? 4 : 1);
        fence_async_smem();
        bar_sync(1, 256);
    }
    TRG(79, 1);
    const int wq = warp & 3;

    if (warp < 4) {
        asm volatile("setmaxnreg.inc.sync.aligned.u32 256;");
        if (b < 24) {
            const int kg = b / 3, ng = b % 3;
            const uint32_t blo = ((sb >> 4) & 0x3fff) | (8u << 16);
            uint4 a[32];
            uint32_t seen = 0;
            bool pre = false;
#pragma unroll 1
            for (int u = 0; u < NT; u++) {
                const uint32_t tag = ring_tag(u, ep);
                const uint4* src = g_o + (((u & (RING - 1)) * 256 + kg * 32) * 4 + wq) * 32 + lane;
                if (!pre) {
                    if (!__all_sync(~0u, seen >= 12 * (ep + 1))) hint_wait(g_cnt + (C_O + u * 8 + kg) * 8, 12 * (ep + 1));
#pragma unroll
                    for (int i = 0; i < VG; i++) a[i] = ldg_pkt(src + i * 128);
                }
                TRG(u, 0);
                float d[96];
                validate<VG>(a, src, 2048, tag);
                if (!pre) {
#pragma unroll
                    for (int i = VG; i < VP; i++) a[i] = ldg_pkt(src + i * 128);
                }
#pragma unroll
                for (int i = VP; i < 32; i++) a[i] = ldg_pkt(src + i * 128);
                wg_fence();
#pragma unroll
                for (int i = 0; i < 32; i++) {
                    if (i == VG) { validate<32 - VG>(a + VG, src + VG * 128, 2048, tag); wg_fence(); }
                    wgmma_rs192t(d, a[i].x, a[i].y, a[i].z, a[i].w, mkdesc(blo + i * 16, 512), i > 0);
                    if (i == VC - 1 || i == 23 || i == 31) wg_commit();
                }
                const unsigned* cn = g_cnt + (C_O + min(u + 1, NT - 1) * 8 + kg) * 8;
                const uint4* nx = g_o + ((((u + 1) & (RING - 1)) * 256 + kg * 32) * 4 + wq) * 32 + lane;
                auto look = [&]() {
                    pre = __all_sync(~0u, seen >= 12 * (ep + 1));
                    if (pre) {
#pragma unroll
                        for (int i = 0; i < VP; i++) a[i] = ldg_pkt(nx + i * 128);
                    } else seen = ldg_word(cn);
                };
                wg_wait<2>();
                seen = ldg_word(cn);
                wg_wait<1>();
                look();
                wg_wait<0>();
                if (!pre) look();
                TRG(u, 1);
                uint4* dst = g_pb + (((u & (RING - 1)) * 64 + wq * 16 + g) * 8 + kg) * 72 + ng * 24 + c;
#pragma unroll
                for (int m = 0; m < 6; m++) {
                    if (m == HB) cnt_hint(g_cnt + (C_WB + u * 4 + wq) * 8, lane);
                    stg128(dst + 4 * m, (pk(d[16 * m], d[16 * m + 1]) & ~1u) | tag, pk(d[16 * m + 4], d[16 * m + 5]), pk(d[16 * m + 8], d[16 * m + 9]), pk(d[16 * m + 12], d[16 * m + 13]));
                    stg128(dst + 4 * m + 8 * 576, (pk(d[16 * m + 2], d[16 * m + 3]) & ~1u) | tag, pk(d[16 * m + 6], d[16 * m + 7]), pk(d[16 * m + 10], d[16 * m + 11]), pk(d[16 * m + 14], d[16 * m + 15]));
                }
                TRG(u, 3);
            }
        } else {
            const int a = b - 24, f = wq >> 1;
            const uint32_t blo = ((sb >> 4) & 0x3fff) | (8u << 16), alo = (((sb + O_RING) >> 4) & 0x3fff) | (1u << 16);
            const bool m0 = 2 * c <= g, m1 = 2 * c + 1 <= g;
            const uint32_t M = (m0 ? 0xffffu : 0u) | (m1 ? 0xffff0000u : 0u);
            uint32_t kh[7], vh[7];
#pragma unroll
            for (int i = 0; i < 7; i++) kh[i] = vh[i] = 0;
            int it = 0;
#pragma unroll 1
            for (int u = 0; u < NTA; u++) {
                float d[84];
#pragma unroll 1
                for (int kb = 0; kb < 9; kb++, it++) {
                    mbar_wait(bar + (it & 3) * 8, (it >> 2) & 1);
                    if (u == 0) mbar_wait(bar + 64 + kb * 8, 0);
                    if (kb == 0) TRG(u, 0);
                    wg_fence();
#pragma unroll
                    for (int q = 0; q < 4; q++)
                        wgmma_ss168t(d, mkdesc(alo + (it & 3) * 512 + q * 2, km::DESC_HI), mkdesc(blo + kb * (A_KB >> 4) + q * 16, 64), kb + q > 0);
                    wg_commit();
                    wg_wait<1>();
                    mbar_arrive(bar + 32 + ((it - 1) & 3) * 8, lane == 0 && kb > 0);
                }
                wg_wait<0>();
                mbar_arrive(bar + 32 + ((it - 1) & 3) * 8, lane == 0);
                TRG(u, 1);
                const bool first = u == f * LAGA;
                const uint32_t tag = ring_tag<NTA>(u, ep);
                const uint32_t qt0 = pk(d[72], d[73]), qt1 = pk(d[74], d[75]), kt0 = pk(d[76], d[77]), kt1 = pk(d[78], d[79]);
                const uint32_t vt0 = movm(pk(d[80], d[81])), vt1 = movm(pk(d[82], d[83]));
                float ot[4] = {0, 0, 0, 0};
                uint4* dst = g_oa + (((u & (RING - 1)) * 4 + wq) * 44 + a * 4) * 32 + lane;
#pragma unroll
                for (int h = 0; h < 3; h++) {
                    const float* q = d + 8 * h; const float* k = d + 24 + 8 * h; const float* v = d + 48 + 8 * h;
                    const uint32_t q0 = pk(q[0], q[1]), q1 = pk(q[2], q[3]), q2 = pk(q[4], q[5]), q3 = pk(q[6], q[7]);
                    const uint32_t k0 = pk(k[0], k[1]), k1 = pk(k[4], k[5]), k2 = pk(k[2], k[3]), k3 = pk(k[6], k[7]);
                    const uint32_t v0 = movm(pk(v[0], v[1])), v1 = movm(pk(v[2], v[3])), v2 = movm(pk(v[4], v[5])), v3 = movm(pk(v[6], v[7]));
                    const uint32_t t0 = c == h ? qt0 : 0, t1 = c == h ? qt1 : 0;
                    float sp[4] = {0, 0, 0, 0}, sl[4] = {0, 0, 0, 0}, sh[4] = {0, 0, 0, 0};
                    mma16(sp, q0, q1, q2, q3, kh[2 * h], kh[2 * h + 1]); mma16(sl, q0, q1, q2, q3, k0, k1); mma16(sh, q0, q1, q2, q3, k2, k3);
                    mma8(sp, t0, t1, kh[6]); mma8(sl, t0, t1, kt0); mma8(sh, t0, t1, kt1);
                    float x0_ = m0 ? sl[0] : first ? -INFINITY : sp[0], x1_ = m1 ? sl[1] : first ? -INFINITY : sp[1];
                    float y0_ = m0 ? sh[2] : sl[2], y1_ = m1 ? sh[3] : sl[3];
                    float mx = fmaxf(x0_, x1_), my = fmaxf(y0_, y1_);
#pragma unroll
                    for (int o = 1; o < 4; o <<= 1) { mx = fmaxf(mx, __shfl_xor_sync(~0u, mx, o)); my = fmaxf(my, __shfl_xor_sync(~0u, my, o)); }
                    mx *= -SC; my *= -SC;
                    x0_ = ex2(fmaf(x0_, SC, mx)); x1_ = ex2(fmaf(x1_, SC, mx)); y0_ = ex2(fmaf(y0_, SC, my)); y1_ = ex2(fmaf(y1_, SC, my));
                    float lx = x0_ + x1_, ly = y0_ + y1_;
#pragma unroll
                    for (int o = 1; o < 4; o <<= 1) { lx += __shfl_xor_sync(~0u, lx, o); ly += __shfl_xor_sync(~0u, ly, o); }
                    lx = rcp(lx); ly = rcp(ly);
                    const uint32_t px = pk(x0_ * lx, x1_ * lx), py = pk(y0_ * ly, y1_ * ly);
                    const uint32_t hm = (g >> 1) == h ? ~0u : 0u;
                    float o0[4] = {0, 0, 0, 0}, o1[4] = {0, 0, 0, 0};
                    mma16(o0, px & M, py & ~M, 0, py & M, v0, v1); mma16(o1, px & M, py & ~M, 0, py & M, v2, v3);
                    mma16(ot, px & M, py & ~M, 0, py & M, vt0 & hm, vt1 & hm);
                    mma8(o0, px & ~M, 0, vh[2 * h]); mma8(o1, px & ~M, 0, vh[2 * h + 1]); mma8(ot, px & ~M, 0, vh[6] & hm);
                    if (h == HA) cnt_hint(g_cnt + (C_A + u * 4 + wq) * 8, lane);
                    stg128(dst + h * 32, (pk(o0[0], o0[1]) & ~1u) | tag, pk(o0[2], o0[3]), pk(o1[0], o1[1]), pk(o1[2], o1[3]));
                    kh[2 * h] = k2; kh[2 * h + 1] = k3; vh[2 * h] = v1; vh[2 * h + 1] = v3;
                }
                kh[6] = kt1; vh[6] = vt1;
                stg128(dst + 96, (pk(ot[0], ot[1]) & ~1u) | tag, pk(ot[2], ot[3]), 0, 0);
                TRG(u, 2);
            }
        }
    } else {
        asm volatile("setmaxnreg.dec.sync.aligned.u32 120;");
        if (b < 24) {
            const int kq = b / 6, nq = b % 6;
            const uint32_t blo = (((sb + O_WA) >> 4) & 0x3fff) | (8u << 16);
#pragma unroll 1
            for (int u = 0; u < NTA; u++) {
                hint_wait(g_cnt + (C_A + u * 4 + wq) * 8, 11 * (ep + 1));
                const uint32_t tag = ring_tag<NTA>(u, ep);
                TRG(u, 0);
                const uint4* src = g_oa + (((u & (RING - 1)) * 4 + wq) * 44 + kq * 11) * 32 + lane;
                uint4 a[11];
                float d[48];
#pragma unroll
                for (int i = 0; i < 11; i++) a[i] = ldg_pkt(src + i * 32);
                validate<11>(a, src, 512, tag);
                wg_fence();
#pragma unroll
                for (int i = 0; i < 11; i++) wgmma_rs96t(d, a[i].x, a[i].y, a[i].z, a[i].w, mkdesc(blo + i * 16, 176), i > 0);
                wg_commit();
                wg_wait<0>();
                TRG(u, 1);
                uint4* dst = g_pa + (((u & (RING - 1)) * 64 + (wq >> 1) * 32 + 2 * g + (wq & 1)) * 4 + kq) * 72 + nq * 12 + c;
#pragma unroll
                for (int m = 0; m < 3; m++) {
                    if (m == HW) cnt_hint(g_cnt + (C_WA + u * 4 + wq) * 8, lane);
                    stg128(dst + 4 * m, (pk(d[16 * m], d[16 * m + 1]) & ~1u) | tag, pk(d[16 * m + 4], d[16 * m + 5]), pk(d[16 * m + 8], d[16 * m + 9]), pk(d[16 * m + 12], d[16 * m + 13]));
                    stg128(dst + 4 * m + 16 * 288, (pk(d[16 * m + 2], d[16 * m + 3]) & ~1u) | tag, pk(d[16 * m + 6], d[16 * m + 7]), pk(d[16 * m + 10], d[16 * m + 11]), pk(d[16 * m + 14], d[16 * m + 15]));
                }
                TRG(u, 3);
            }
        } else if (warp == 4) {
            mbar_expect(bar + 64 + lane * 8, A_KB, lane < 9);
            int it = 0;
#pragma unroll 1
            for (int u = 0; u < NTA; u++) {
                if (u == 0) { cnt_wait(g_cnt + C_W * 8, 96 * (ep + 1)); TRG(78, 0); }
                if (u < NSEG) cnt_wait(g_cnt + (C_N0 + u) * 8, 32 * (ep + 1));
                if (u > LAGA + LAG) cnt_wait(g_cnt + (C_RB + NSEG + u - LAGA - LAG - 1) * 8, 32 * (ep + 1));
                if (u >= LAGA) cnt_wait(g_cnt + (C_RB + u - LAGA) * 8, 32 * (ep + 1));
                TRG(u, 0);
                asm volatile("fence.proxy.async.global;" ::: "memory");
                const bool on = lane == 0 ? u < NSEG : lane == 1 && u >= LAGA;
#pragma unroll 1
                for (int kb = 0; kb < 9; kb++, it++) {
                    if (it >= 4) mbar_wait(bar + 32 + (it & 3) * 8, ((it >> 2) - 1) & 1);
                    mbar_expect(bar + (it & 3) * 8, u < NSEG && u >= LAGA ? 8192 : 4096, lane == 0);
                    asm volatile("{.reg .pred p; setp.ne.u32 p, %3, 0; @p cp.async.bulk.shared::cluster.global.mbarrier::complete_tx::bytes [%0], [%1], 4096, [%2];}"
                        :: "r"(sb + O_RING + (it & 3) * 8192 + (lane & 1) * 4096), "l"(g_xa + u * 4608 + (lane & 1) * 2304 + kb * 256), "r"(bar + (it & 3) * 8), "r"((uint32_t)on) : "memory");
                    if (u == 0) asm volatile("{.reg .pred p; setp.ne.u32 p, %4, 0; @p cp.async.bulk.shared::cluster.global.mbarrier::complete_tx::bytes [%0], [%1], %3, [%2];}"
                        :: "r"(sb + lane * A_KB), "l"(g_wa + ((b - 24) * 9 + lane) * (A_KB / 16)), "r"(bar + 64 + lane * 8), "n"(A_KB),
                           "r"((uint32_t)(lane < 9 && kb == (lane < 4 ? lane : lane < 6 ? 3 : lane - 2))) : "memory");
                }
            }
        } else if ((warp - 5) * 11 + b - 24 < 32) rows_a(xin, 1, (warp - 5) * 11 + b - 24, lane, ep, warp);
    }
}

static Tune h_tune = {{0, 10, 1, 2, 2, 6000, 0, 0, 10000, 0}};

extern "C" void kernel_launch(void* const* d_in, const int* in_sizes, int n_in, void* d_out, int out_size) {
    const __nv_bfloat16* x = (const __nv_bfloat16*)d_in[0];
    const __nv_bfloat16* wqkv = (const __nv_bfloat16*)d_in[1];
    const __nv_bfloat16* wo = (const __nv_bfloat16*)d_in[2];
    const __nv_bfloat16* mem0 = (const __nv_bfloat16*)d_in[4];
    const __nv_bfloat16* Wq = (const __nv_bfloat16*)d_in[5];
    const __nv_bfloat16* Wk = (const __nv_bfloat16*)d_in[6];
    const __nv_bfloat16* Wv = (const __nv_bfloat16*)d_in[7];
    const __nv_bfloat16* Wo = (const __nv_bfloat16*)d_in[8];
    cudaFuncSetAttribute(k_main, cudaFuncAttributeMaxDynamicSharedMemorySize, km::SMEM);
    cudaFuncSetAttribute(k_aux, cudaFuncAttributeMaxDynamicSharedMemorySize, ka::SMEM);
    cudaStream_t s = cudaStreamPerThread;
    k_main<<<96, 384, km::SMEM, s>>>(x, wqkv, wo, mem0, Wq, Wk, Wv, Wo, h_tune);
    cudaLaunchConfig_t cfg = {};
    cudaLaunchAttribute at[1];
    at[0].id = cudaLaunchAttributeProgrammaticStreamSerialization;
    at[0].val.programmaticStreamSerializationAllowed = 1;
    cfg.stream = s; cfg.attrs = at; cfg.numAttrs = 1;
    cfg.gridDim = dim3(36); cfg.blockDim = dim3(384); cfg.dynamicSmemBytes = ka::SMEM;
    cudaLaunchKernelEx(&cfg, k_aux, x, wqkv, wo, Wo, (__nv_bfloat16*)d_out, h_tune);
}
```

```cpp
#include <cuda_runtime.h>
#include <cuda_bf16.h>
#include <stdint.h>

#define LAG 7
constexpr int NSEG = 64;
constexpr int NT = NSEG + LAG;
#define AHEAD 1
constexpr int LAGA = LAG + AHEAD;
constexpr int NTA = NSEG + LAGA;
#define RING_ 8
constexpr int RING = RING_;
constexpr int DM = 576;

__device__ __align__(1024) uint4 g_xt[NT * 2 * 9 * 256];
__device__ __align__(1024) uint4 g_o[RING * 4 * 256 * 32];
__device__ __align__(1024) uint4 g_ex[2 * 131072];
__device__ unsigned g_side[96];
__device__ __align__(1024) uint4 g_pb[RING * 64 * 8 * 72];
__device__ __align__(1024) uint4 g_pa[RING * 64 * 4 * 72];
__device__ __align__(1024) uint4 g_oa[RING * 4 * 44 * 32];
__device__ __align__(1024) uint4 g_xa[NTA * 2 * 9 * 256];
__device__ __align__(1024) uint4 g_wa[11 * 9 * 21 * 64];
__device__ __align__(1024) uint4 g_x[3 * 2048 * 72];

constexpr int C_X = 0;
constexpr int C_O = C_X + NT;
constexpr int C_WB = C_O + NT * 8;
constexpr int C_RB = C_WB + NT * 4;
constexpr int C_A = C_RB + 2 * NSEG;
constexpr int C_WA = C_A + NTA * 4;
constexpr int C_N0 = C_WA + NTA * 4;
constexpr int C_W = C_N0 + NSEG;
constexpr int C_DONE = C_W + 1;
constexpr int C_TOTAL = C_DONE + 1;
__device__ __align__(1024) unsigned g_cnt[C_TOTAL * 8];
__device__ unsigned g_epoch;

struct Tune { uint32_t v[10]; };
#define TR(i)
#define TR1(i)
#define TR_ON(t)
#define TR_INIT(base)
#define TR_DUMP(slot)
#define TRG(t, i)
constexpr int TR_BYTES = 0;

#define DEVI __device__ __forceinline__
DEVI uint32_t smem_u32(const void* p) { return (uint32_t)__cvta_generic_to_shared(p); }
DEVI uint32_t pk(float lo, float hi) { uint32_t r; asm("cvt.rn.bf16x2.f32 %0, %1, %2;" : "=r"(r) : "f"(hi), "f"(lo)); return r; }
DEVI float bf_lo(uint32_t u) { return __uint_as_float(u << 16); }
DEVI float bf_hi(uint32_t u) { return __uint_as_float(u & 0xffff0000u); }
DEVI uint32_t add2(uint32_t a, uint32_t b) { uint32_t d; asm("add.rn.bf16x2 %0, %1, %2;" : "=r"(d) : "r"(a), "r"(b)); return d; }
DEVI uint32_t movm(uint32_t a) { uint32_t d; asm volatile("movmatrix.sync.aligned.m8n8.trans.b16 %0, %1;" : "=r"(d) : "r"(a)); return d; }
DEVI float2 shfl2(float a, float b, int o) {
    float2 r; asm volatile("shfl.sync.bfly.b32 %0, %2, %4, 31, -1; shfl.sync.bfly.b32 %1, %3, %4, 31, -1;" : "=&f"(r.x), "=f"(r.y) : "f"(a), "f"(b), "r"(o)); return r;
}
DEVI float ex2(float x) { float y; asm("ex2.approx.ftz.f32 %0, %1;" : "=f"(y) : "f"(x)); return y; }
DEVI float rcp(float x) { float y; asm("rcp.approx.ftz.f32 %0, %1;" : "=f"(y) : "f"(x)); return y; }
DEVI void mma16(float (&d)[4], uint32_t a0, uint32_t a1, uint32_t a2, uint32_t a3, uint32_t b0, uint32_t b1) {
    asm volatile("mma.sync.aligned.m16n8k16.row.col.f32.bf16.bf16.f32 {%0,%1,%2,%3}, {%4,%5,%6,%7}, {%8,%9}, {%0,%1,%2,%3};"
        : "+f"(d[0]), "+f"(d[1]), "+f"(d[2]), "+f"(d[3]) : "r"(a0), "r"(a1), "r"(a2), "r"(a3), "r"(b0), "r"(b1));
}
DEVI void mma8(float (&d)[4], uint32_t a0, uint32_t a1, uint32_t b0) {
    asm volatile("mma.sync.aligned.m16n8k8.row.col.f32.bf16.bf16.f32 {%0,%1,%2,%3}, {%4,%5}, {%6}, {%0,%1,%2,%3};"
        : "+f"(d[0]), "+f"(d[1]), "+f"(d[2]), "+f"(d[3]) : "r"(a0), "r"(a1), "r"(b0));
}
DEVI uint4 lds128(uint32_t a) { uint4 v; asm volatile("ld.shared.v4.u32 {%0,%1,%2,%3}, [%4];" : "=r"(v.x), "=r"(v.y), "=r"(v.z), "=r"(v.w) : "r"(a) : "memory"); return v; }
DEVI uint2 lds64(uint32_t a) { uint2 v; asm volatile("ld.shared.v2.u32 {%0,%1}, [%2];" : "=r"(v.x), "=r"(v.y) : "r"(a) : "memory"); return v; }
DEVI uint32_t lds32(uint32_t a) { uint32_t v; asm volatile("ld.shared.u32 %0, [%1];" : "=r"(v) : "r"(a) : "memory"); return v; }
DEVI uint32_t lds32v(uint32_t a) { uint32_t v; asm volatile("ld.volatile.shared.u32 %0, [%1];" : "=r"(v) : "r"(a) : "memory"); return v; }
DEVI uint4 lds128v(uint32_t a) { uint4 v; asm volatile("ld.volatile.shared.v4.u32 {%0,%1,%2,%3}, [%4];" : "=r"(v.x), "=r"(v.y), "=r"(v.z), "=r"(v.w) : "r"(a) : "memory"); return v; }
DEVI uint32_t lds16(uint32_t a) { uint32_t v; asm volatile("ld.shared.u16 %0, [%1];" : "=r"(v) : "r"(a) : "memory"); return v; }
DEVI uint4 ldsm4(uint32_t a) { uint4 v; asm volatile("ldmatrix.sync.aligned.m8n8.x4.shared.b16 {%0,%1,%2,%3}, [%4];" : "=r"(v.x), "=r"(v.y), "=r"(v.z), "=r"(v.w) : "r"(a) : "memory"); return v; }
DEVI uint4 ldsm4p(uint32_t a, bool pred) {
    uint4 v; asm volatile("{.reg .pred p; setp.ne.u32 p, %5, 0; @p ldmatrix.sync.aligned.m8n8.x4.shared.b16 {%0,%1,%2,%3}, [%4];}" : "=r"(v.x), "=r"(v.y), "=r"(v.z), "=r"(v.w) : "r"(a), "r"((uint32_t)pred) : "memory"); return v;
}
DEVI uint4 ldsm4t(uint32_t a) { uint4 v; asm volatile("ldmatrix.sync.aligned.m8n8.x4.trans.shared.b16 {%0,%1,%2,%3}, [%4];" : "=r"(v.x), "=r"(v.y), "=r"(v.z), "=r"(v.w) : "r"(a) : "memory"); return v; }
DEVI uint2 ldsm2(uint32_t a) { uint2 v; asm volatile("ldmatrix.sync.aligned.m8n8.x2.shared.b16 {%0,%1}, [%2];" : "=r"(v.x), "=r"(v.y) : "r"(a) : "memory"); return v; }
DEVI void stsm4t(uint32_t a, uint32_t x, uint32_t y, uint32_t z, uint32_t w) { asm volatile("stmatrix.sync.aligned.m8n8.x4.trans.shared.b16 [%0], {%1,%2,%3,%4};" :: "r"(a), "r"(x), "r"(y), "r"(z), "r"(w) : "memory"); }
DEVI void sts128(uint32_t a, uint32_t x, uint32_t y, uint32_t z, uint32_t w) { asm volatile("st.shared.v4.u32 [%0], {%1,%2,%3,%4};" :: "r"(a), "r"(x), "r"(y), "r"(z), "r"(w) : "memory"); }
DEVI void sts64(uint32_t a, uint32_t x, uint32_t y) { asm volatile("st.shared.v2.u32 [%0], {%1,%2};" :: "r"(a), "r"(x), "r"(y) : "memory"); }
DEVI void sts32(uint32_t a, uint32_t x) { asm volatile("st.shared.u32 [%0], %1;" :: "r"(a), "r"(x) : "memory"); }
DEVI void sts32p(uint32_t a, uint32_t x, bool pred) { asm volatile("{.reg .pred p; setp.ne.u32 p, %2, 0; @p st.shared.u32 [%0], %1;}" :: "r"(a), "r"(x), "r"((uint32_t)pred) : "memory"); }
DEVI void sta128(uint32_t a, uint32_t x, uint32_t y, uint32_t z, uint32_t w, uint32_t bar) {
    asm volatile("st.async.weak.shared::cluster.mbarrier::complete_tx::bytes.v4.b32 [%0], {%1,%2,%3,%4}, [%5];" :: "r"(a), "r"(x), "r"(y), "r"(z), "r"(w), "r"(bar) : "memory");
}
DEVI void sta128p(uint32_t a, uint32_t x, uint32_t y, uint32_t z, uint32_t w, uint32_t bar, bool pred) {
    asm volatile("{.reg .pred p; setp.ne.u32 p, %6, 0; @p st.async.weak.shared::cluster.mbarrier::complete_tx::bytes.v4.b32 [%0], {%1,%2,%3,%4}, [%5];}" :: "r"(a), "r"(x), "r"(y), "r"(z), "r"(w), "r"(bar), "r"((uint32_t)pred) : "memory");
}
DEVI void sta64(uint32_t a, uint32_t x, uint32_t y, uint32_t bar) {
    asm volatile("st.async.weak.shared::cluster.mbarrier::complete_tx::bytes.v2.b32 [%0], {%1,%2}, [%3];" :: "r"(a), "r"(x), "r"(y), "r"(bar) : "memory");
}
DEVI void sta32(uint32_t a, uint32_t x, uint32_t bar) {
    asm volatile("st.async.weak.shared::cluster.mbarrier::complete_tx::bytes.b32 [%0], %1, [%2];" :: "r"(a), "r"(x), "r"(bar) : "memory");
}
DEVI uint4 ldg_pkt(const void* p) {
    uint4 v;
    asm volatile("ld.relaxed.gpu.global.v4.u32 {%0,%1,%2,%3}, [%4];" : "=r"(v.x), "=r"(v.y), "=r"(v.z), "=r"(v.w) : "l"(p) : "memory");
    return v;
}
DEVI void ldg_pkt_if(uint4& v, const void* p, bool pred) {
    asm volatile("{.reg .pred p; setp.ne.u32 p, %5, 0; @p ld.relaxed.gpu.global.v4.u32 {%0,%1,%2,%3}, [%4];}"
        : "+r"(v.x), "+r"(v.y), "+r"(v.z), "+r"(v.w) : "l"(p), "r"((uint32_t)pred) : "memory");
}
DEVI void ldg_pkt_retry(uint4& v, const void* p, uint32_t tag) {
    asm volatile("{.reg .pred p; .reg .b32 t; lop3.b32 t, %0, %5, 1, 0x28; setp.ne.u32 p, t, 0; @p ld.relaxed.gpu.global.v4.u32 {%0,%1,%2,%3}, [%4];}"
        : "+r"(v.x), "+r"(v.y), "+r"(v.z), "+r"(v.w) : "l"(p), "r"(tag) : "memory");
}
DEVI void stg_pkt(void* p, uint32_t x, uint32_t y, uint32_t z, uint32_t w) {
    asm volatile("st.relaxed.gpu.global.v4.u32 [%0], {%1,%2,%3,%4};" :: "l"(p), "r"(x), "r"(y), "r"(z), "r"(w) : "memory");
}
DEVI uint32_t ldg_word(const void* p) { uint32_t v; asm volatile("ld.relaxed.gpu.global.u32 %0, [%1];" : "=r"(v) : "l"(p) : "memory"); return v; }
DEVI void stg_word(void* p, uint32_t x, bool pred) {
    asm volatile("{.reg .pred p; setp.ne.u32 p, %2, 0; @p st.relaxed.gpu.global.u32 [%0], %1;}" :: "l"(p), "r"(x), "r"((uint32_t)pred) : "memory");
}
DEVI uint2 ldg64nc(const void* p) { uint2 v; asm volatile("ld.global.nc.L1::no_allocate.v2.u32 {%0,%1}, [%2];" : "=r"(v.x), "=r"(v.y) : "l"(p)); return v; }
DEVI void prefetch_l2(const void* p, uint32_t bytes) { asm volatile("cp.async.bulk.prefetch.L2.global [%0], %1;" :: "l"(p), "r"(bytes) : "memory"); }
DEVI uint4 ldg128(const void* p) { uint4 v; asm volatile("ld.global.cg.v4.u32 {%0,%1,%2,%3}, [%4];" : "=r"(v.x), "=r"(v.y), "=r"(v.z), "=r"(v.w) : "l"(p) : "memory"); return v; }
DEVI uint2 ldg64(const void* p) { uint2 v; asm volatile("ld.global.cg.v2.u32 {%0,%1}, [%2];" : "=r"(v.x), "=r"(v.y) : "l"(p) : "memory"); return v; }
DEVI uint32_t ldg32(const void* p) { uint32_t v; asm volatile("ld.global.cg.u32 %0, [%1];" : "=r"(v) : "l"(p) : "memory"); return v; }
DEVI void stg128(void* p, uint32_t x, uint32_t y, uint32_t z, uint32_t w) { asm volatile("st.global.cg.v4.u32 [%0], {%1,%2,%3,%4};" :: "l"(p), "r"(x), "r"(y), "r"(z), "r"(w) : "memory"); }
DEVI void stg128p(void* p, uint32_t x, uint32_t y, uint32_t z, uint32_t w, bool pred) { asm volatile("{.reg .pred p; setp.ne.u32 p, %5, 0; @p st.global.cg.v4.u32 [%0], {%1,%2,%3,%4};}" :: "l"(p), "r"(x), "r"(y), "r"(z), "r"(w), "r"((uint32_t)pred) : "memory"); }
DEVI void stg64(void* p, uint32_t x, uint32_t y) { asm volatile("st.global.cg.v2.u32 [%0], {%1,%2};" :: "l"(p), "r"(x), "r"(y) : "memory"); }
DEVI void stg32(void* p, uint32_t x) { asm volatile("st.global.cg.u32 [%0], %1;" :: "l"(p), "r"(x) : "memory"); }
DEVI void cp16(uint32_t dst, const void* src) { asm volatile("cp.async.cg.shared.global [%0], [%1], 16;" :: "r"(dst), "l"(src) : "memory"); }
DEVI void cp16_if(uint32_t dst, const void* src, bool pred) { asm volatile("{.reg .pred p; setp.ne.u32 p, %2, 0; @p cp.async.cg.shared.global [%0], [%1], 16;}" :: "r"(dst), "l"(src), "r"((uint32_t)pred) : "memory"); }
DEVI void cp_commit() { asm volatile("cp.async.commit_group;" ::: "memory"); }
DEVI void cp4(uint32_t dst, const void* src) { asm volatile("cp.async.ca.shared.global [%0], [%1], 4;" :: "r"(dst), "l"(src) : "memory"); }
template <int N> DEVI void cp_wait() { asm volatile("cp.async.wait_group %0;" :: "n"(N) : "memory"); }
DEVI void cp_wait_all() { asm volatile("cp.async.wait_all;" ::: "memory"); }
DEVI void bar_sync(int id, int n) { asm volatile("bar.sync %0, %1;" :: "r"(id), "r"(n) : "memory"); }
DEVI void bar_arrive(int id, int n) { asm volatile("bar.arrive %0, %1;" :: "r"(id), "r"(n) : "memory"); }
DEVI void fence_async_smem() { asm volatile("fence.proxy.async.shared::cta;" ::: "memory"); }
DEVI void fence_async_global() { asm volatile("fence.proxy.async.global;" ::: "memory"); }
DEVI void mbar_init(uint32_t b, int n) { asm volatile("mbarrier.init.shared.b64 [%0], %1;" :: "r"(b), "r"(n) : "memory"); }
DEVI void mbar_expect(uint32_t b, uint32_t bytes, bool pred) {
    asm volatile("{.reg .pred p; setp.ne.u32 p, %2, 0; @p mbarrier.arrive.expect_tx.shared.b64 _, [%0], %1;}" :: "r"(b), "r"(bytes), "r"((uint32_t)pred) : "memory");
}
DEVI void mbar_arrive(uint32_t b, bool pred) { asm volatile("{.reg .pred p; setp.ne.u32 p, %1, 0; @p mbarrier.arrive.shared.b64 _, [%0];}" :: "r"(b), "r"((uint32_t)pred) : "memory"); }
DEVI void mbar_arrive_all3(uint32_t b, uint32_t lane) {
    asm volatile("{.reg .pred p; .reg .u32 a; setp.lt.u32 p, %1, 3; @p mapa.shared::cluster.u32 a, %0, %1; @p mbarrier.arrive.relaxed.cluster.shared::cluster.b64 _, [a];}" :: "r"(b), "r"(lane) : "memory");
}
#define FAULT "or.b32 n, n, 1; st.volatile.shared.u32 [n], n;\n"
#define LIM1 "400000"
#define LIM2 "2000000"
DEVI void fault_if(bool p, uint32_t n) { asm volatile("{.reg .pred p; setp.ne.u32 p, %0, 0; @p st.volatile.shared.u32 [%1], %1;}" :: "r"((uint32_t)p), "r"(n | 1) : "memory"); }
DEVI void mbar_wait(uint32_t b, uint32_t parity) {
    asm volatile("{.reg .pred p; .reg .u32 n;\n"
        "mbarrier.try_wait.parity.shared::cta.b64 p, [%0], %1;\n"
        "@p bra.uni D%=;\n"
        "mov.u32 n, 0;\n"
        "W%=: mbarrier.try_wait.parity.shared::cta.b64 p, [%0], %1;\n"
        "@p bra.uni D%=;\n"
        "add.u32 n, n, 1; setp.lt.u32 p, n, " LIM1 "; @p bra.uni W%=;\n"
        FAULT
        "D%=:}" :: "r"(b), "r"(parity) : "memory");
}
constexpr int POLL_LIMIT = 2000000;
DEVI void cnt_wait(const unsigned* c, unsigned target) {
    asm volatile("{.reg .pred p; .reg .u32 n, v;\n"
        "ld.acquire.gpu.global.u32 v, [%0];\n"
        "setp.ge.u32 p, v, %1; vote.sync.all.pred p, p, 0xffffffff; @p bra.uni D%=;\n"
        "mov.u32 n, 0;\n"
        "W%=: ld.acquire.gpu.global.u32 v, [%0];\n"
        "setp.ge.u32 p, v, %1; vote.sync.all.pred p, p, 0xffffffff; @p bra.uni D%=;\n"
        "add.u32 n, n, 1; setp.lt.u32 p, n, " LIM2 "; @p bra.uni W%=;\n"
        FAULT
        "D%=:}" :: "l"(c), "r"(target) : "memory");
}
DEVI void hint_wait(const unsigned* c, unsigned target) {
    asm volatile("{.reg .pred p; .reg .u32 n, v;\n"
        "ld.relaxed.gpu.global.u32 v, [%0];\n"
        "setp.ge.u32 p, v, %1; vote.sync.all.pred p, p, 0xffffffff; @p bra.uni D%=;\n"
        "mov.u32 n, 0;\n"
        "W%=: ld.relaxed.gpu.global.u32 v, [%0];\n"
        "setp.ge.u32 p, v, %1; vote.sync.all.pred p, p, 0xffffffff; @p bra.uni D%=;\n"
        "add.u32 n, n, 1; setp.lt.u32 p, n, " LIM2 "; @p bra.uni W%=;\n"
        FAULT
        "D%=:}" :: "l"(c), "r"(target) : "memory");
}
DEVI void cnt_look(const unsigned* c, unsigned target, uint32_t flag, uint32_t val) {
    asm volatile("{.reg .pred q; .reg .u32 v; ld.acquire.gpu.global.u32 v, [%0]; setp.ge.u32 q, v, %1; @q st.release.cta.shared.u32 [%2], %3;}"
        :: "l"(c), "r"(target), "r"(flag), "r"(val) : "memory");
}
DEVI uint32_t lds_acq(uint32_t a) { uint32_t v; asm volatile("ld.acquire.cta.shared.u32 %0, [%1];" : "=r"(v) : "r"(a) : "memory"); return v; }
template <int N = 1> DEVI void cnt_add(unsigned* c, int lane) {
    asm volatile("{.reg .pred p; setp.eq.u32 p, %1, 0; fence.acq_rel.gpu; bar.warp.sync 0xffffffff; @p red.relaxed.gpu.global.add.u32 [%0], %2;}" :: "l"(c + lane), "r"(lane), "n"(N) : "memory");
}
DEVI void cnt_hint(unsigned* c, int lane) {
    asm volatile("{.reg .pred p; setp.eq.u32 p, %1, 0; @p red.relaxed.gpu.global.add.u32 [%0], 1;}" :: "l"(c + lane), "r"(lane) : "memory");
}
template <int N = NT> DEVI uint32_t ring_tag(unsigned u, uint32_t ep) { return (u / RING + ep * ((N - 1 - u % RING) / RING + 1) + 1) & 1; }
static_assert(RING >= LAGA && RING > LAG, "ring too short");
DEVI uint32_t lop_bad(uint32_t acc, uint32_t x, uint32_t y, uint32_t tag) {
    uint32_t d; asm("{.reg .b32 t; lop3.b32 t, %2, %3, %4, 0x7e; or.b32 %0, t, %1;}" : "=r"(d) : "r"(acc), "r"(x), "r"(y), "r"(tag)); return d;
}
template <int N> DEVI void validate(uint4* v, const void* p, int step, uint32_t tag) {
    for (int n = 0;; n++) {
        uint32_t bad = 0;
#pragma unroll
        for (int i = 0; i < N; i += 2) bad = lop_bad(bad, v[i].x, v[i + 1 < N ? i + 1 : i].x, tag);
        if (!__any_sync(~0u, bad & 1)) break;
#pragma unroll
        for (int i = 0; i < N; i++) ldg_pkt_retry(v[i], static_cast<const char*>(p) + i * step, tag);
        fault_if(n > POLL_LIMIT, n);
    }
}
DEVI uint32_t page_par(uint32_t off) { return __popc((off >> 12) & 0xb2) & 1; }
DEVI uint32_t inbox_off(int b) { return (b >> 1) * 32768 + (b & 1) * 8192; }
DEVI uint32_t mem_off(int w, int i) { return 0x180000 + w * 1024 + (i & 1) * 512 + (i & 3) * 16384 + (i < 4 ? 0 : i < 8 ? 0x30000 : 0x40000); }
DEVI void sched_fence(uint32_t zero, uint32_t id) { asm volatile("{.reg .pred p; setp.ne.u32 p, %0, %1; @p bra.uni D%=; exit; D%=:}" :: "r"(zero), "r"(id) : "memory"); }
DEVI uint32_t clk() { uint32_t c; asm volatile("mov.u32 %0, %%clock;" : "=r"(c) :: "memory"); return c; }
DEVI void delay(uint32_t n) {
    if (n) asm volatile("{.reg .pred p; .reg .u32 c, e; mov.u32 e, %%clock;\n W%=: mov.u32 c, %%clock; sub.u32 c, c, e; setp.lt.u32 p, c, %0; @p bra.uni W%=;}" :: "r"(n) : "memory");
}
DEVI void pause(uint32_t n) {
    asm volatile("{.reg .pred p; .reg .f32 x; .reg .s32 c; cvt.rn.f32.u32 x, %0;\n"
        "W%=: add.f32 x, x, 0fBF800000; mul.f32 x, x, x; sqrt.approx.ftz.f32 x, x; setp.gt.f32 p, x, 0f3F000000; @p bra.uni W%=;\n"
        "setp.lt.f32 p, x, 0fC1000000; @p st.volatile.shared.f32 [%0], x;}" :: "r"(n) : "memory");
}
DEVI void delay_until(uint32_t t0, uint32_t n) {
    asm volatile("{.reg .pred p; .reg .u32 c;\n W%=: mov.u32 c, %%clock; sub.u32 c, c, %1; setp.lt.u32 p, c, %0; @p bra.uni W%=;}" :: "r"(n), "r"(t0) : "memory");
}
DEVI void wg_fence() { asm volatile("wgmma.fence.sync.aligned;" ::: "memory"); }
DEVI void wg_commit() { asm volatile("wgmma.commit_group.sync.aligned;" ::: "memory"); }
template <int N> DEVI void wg_wait() { asm volatile("wgmma.wait_group.sync.aligned %0;" :: "n"(N) : "memory"); }
DEVI uint64_t mkdesc(uint32_t lo, uint32_t hi) { uint64_t d; asm("mov.b64 %0, {%1,%2};" : "=l"(d) : "r"(lo), "r"(hi)); return d; }
DEVI void cluster_arrive() { asm volatile("barrier.cluster.arrive.relaxed.aligned;" ::: "memory"); }
DEVI void cluster_wait() { asm volatile("barrier.cluster.wait.aligned;" ::: "memory"); }
DEVI void cluster_sync() { asm volatile("barrier.cluster.arrive.aligned;\n barrier.cluster.wait.aligned;" ::: "memory"); }
DEVI void wgmma_ss16t(float (&d)[8], uint64_t da, uint64_t db, int acc) {
    asm volatile("{.reg .pred p; setp.ne.b32 p, %10, 0;\n"
        "wgmma.mma_async.sync.aligned.m64n16k16.f32.bf16.bf16 {%0,%1,%2,%3,%4,%5,%6,%7}, %8, %9, p, 1, 1, 0, 1;}"
        : "+f"(d[0]), "+f"(d[1]), "+f"(d[2]), "+f"(d[3]), "+f"(d[4]), "+f"(d[5]), "+f"(d[6]), "+f"(d[7])
        : "l"(da), "l"(db), "r"(acc));
}
DEVI void wgmma_ss16a(float (&d)[8], uint64_t da, uint64_t db, int acc) {
    asm volatile("{.reg .pred p; setp.ne.b32 p, %10, 0;\n"
        "wgmma.mma_async.sync.aligned.m64n16k16.f32.bf16.bf16 {%0,%1,%2,%3,%4,%5,%6,%7}, %8, %9, p, 1, 1, 1, 0;}"
        : "+f"(d[0]), "+f"(d[1]), "+f"(d[2]), "+f"(d[3]), "+f"(d[4]), "+f"(d[5]), "+f"(d[6]), "+f"(d[7])
        : "l"(da), "l"(db), "r"(acc));
}
DEVI void wgmma_ss64(float (&d)[32], uint64_t da, uint64_t db, int acc) {
    asm volatile("{.reg .pred p; setp.ne.b32 p, %34, 0;\n"
        "wgmma.mma_async.sync.aligned.m64n64k16.f32.bf16.bf16 {%0,%1,%2,%3,%4,%5,%6,%7,%8,%9,%10,%11,%12,%13,%14,%15,%16,%17,%18,%19,%20,%21,%22,%23,%24,%25,%26,%27,%28,%29,%30,%31}, %32, %33, p, 1, 1, 0, 0;}"
        : "+f"(d[0]), "+f"(d[1]), "+f"(d[2]), "+f"(d[3]), "+f"(d[4]), "+f"(d[5]), "+f"(d[6]), "+f"(d[7]), "+f"(d[8]), "+f"(d[9]), "+f"(d[10]), "+f"(d[11]), "+f"(d[12]), "+f"(d[13]), "+f"(d[14]), "+f"(d[15]), "+f"(d[16]), "+f"(d[17]), "+f"(d[18]), "+f"(d[19]), "+f"(d[20]), "+f"(d[21]), "+f"(d[22]), "+f"(d[23]), "+f"(d[24]), "+f"(d[25]), "+f"(d[26]), "+f"(d[27]), "+f"(d[28]), "+f"(d[29]), "+f"(d[30]), "+f"(d[31])
        : "l"(da), "l"(db), "r"(acc));
}
DEVI void wgmma_rs16t(float (&d)[8], uint32_t a0, uint32_t a1, uint32_t a2, uint32_t a3, uint64_t db, int acc) {
    asm volatile("{.reg .pred p; setp.ne.b32 p, %13, 0;\n"
        "wgmma.mma_async.sync.aligned.m64n16k16.f32.bf16.bf16 {%0,%1,%2,%3,%4,%5,%6,%7}, {%8,%9,%10,%11}, %12, p, 1, 1, 1;}"
        : "+f"(d[0]), "+f"(d[1]), "+f"(d[2]), "+f"(d[3]), "+f"(d[4]), "+f"(d[5]), "+f"(d[6]), "+f"(d[7])
        : "r"(a0), "r"(a1), "r"(a2), "r"(a3), "l"(db), "r"(acc));
}
DEVI void wgmma_rs64(float (&d)[32], uint32_t a0, uint32_t a1, uint32_t a2, uint32_t a3, uint64_t db, int acc) {
    asm volatile("{.reg .pred p; setp.ne.b32 p, %37, 0;\n"
        "wgmma.mma_async.sync.aligned.m64n64k16.f32.bf16.bf16 {%0,%1,%2,%3,%4,%5,%6,%7,%8,%9,%10,%11,%12,%13,%14,%15,%16,%17,%18,%19,%20,%21,%22,%23,%24,%25,%26,%27,%28,%29,%30,%31}, {%32,%33,%34,%35}, %36, p, 1, 1, 0;}"
        : "+f"(d[0]), "+f"(d[1]), "+f"(d[2]), "+f"(d[3]), "+f"(d[4]), "+f"(d[5]), "+f"(d[6]), "+f"(d[7]), "+f"(d[8]), "+f"(d[9]), "+f"(d[10]), "+f"(d[11]), "+f"(d[12]), "+f"(d[13]), "+f"(d[14]), "+f"(d[15]), "+f"(d[16]), "+f"(d[17]), "+f"(d[18]), "+f"(d[19]), "+f"(d[20]), "+f"(d[21]), "+f"(d[22]), "+f"(d[23]), "+f"(d[24]), "+f"(d[25]), "+f"(d[26]), "+f"(d[27]), "+f"(d[28]), "+f"(d[29]), "+f"(d[30]), "+f"(d[31])
        : "r"(a0), "r"(a1), "r"(a2), "r"(a3), "l"(db), "r"(acc));
}
DEVI void wgmma_ss168t(float (&d)[84], uint64_t da, uint64_t db, int acc) {
    asm volatile("{.reg .pred p; setp.ne.b32 p, %86, 0;\n"
        "wgmma.mma_async.sync.aligned.m64n168k16.f32.bf16.bf16 {%0,%1,%2,%3,%4,%5,%6,%7,%8,%9,%10,%11,%12,%13,%14,%15,%16,%17,%18,%19,%20,%21,%22,%23,%24,%25,%26,%27,%28,%29,%30,%31,%32,%33,%34,%35,%36,%37,%38,%39,%40,%41,%42,%43,%44,%45,%46,%47,%48,%49,%50,%51,%52,%53,%54,%55,%56,%57,%58,%59,%60,%61,%62,%63,%64,%65,%66,%67,%68,%69,%70,%71,%72,%73,%74,%75,%76,%77,%78,%79,%80,%81,%82,%83}, %84, %85, p, 1, 1, 0, 1;}"
        : "+f"(d[0]), "+f"(d[1]), "+f"(d[2]), "+f"(d[3]), "+f"(d[4]), "+f"(d[5]), "+f"(d[6]), "+f"(d[7]), "+f"(d[8]), "+f"(d[9]), "+f"(d[10]), "+f"(d[11]), "+f"(d[12]), "+f"(d[13]), "+f"(d[14]), "+f"(d[15]), "+f"(d[16]), "+f"(d[17]), "+f"(d[18]), "+f"(d[19]), "+f"(d[20]), "+f"(d[21]), "+f"(d[22]), "+f"(d[23]), "+f"(d[24]), "+f"(d[25]), "+f"(d[26]), "+f"(d[27]), "+f"(d[28]), "+f"(d[29]), "+f"(d[30]), "+f"(d[31]), "+f"(d[32]), "+f"(d[33]), "+f"(d[34]), "+f"(d[35]), "+f"(d[36]), "+f"(d[37]), "+f"(d[38]), "+f"(d[39]), "+f"(d[40]), "+f"(d[41]), "+f"(d[42]), "+f"(d[43]), "+f"(d[44]), "+f"(d[45]), "+f"(d[46]), "+f"(d[47]), "+f"(d[48]), "+f"(d[49]), "+f"(d[50]), "+f"(d[51]), "+f"(d[52]), "+f"(d[53]), "+f"(d[54]), "+f"(d[55]), "+f"(d[56]), "+f"(d[57]), "+f"(d[58]), "+f"(d[59]), "+f"(d[60]), "+f"(d[61]), "+f"(d[62]), "+f"(d[63]), "+f"(d[64]), "+f"(d[65]), "+f"(d[66]), "+f"(d[67]), "+f"(d[68]), "+f"(d[69]), "+f"(d[70]), "+f"(d[71]), "+f"(d[72]), "+f"(d[73]), "+f"(d[74]), "+f"(d[75]), "+f"(d[76]), "+f"(d[77]), "+f"(d[78]), "+f"(d[79]), "+f"(d[80]), "+f"(d[81]), "+f"(d[82]), "+f"(d[83])
        : "l"(da), "l"(db), "r"(acc));
}
DEVI void wgmma_rs96t(float (&d)[48], uint32_t a0, uint32_t a1, uint32_t a2, uint32_t a3, uint64_t db, int acc) {
    asm volatile("{.reg .pred p; setp.ne.b32 p, %53, 0;\n"
        "wgmma.mma_async.sync.aligned.m64n96k16.f32.bf16.bf16 {%0,%1,%2,%3,%4,%5,%6,%7,%8,%9,%10,%11,%12,%13,%14,%15,%16,%17,%18,%19,%20,%21,%22,%23,%24,%25,%26,%27,%28,%29,%30,%31,%32,%33,%34,%35,%36,%37,%38,%39,%40,%41,%42,%43,%44,%45,%46,%47}, {%48,%49,%50,%51}, %52, p, 1, 1, 1;}"
        : "+f"(d[0]), "+f"(d[1]), "+f"(d[2]), "+f"(d[3]), "+f"(d[4]), "+f"(d[5]), "+f"(d[6]), "+f"(d[7]), "+f"(d[8]), "+f"(d[9]), "+f"(d[10]), "+f"(d[11]), "+f"(d[12]), "+f"(d[13]), "+f"(d[14]), "+f"(d[15]), "+f"(d[16]), "+f"(d[17]), "+f"(d[18]), "+f"(d[19]), "+f"(d[20]), "+f"(d[21]), "+f"(d[22]), "+f"(d[23]), "+f"(d[24]), "+f"(d[25]), "+f"(d[26]), "+f"(d[27]), "+f"(d[28]), "+f"(d[29]), "+f"(d[30]), "+f"(d[31]), "+f"(d[32]), "+f"(d[33]), "+f"(d[34]), "+f"(d[35]), "+f"(d[36]), "+f"(d[37]), "+f"(d[38]), "+f"(d[39]), "+f"(d[40]), "+f"(d[41]), "+f"(d[42]), "+f"(d[43]), "+f"(d[44]), "+f"(d[45]), "+f"(d[46]), "+f"(d[47])
        : "r"(a0), "r"(a1), "r"(a2), "r"(a3), "l"(db), "r"(acc));
}
DEVI void wgmma_rs192t(float (&d)[96], uint32_t a0, uint32_t a1, uint32_t a2, uint32_t a3, uint64_t db, int acc) {
    asm volatile("{.reg .pred p; setp.ne.b32 p, %101, 0;\n"
        "wgmma.mma_async.sync.aligned.m64n192k16.f32.bf16.bf16 {%0,%1,%2,%3,%4,%5,%6,%7,%8,%9,%10,%11,%12,%13,%14,%15,%16,%17,%18,%19,%20,%21,%22,%23,%24,%25,%26,%27,%28,%29,%30,%31,%32,%33,%34,%35,%36,%37,%38,%39,%40,%41,%42,%43,%44,%45,%46,%47,%48,%49,%50,%51,%52,%53,%54,%55,%56,%57,%58,%59,%60,%61,%62,%63,%64,%65,%66,%67,%68,%69,%70,%71,%72,%73,%74,%75,%76,%77,%78,%79,%80,%81,%82,%83,%84,%85,%86,%87,%88,%89,%90,%91,%92,%93,%94,%95}, {%96,%97,%98,%99}, %100, p, 1, 1, 1;}"
        : "+f"(d[0]), "+f"(d[1]), "+f"(d[2]), "+f"(d[3]), "+f"(d[4]), "+f"(d[5]), "+f"(d[6]), "+f"(d[7]), "+f"(d[8]), "+f"(d[9]), "+f"(d[10]), "+f"(d[11]), "+f"(d[12]), "+f"(d[13]), "+f"(d[14]), "+f"(d[15]), "+f"(d[16]), "+f"(d[17]), "+f"(d[18]), "+f"(d[19]), "+f"(d[20]), "+f"(d[21]), "+f"(d[22]), "+f"(d[23]), "+f"(d[24]), "+f"(d[25]), "+f"(d[26]), "+f"(d[27]), "+f"(d[28]), "+f"(d[29]), "+f"(d[30]), "+f"(d[31]), "+f"(d[32]), "+f"(d[33]), "+f"(d[34]), "+f"(d[35]), "+f"(d[36]), "+f"(d[37]), "+f"(d[38]), "+f"(d[39]), "+f"(d[40]), "+f"(d[41]), "+f"(d[42]), "+f"(d[43]), "+f"(d[44]), "+f"(d[45]), "+f"(d[46]), "+f"(d[47]), "+f"(d[48]), "+f"(d[49]), "+f"(d[50]), "+f"(d[51]), "+f"(d[52]), "+f"(d[53]), "+f"(d[54]), "+f"(d[55]), "+f"(d[56]), "+f"(d[57]), "+f"(d[58]), "+f"(d[59]), "+f"(d[60]), "+f"(d[61]), "+f"(d[62]), "+f"(d[63]), "+f"(d[64]), "+f"(d[65]), "+f"(d[66]), "+f"(d[67]), "+f"(d[68]), "+f"(d[69]), "+f"(d[70]), "+f"(d[71]), "+f"(d[72]), "+f"(d[73]), "+f"(d[74]), "+f"(d[75]), "+f"(d[76]), "+f"(d[77]), "+f"(d[78]), "+f"(d[79]), "+f"(d[80]), "+f"(d[81]), "+f"(d[82]), "+f"(d[83]), "+f"(d[84]), "+f"(d[85]), "+f"(d[86]), "+f"(d[87]), "+f"(d[88]), "+f"(d[89]), "+f"(d[90]), "+f"(d[91]), "+f"(d[92]), "+f"(d[93]), "+f"(d[94]), "+f"(d[95])
        : "r"(a0), "r"(a1), "r"(a2), "r"(a3), "l"(db), "r"(acc));
}

#define TRD(t, i)
namespace km {
#define NSS 6
#define RG "184"
#define RW "136"
#define NFL 2
#define EK 7
#define FK 3
#define LDP 3
#define SND 1
constexpr int O_H = 0;
constexpr int O_MB = 73728;
constexpr int O_VX = 96768;
constexpr int O_KX = 113152;
constexpr int O_QX = 119296;
constexpr int O_VM = 125440;
constexpr int O_KM = 129536;
constexpr int O_QM = 131072;
constexpr int O_SM = 132608;
constexpr int O_ST = 135168;
constexpr int O_OX = 145408;
constexpr int O_WO = 149504;
constexpr int O_OS = O_WO;
constexpr int O_WS = O_WO + 49152;
constexpr int O_RL = 110592;
constexpr int O_BAR = O_WS + NSS * 4096;
constexpr int SMEM = O_BAR + 128 + 1024 + TR_BYTES;
enum { B_X = 0, B_WIN = 16, B_VX = 24, B_SM = 32, B_ST = 40, B_EP = 56 };
#define DLY1 (tune.v[0] + tune.v[4] * w)
#define DLY2 tune.v[1]
#define EARLY tune.v[2]
#define DLYO tune.v[3]
#define DLY0 tune.v[5]
#define DLYX tune.v[6]
#define DLYP tune.v[7]
#define DLYW tune.v[8]
#define DLYB tune.v[9]
constexpr uint32_t DESC_HI = (1024 >> 4) | (1u << 30);
constexpr float SC = 0.08838834764831845f * 1.4426950408889634f;
}

__global__ void __cluster_dims__(3, 1, 1) __launch_bounds__(384, 1)
k_main(const __nv_bfloat16* __restrict__ x0, const __nv_bfloat16* __restrict__ wqkv, const __nv_bfloat16* __restrict__ wo,
       const __nv_bfloat16* __restrict__ mem0, const __nv_bfloat16* __restrict__ Wq, const __nv_bfloat16* __restrict__ Wk,
       const __nv_bfloat16* __restrict__ Wv, const __nv_bfloat16* __restrict__ Wo, const Tune tune) {
    using namespace km;
    extern __shared__ unsigned char smem_raw[];
    const uint32_t sb = (smem_u32(smem_raw) + 1023) & ~1023u;
    const int tid = threadIdx.x, lane = tid & 31, warp = __shfl_sync(~0u, tid >> 5, 0);
    uint32_t l16 = __shfl_sync(~0u, lane * 16, lane);
#define OPQ() asm volatile("" : "+r"(l16))
    const int b = blockIdx.x, h = b / 3, r = b % 3;
    const int nq = r == 2 ? 2 : 3;
    const uint32_t bar = sb + O_BAR;
    asm volatile("griddepcontrol.launch_dependents;");
    const uint32_t t_start = clk();
    if (warp == 0 && b < 72) {
        if (lane == 0) { mbar_init(bar + 96, 1); fence_async_smem(); mbar_expect(bar + 96, 8 * 3456, true); }
        __syncwarp();
        if (lane < 8) asm volatile("cp.async.bulk.shared::cluster.global.mbarrier::complete_tx::bytes [%0], [%1], 3456, [%2];" :: "r"(sb + O_RL + lane * 3472), "l"(wqkv + (b * 8 + lane) * 1728), "r"(bar + 96) : "memory");
    }
    if (tid == 352) {
        prefetch_l2(x0 + b * (2 * DM), 2 * 1152); prefetch_l2(wo + b * (6 * DM), 6 * 1152);
    }
    if (tid == 320) sts32(bar + 64, ldg32(&g_epoch));
#define EP lds32(bar + 64)
    TR_INIT(bar + 128);
    TRG(79, 0);
    uint32_t roff0, roff1;
    {
        uint32_t y0, y1;
        asm("mapa.shared::cluster.u32 %0, %1, %2;" : "=r"(y0) : "r"(sb), "r"((r + 1) % 3));
        asm("mapa.shared::cluster.u32 %0, %1, %2;" : "=r"(y1) : "r"(sb), "r"((r + 2) % 3));
        roff0 = y0 - sb; roff1 = y1 - sb;
    }
#define IDENT (((l16 >> 7) == ((l16 >> 4) & 3) ? 0x3f80u : 0u) << ((l16 >> 2) & 16))
#define LSWAP ((l16 & 0x70) | ((l16 & 0x80) << 1) | ((l16 & 0x100) >> 1))
    const uint32_t nv_remote = 8 - (8 - 2 * nq);

    auto fetch_tile = [&](int u) {
        fence_async_global();
        TRG(u, 0);
        const bool a0 = u < NSEG, a1 = u >= LAG;
        mbar_expect(bar + B_X, ((int)a0 + (int)a1) * 36864, l16 == 0);
        const uint32_t off = r * 24576 + (l16 << 9) + (a0 ? 0 : 4096);
        asm volatile("{.reg .pred p; setp.lt.u32 p, %5, %6;\n"
            "@p cp.async.bulk.shared::cluster.global.mbarrier::complete_tx::bytes.multicast::cluster [%0], [%1], %4, [%2], %3;}"
            :: "r"(sb + O_H + off), "l"(reinterpret_cast<const char*>(g_xt + u * 4608) + off), "r"(bar + B_X), "h"((uint16_t)7),
               "r"(a0 && a1 ? 24576 : 4096), "r"(l16), "r"(a0 && a1 ? 16 : 48) : "memory");
    };

    int warp_ = warp;
    asm volatile("" : "+r"(warp_));
    if (warp_ < 8) {
        const int ci = tid & 15, slot = ci >> 1, d0 = tid >> 4;
        const __nv_bfloat16* src = slot < nq ? Wq + (3 * r + slot) * 16 : slot < 2 * nq ? Wk + (3 * r + slot - nq) * 16 : Wv + (2 * r + slot - 2 * nq) * 16;
        src += h * 128 + (ci & 1) * 8 + d0 * 4096;
        if (b < 72) {
            bar_sync(10, 256);
            mbar_wait(bar + 96, 0);
            TR1(4);
#pragma unroll 2
            for (int ag = tid >> 3; ag < 231; ag += 32) {
                const int a = ag / 21, gr = ag % 21, tl = gr >= 18;
                const int head = 3 * a + (tl ? 0 : (gr % 6) >> 1), nw = tl ? min(3, 32 - head) : head < 32 ? 4 : 0;
                const uint32_t p = sb + O_RL + (tid & 7) * 3472 + (tl ? gr - 18 : gr / 6) * 1152 + head * 36 + (tl ? 32 : (gr & 1) * 16), step = tl ? 36 : 4;
                uint32_t v[4];
#pragma unroll
                for (int i = 0; i < 4; i++) { v[i] = lds32(p + i * step); if (i >= nw) v[i] = 0; }
                stg128(g_wa + ((a * 9 + (b >> 3)) * 21 + gr) * 64 + (b & 7) * 8 + (tid & 7), v[0], v[1], v[2], v[3]);
            }
        }
        {
            bar_arrive(15, 288);
            TR1(5);
            delay_until(t_start, DLY0);
            uint32_t dst = sb + d0 * 256 + ((ci ^ (d0 & 7)) << 4);
#pragma unroll 1
            for (int q = 0; q < 12; q++, dst += 12288, src += 3 * 65536) {
#pragma unroll
                for (int i = 0; i < 3; i++) cp16(dst + i * 4096, src + i * 65536);
                cp_commit();
                cp_wait<NFL - 1>();
                if (q == 7) bar_sync(10, 256);
            }
            cp_wait_all();
            bar_sync(10, 256);
        }
        TR1(1);
    }
    if (warp < 8) {
        asm volatile("setmaxnreg.inc.sync.aligned.u32 " RG ";");
        constexpr int SSP = 36 / NSS;
#define IS_SS(kk) ((kk) % SSP == 3)
#define AI(kk) (4 * ((kk) - ((kk) + SSP - 4) / SSP))
        uint32_t a[144 - 4 * NSS];
        {
            const int mi = lane >> 3;
            const uint32_t ad = sb + ((mi >> 1) * 8 + (lane & 7)) * 256 + (((warp * 2 + (mi & 1)) ^ (lane & 7)) << 4);
#pragma unroll
            for (int kk = 0; kk < 36; kk++) {
                const uint4 f = ldsm4t(ad + kk * 4096);
                if (IS_SS(kk)) {
                    const uint32_t o0 = sb + O_WS + (kk / SSP) * 4096 + warp * 512 + lane * 4;
                    sts32(o0, f.x); sts32(o0 + 256, f.y); sts32(o0 + 128, f.z); sts32(o0 + 384, f.w);
                } else { a[AI(kk)] = f.x; a[AI(kk) + 1] = f.y; a[AI(kk) + 2] = f.z; a[AI(kk) + 3] = f.w; }
            }
            TR1(2);
            bar_sync(9, 384);
#pragma unroll
            for (int i = 0; i < 9; i++) sts128(sb + O_H + i * 8192 + 4096 + tid * 16, 0, 0, 0, 0);
#pragma unroll
            for (int i = 0; i < 8; i++) if (i * 256 + tid < (O_OX - O_KX) / 16) sts128(sb + O_KX + i * 4096 + tid * 16, 0, 0, 0, 0);
            fence_async_smem();
            cluster_sync();
        }
        TR1(3);
        const int kind = warp < nq ? 0 : warp < 2 * nq ? 1 : 2;
        const int sl = kind == 0 ? warp : kind == 1 ? warp - nq : 2 * r + warp - 2 * nq;
        const uint32_t adX0 = sb + (kind == 0 ? O_QX : kind == 1 ? O_KX : O_VX) + sl * 2048;
        const uint32_t adM0 = sb + (kind == 0 ? O_QM : kind == 1 ? O_KM : O_VM) + sl * 512;
        const uint32_t hlo = (((sb + O_H) >> 4) & 0x3fff) | (1u << 16);
        const uint32_t mlo = (((sb + O_MB) >> 4) & 0x3fff) | (16u << 16);
        const uint32_t wlo = (((sb + O_WS + (warp >> 2) * 2048) >> 4) & 0x3fff) | (8u << 16);
        const int L = (warp >> 1) & 1, qh = warp & 1;
        const uint32_t st = sb + O_ST + warp * 1280;

#pragma unroll 1
        for (int t = -1;; t++) {
            TR_ON(t);
            OPQ();
            const uint32_t adX = adX0 + l16, adM = adM0 + l16, l8 = l16 >> 1;
            const uint32_t lq = LSWAP;
            if (t >= 0) {
                float d0[8], d1[8];
                {
#pragma unroll
                    for (int G = 0; G < 3; G++) {
                        if (warp < 4) bar_sync(1 + G, 160); else bar_sync(12 + G, 160);
                        if (G == 0) wg_fence();
#pragma unroll
                        for (int q = 0; q < 12; q++) {
                            const int kk = 12 * G + q;
                            const uint64_t db = mkdesc(mlo + kk * 32, 8);
                            if (IS_SS(kk)) wgmma_ss16t((kk & 1) ? d1 : d0, mkdesc(wlo + (kk / SSP) * 256, 16), db, 1);
                            else wgmma_rs16t((kk & 1) ? d1 : d0, a[AI(kk)], a[AI(kk) + 1], a[AI(kk) + 2], a[AI(kk) + 3], db, kk >= 2);
                            if (kk == 0) TR(0);
                        }
                    }
                    wg_commit();
                }
#define PM(i) pk(d0[2 * (i)] + d1[2 * (i)], d0[2 * (i) + 1] + d1[2 * (i) + 1])
                if (warp >= 4) {
                    wg_wait<0>();
                    TR(1);
                    const uint32_t p0 = PM(0), p1 = PM(1), p2 = PM(2), p3 = PM(3);
                    if (kind == 2) {
                        sts128(adM, p0, p1, p2, p3);
                        bar_arrive(4, 384);
                        sta128(adM + roff0, p0, p1, p2, p3, bar + B_SM + roff0);
                        sta128(adM + roff1, p0, p1, p2, p3, bar + B_SM + roff1);
                    } else {
                        stsm4t(adM, p0, p1, p2, p3);
                        bar_arrive(4, 384);
                    }
                } else {
                    uint4 q[3], k[3][2];
                    mbar_wait(bar + B_EP, t & 1);
#pragma unroll
                    for (int m = 0; m < LDP; m++) {
                        q[m] = ldsm4(sb + O_QX + m * 2048 + warp * 512 + lq);
                        k[m][0] = ldsm4(sb + O_KX + m * 2048 + L * 1024 + l16); k[m][1] = ldsm4(sb + O_KX + m * 2048 + L * 1024 + 512 + l16);
                    }
                    wg_wait<0>();
                    TR(1);
                    stsm4t(adM, PM(0), PM(1), PM(2), PM(3));
                    bar_arrive(4, 384);
                    sched_fence(gridDim.y, 6);
#pragma unroll
                    for (int m = LDP; m < 3; m++) {
                        q[m] = ldsm4(sb + O_QX + m * 2048 + warp * 512 + lq);
                        k[m][0] = ldsm4(sb + O_KX + m * 2048 + L * 1024 + l16); k[m][1] = ldsm4(sb + O_KX + m * 2048 + L * 1024 + 512 + l16);
                    }
                    float s[5][4];
                    {
                        float y[4] = {0, 0, 0, 0};
#pragma unroll
                        for (int n = 0; n < 5; n++) s[n][0] = s[n][1] = s[n][2] = s[n][3] = 0.f;
#pragma unroll
                        for (int m = 0; m < 3; m++) {
                            mma16(s[0], q[m].x, q[m].y, q[m].z, q[m].w, k[m][0].x, k[m][0].y); mma16(s[1], q[m].x, q[m].y, q[m].z, q[m].w, k[m][0].z, k[m][0].w);
                            mma16(s[2], q[m].x, q[m].y, q[m].z, q[m].w, k[m][1].x, k[m][1].y); mma16(s[3], q[m].x, q[m].y, q[m].z, q[m].w, k[m][1].z, k[m][1].w);
                        }
                        auto send = [&]() {
                            uint32_t w0 = pk(s[0][0], s[0][1]), w1 = pk(s[0][2], s[0][3]), w2 = pk(s[1][0], s[1][1]), w3 = pk(s[1][2], s[1][3]);
                            sta128(st + l16 + 5120 + roff0, w0, w1, w2, w3, bar + B_ST + roff0);
                            sta128(st + l16 + roff1, w0, w1, w2, w3, bar + B_ST + roff1);
                            w0 = pk(s[2][0], s[2][1]); w1 = pk(s[2][2], s[2][3]); w2 = pk(s[3][0], s[3][1]); w3 = pk(s[3][2], s[3][3]);
                            sta128p(st + l16 + 5120 + 512 + roff0, w0, w1, w2, w3, bar + B_ST + roff0, qh);
                            sta128p(st + l16 + 512 + roff1, w0, w1, w2, w3, bar + B_ST + roff1, qh);
                        };
                        sched_fence(gridDim.y, 7);
                        bar_sync(5, 256);
                        const uint4 k01 = ldsm4(sb + O_KM + L * 256 + l16 + (l16 & 256));
                        const uint2 k2 = ldsm2(sb + O_KM + 1024 + L * 256 + l16);
                        if (SND == 0) send();
                        mma16(s[4], q[0].x, q[0].y, q[0].z, q[0].w, k01.x, k01.y);
                        mma16(y, q[1].x, q[1].y, q[1].z, q[1].w, k01.z, k01.w);
                        mma16(s[4], q[2].x, q[2].y, q[2].z, q[2].w, k2.x, k2.y);
#pragma unroll
                        for (int j = 0; j < 4; j++) s[4][j] += y[j];
                        const uint32_t w0 = pk(s[4][0], s[4][1]), w1 = pk(s[4][2], s[4][3]);
                        sta64(st + l8 + 5120 + 1024 + roff0, w0, w1, bar + B_ST + roff0);
                        sta64(st + l8 + 1024 + roff1, w0, w1, bar + B_ST + roff1);
                        if (SND == 1) send();
                        TR(2);
                        const int lim = 16 * qh + (int)(l16 >> 6) - (int)((l16 >> 3) & 6);
#pragma unroll
                        for (int n = 0; n < 4; n++)
#pragma unroll
                            for (int j = 0; j < 4; j++) if (!(n == 0 && j >= 2) && 8 * (n - (j >> 1)) + (j & 1) > lim) s[n][j] = -1e30f;
#pragma unroll
                        for (int n = 0; n < 4; n++) asm volatile("" : "+f"(s[n][0]), "+f"(s[n][1]), "+f"(s[n][2]), "+f"(s[n][3]));
                    }
                    uint4 v0[3], v1[3]; uint2 vm[3];
                    const uint32_t vad = sb + O_VX + 3 * r * 2048 + L * 1024 + l16;
#pragma unroll
                    for (int m = 0; m < 3; m++) v0[m] = lds128(vad + m * 2048);
                    const uint32_t otag = ring_tag(t, EP);
                    uint32_t ident = IDENT;
                    asm volatile("" : "+r"(ident));
                    mbar_wait(bar + B_SM, t & 1);
                    mbar_wait(bar + B_ST, t & 1);
                    TR(3);
                    float mx0, mx1;
                    {
                        const uint4 u = lds128(st + l16), v = lds128(st + 512 + l16); const uint2 w = lds64(st + 1024 + l8);
                        const uint4 x = lds128(st + 5120 + l16), y = lds128(st + 5120 + 512 + l16); const uint2 z = lds64(st + 5120 + 1024 + l8);
                        mma8(s[0], u.x, u.y, ident); mma8(s[1], u.z, u.w, ident); mma8(s[2], v.x, v.y, ident); mma8(s[3], v.z, v.w, ident); mma8(s[4], w.x, w.y, ident);
                        mma8(s[0], x.x, x.y, ident); mma8(s[1], x.z, x.w, ident); mma8(s[2], y.x, y.y, ident); mma8(s[3], y.z, y.w, ident); mma8(s[4], z.x, z.y, ident);
                        mx0 = fmaxf(fmaxf(fmaxf(s[0][0], s[0][1]), fmaxf(s[1][0], s[1][1])), fmaxf(fmaxf(s[2][0], s[2][1]), fmaxf(s[3][0], s[3][1])));
                        mx1 = fmaxf(fmaxf(fmaxf(s[0][2], s[0][3]), fmaxf(s[1][2], s[1][3])), fmaxf(fmaxf(s[2][2], s[2][3]), fmaxf(s[3][2], s[3][3])));
                        mx0 = fmaxf(mx0, fmaxf(s[4][0], s[4][1])); mx1 = fmaxf(mx1, fmaxf(s[4][2], s[4][3]));
                    }
#pragma unroll
                    for (int o = 1; o < 4; o <<= 1) { const float2 z = shfl2(mx0, mx1, o); mx0 = fmaxf(mx0, z.x); mx1 = fmaxf(mx1, z.y); }
                    mx0 *= -SC; mx1 *= -SC;
                    float l[4] = {0, 0, 0, 0};
                    uint32_t p[10];
#pragma unroll
                    for (int n = 0; n < 5; n++) {
                        const float e0 = ex2(fmaf(s[n][0], SC, mx0)), e1 = ex2(fmaf(s[n][1], SC, mx0));
                        const float e2 = ex2(fmaf(s[n][2], SC, mx1)), e3 = ex2(fmaf(s[n][3], SC, mx1));
                        p[2 * n] = pk(e0, e1); p[2 * n + 1] = pk(e2, e3);
                        mma8(l, p[2 * n], p[2 * n + 1], 0x3f803f80);
                    }
#pragma unroll
                    for (int m = 0; m < 3; m++) vm[m] = lds64(sb + O_VM + (3 * r + m) * 512 + l16 + L * 8);
                    sched_fence(gridDim.y, 5);
                    const float l0 = rcp(l[0]), l1 = rcp(l[2]);
                    float o[6][4];
#pragma unroll
                    for (int m = 0; m < 6; m++) o[m][0] = o[m][1] = o[m][2] = o[m][3] = 0.f;
#pragma unroll
                    for (int m = 0; m < 3; m++) { mma8(o[2 * m], p[0], p[1], v0[m].x); mma8(o[2 * m + 1], p[0], p[1], v0[m].y); }
#pragma unroll
                    for (int m = 0; m < 3; m++) { mma8(o[2 * m], p[2], p[3], v0[m].z); mma8(o[2 * m + 1], p[2], p[3], v0[m].w); v1[m] = lds128(vad + m * 2048 + 512); }
#pragma unroll
                    for (int m = 0; m < 3; m++) { mma8(o[2 * m], p[8], p[9], vm[m].x); mma8(o[2 * m + 1], p[8], p[9], vm[m].y); }
#pragma unroll
                    for (int m = 0; m < 3; m++) { mma8(o[2 * m], p[4], p[5], v1[m].x); mma8(o[2 * m + 1], p[4], p[5], v1[m].y); }
#pragma unroll
                    for (int m = 0; m < 3; m++) { mma8(o[2 * m], p[6], p[7], v1[m].z); mma8(o[2 * m + 1], p[6], p[7], v1[m].w); }
                    sched_fence(gridDim.y, 8);
                    if (t + 1 < NT) bar_arrive(11, 384);
#pragma unroll
                    for (int m = 0; m < 3; m++)
                        sts128(sb + O_OS + warp * 512 + m * 2048 + l16, (pk(o[2 * m][0] * l0, o[2 * m][1] * l0) & ~1u) | otag, pk(o[2 * m][2] * l1, o[2 * m][3] * l1),
                               pk(o[2 * m + 1][0] * l0, o[2 * m + 1][1] * l0), pk(o[2 * m + 1][2] * l1, o[2 * m + 1][3] * l1));
                    TR(4);
                }
            }
            if (t + 1 >= NT) break;
            {
                float d[32];
                if (warp < 4) { if (t < 0) mbar_wait(bar + B_X, 0); bar_sync(7, 256); }
                else {
                    if (warp == 7) {
                        if (t >= 0) { mbar_wait(bar + B_EP, t & 1); mbar_wait(bar + B_VX, t & 1); }
                        if (__shfl_sync(~0u, lds_acq(bar + 8), 0) != t + 1) cnt_wait(g_cnt + (C_X + t + 1) * 8, 64 * (EP + 1));
                        else if (DLYX) pause(DLYX);
                        fetch_tile(t + 1);
                        TR(2);
                    }
                    mbar_wait(bar + B_X, (t + 1) & 1);
                    TR(3);
                    if (t >= 0) bar_sync(11, 384);
                }
                wg_fence();
                TR(6);
#pragma unroll
                for (int kk = 0; kk < 36; kk++) {
                    const uint64_t db = mkdesc(hlo + ((kk >> 2) * 8192 + (kk & 3) * 32) / 16, DESC_HI);
                    if (IS_SS(kk)) wgmma_ss64(d, mkdesc(wlo + (kk / SSP) * 256, 16), db, 1);
                    else wgmma_rs64(d, a[AI(kk)], a[AI(kk) + 1], a[AI(kk) + 2], a[AI(kk) + 3], db, kk > 0);
                }
                wg_commit();
                TR(5);
                mbar_wait(bar + B_WIN, (t + 1) & 1);
                wg_wait<0>();
                TR(7);
                uint32_t p[16];
#pragma unroll
                for (int u = 0; u < 16; u++) p[u] = pk(d[2 * u], d[2 * u + 1]);
                if (kind == 2) {
#pragma unroll
                    for (int u = 0; u < 4; u++) sts128(adX + u * 512, p[4 * u], p[4 * u + 1], p[4 * u + 2], p[4 * u + 3]);
                } else {
#pragma unroll
                    for (int u = 0; u < 4; u++) stsm4t(adX + u * 512, p[4 * u], p[4 * u + 1], p[4 * u + 2], p[4 * u + 3]);
                }
                __syncwarp();
                asm volatile("{.reg .pred p; setp.eq.u32 p, %1, 0; @p mbarrier.arrive.shared.b64 _, [%0];}" :: "r"(bar + B_EP), "r"(l16) : "memory");
                TR(8);
            }
        }
        if (warp < 4) bar_arrive(7, 160);
        cluster_sync();
    } else {
        asm volatile("setmaxnreg.dec.sync.aligned.u32 " RW ";");
        const int w = warp - 8, t2 = tid - 256;
        if (t2 == 0) {
            mbar_init(bar + B_X, 1); sts32(bar + 8, ~0u); mbar_init(bar + B_WIN, 3);
            mbar_init(bar + B_VX, 1); mbar_init(bar + B_SM, 1); mbar_init(bar + B_ST, 1); mbar_init(bar + B_EP, 8);
            asm volatile("fence.mbarrier_init.release.cluster;" ::: "memory");
        }
        char* const ex = reinterpret_cast<char*>((reinterpret_cast<uintptr_t>(g_ex) + 0x1fffff) & ~(uintptr_t)0x1fffff);
        char* rbase = ex; uint32_t side = 0;
        {
            uint32_t m0[5][4];
#pragma unroll
            for (int i = 0; i < 5; i++) {
                const unsigned short* m = reinterpret_cast<const unsigned short*>(mem0) + min(i * 128 + t2, DM - 1);
#pragma unroll
                for (int j = 0; j < 4; j++) m0[i][j] = m[2 * j * DM] | (m[(2 * j + 1) * DM] << 16);
            }
            if (w == 3) { bar_sync(15, 288); cnt_add(g_cnt + C_W * 8, lane); TR1(1); }
            else {
                if (w < 2) {
                    unsigned* pp = reinterpret_cast<unsigned*>(ex + inbox_off(b) + 16384 + w * 4096 + 2048);
                    uint32_t best = ~0u, v = 0;
                    if (lane == 0) {
#pragma unroll 1
                        for (int i = 0; i < 5; i++) {
                            const uint32_t c0 = clk();
                            v = atomicAdd(pp + (v >> 31), 0);
                            asm volatile("" :: "r"(v) : "memory");
                            sts32(bar + 80, v);
                            best = min(best, clk() - c0);
                        }
                        sts32(bar + 72 + w * 4, best);
                    }
                }
                bar_sync(8, 96);
                const uint32_t xs = lds32(bar + 76) < lds32(bar + 72), ep = EP;
                side = xs ^ page_par(inbox_off(b));
                rbase = ex + inbox_off(b) + xs * 4096;
                const uint32_t inv = (ep * (NT - 1)) & 1;
#pragma unroll
                for (int i = 0; i < 4; i++) stg128(rbase + (w == 2 ? 16384 : w * 2048) + i * 512 + lane * 16, inv, 0, 0, 0);
                __threadfence();
                bar_sync(8, 96);
                if (t2 == 0) stg_word(g_side + b, (ep + 1) * 2 + xs, true);
                TR1(4);
            }
            delay_until(t_start, DLYW);
#pragma unroll 4
            for (int i = t2; i < 128 * 24; i += 128) {
                const int e = (i >> 3) & 127, G = i >> 10, q = i & 7;
                cp16(sb + O_WO + G * 16384 + e * 128 + ((q ^ (e & 7) ^ ((h >> 1) & 1)) << 4), Wo + (size_t)(h * 128 + e) * DM + G * 192 + r * 64 + q * 8);
            }
            bar_sync(9, 384);
#pragma unroll
            for (int i = 0; i < 5; i++) {
                const int k = min(i * 128 + t2, DM - 1);
                const uint32_t ad = sb + O_MB + (k >> 3) * 256 + (k & 7) * 16;
                sts128(ad, m0[i][0], m0[i][1], m0[i][2], m0[i][3]); sts128(ad + 128, m0[i][0], m0[i][1], m0[i][2], m0[i][3]);
            }
            fence_async_smem();
        }
        auto arm = [&]() {
            const uint32_t ln = l16 >> 4;
            mbar_expect(bar + B_VX + (ln & 3) * 8, ln == 0 ? nv_remote * 2048 : ln == 1 ? nv_remote * 512 + 2560 : 8192, ln < 3);
        };
        if (w == 3) arm();
        cluster_sync();
        TR1(3);
        const int L = w >> 1, hf = w & 1;
        const uint32_t rd = hf ? roff1 : roff0;
        const uint32_t rzero = gridDim.y + 100;
#define WOAD (sb + O_WO + ((l16 & 0x100) << 2) + ((l16 & 0x70) << 3) + (((w * 32) | ((l16 >> 3) & 16)) ^ (l16 & 0x70)))

        auto store_o = [&](int u) {
            asm volatile("{.reg .pred p; setp.eq.u32 p, %3, 0;\n"
                "@p cp.async.bulk.global.shared::cta.bulk_group [%0], [%1], %2;\n cp.async.bulk.commit_group;}"
                :: "l"(g_o + ((u & (RING - 1)) * 256 + h * 8 + 3 * r) * 128), "r"(sb + O_OS), "r"(nq * 2048), "r"(l16) : "memory");
            cnt_hint(g_cnt + (C_O + u * 8 + (h >> 2)) * 8, l16);
            TRG(u, 2);
        };
        bar_arrive(7, 256);
        if (w < 3) {
            bar_arrive(1 + w, 160); bar_arrive(12 + w, 160);
        } else {
            mbar_arrive_all3(bar + B_WIN, l16 >> 4);

        }
        cp_wait_all();
        bar_sync(6, 128);
        uint32_t poff;
        {
            const int rb = r * 32 + w * 8 + (lane >> 2);
            const uint32_t want = EP + 1;
            uint32_t v;
            for (int n = 0; __any_sync(~0u, ((v = ldg_word(g_side + rb)) >> 1) != want); n++) fault_if(n > POLL_LIMIT, n);
            __threadfence();
            poff = inbox_off(rb) + (v & 1) * 4096 + h * 64 + (lane & 3) * 16;
        }
        side = __shfl_sync(~0u, side, 0);
        const uint32_t roff = __shfl_sync(~0u, (uint32_t)(rbase - ex), 0) + (w == 2 ? 16384 : (w & 1) * 2048);
        uint4 a0[8];
#pragma unroll
        for (int kk = 0; kk < 8; kk++) a0[kk] = ldsm4t(WOAD + kk * 2048);
#pragma unroll 1
        for (int t = 0;; t++) {
            TR_ON(t);
            OPQ();
            mbar_wait(bar + B_EP, t & 1);
            if (w == 3) {
                fence_async_smem();
                const uint32_t ad = sb + O_VX + r * 4096;
                asm volatile("{.reg .pred p; setp.eq.u32 p, %5, 0;\n"
                    "@p cp.async.bulk.shared::cluster.shared::cta.mbarrier::complete_tx::bytes [%0], [%2], %6, [%3];\n"
                    "@p cp.async.bulk.shared::cluster.shared::cta.mbarrier::complete_tx::bytes [%1], [%2], %6, [%4];}"
                    :: "r"(ad + roff0), "r"(ad + roff1), "r"(ad), "r"(bar + B_VX + roff0), "r"(bar + B_VX + roff1), "r"(l16), "r"(16384 - 4096 * nq) : "memory");
                TR(7);
            }
            uint4 kx[3][2], vx[4][2];
            const uint32_t lp = LSWAP;
#pragma unroll
            for (int m = 0; m < 3; m++) {
                kx[m][0] = ldsm4(sb + O_KX + m * 2048 + L * 1024 + lp);
                kx[m][1] = ldsm4(sb + O_KX + m * 2048 + L * 1024 + 512 + lp);
            }
            if (w == 3) {
                asm volatile("cp.async.bulk.wait_group.read 0;" ::: "memory");
                if (__shfl_sync(~0u, lds32(bar + 8), 0) != t + 1) cnt_look(g_cnt + (C_X + t + 1) * 8, 64 * (EP + 1), bar + 8, t + 1);
            }
            mbar_wait(bar + B_VX, t & 1);
            TR(0);
            bar_sync(4, 384);
            float s0[4] = {0, 0, 0, 0}, s1[4] = {0, 0, 0, 0}, sm[4] = {0, 0, 0, 0};
            {
                const uint4 q01 = ldsm4(sb + O_QM + L * 256 + l16 + (l16 & 256));
                const uint2 q2 = ldsm2(sb + O_QM + 1024 + L * 256 + l16);
                uint4 km_[3];
#pragma unroll
                for (int m = 0; m < 3; m++) km_[m] = ldsm4(sb + O_KM + m * 512 + (lp ^ (L << 8)));
                mma16(s0, kx[0][0].x, kx[0][0].y, kx[0][0].z, kx[0][0].w, q01.x, q01.y);
                mma16(s1, kx[0][1].x, kx[0][1].y, kx[0][1].z, kx[0][1].w, q01.x, q01.y);
                mma16(sm, km_[0].x, km_[0].y, km_[0].z, km_[0].w, q01.x, q01.y);
                mma16(s0, kx[1][0].x, kx[1][0].y, kx[1][0].z, kx[1][0].w, q01.z, q01.w);
                mma16(s1, kx[1][1].x, kx[1][1].y, kx[1][1].z, kx[1][1].w, q01.z, q01.w);
                mma16(sm, km_[1].x, km_[1].y, km_[1].z, km_[1].w, q01.z, q01.w);
                bar_arrive(5 + (__float_as_uint(s0[0]) & (rzero - 101)), 256);
                mma16(s0, kx[2][0].x, kx[2][0].y, kx[2][0].z, kx[2][0].w, q2.x, q2.y);
                mma16(s1, kx[2][1].x, kx[2][1].y, kx[2][1].z, kx[2][1].w, q2.x, q2.y);
                mma16(sm, km_[2].x, km_[2].y, km_[2].z, km_[2].w, q2.x, q2.y);
                const uint32_t ad = sb + O_SM + (1 - hf) * 1280 + L * 640 + rd;
                sta128(ad + l16, pk(s0[0], s0[1]), pk(s0[2], s0[3]), pk(s1[0], s1[1]), pk(s1[2], s1[3]), bar + B_SM + rd);
                sta32(ad + 512 + (l16 >> 2), pk(sm[0], sm[1]), bar + B_SM + rd);
            }
            TR(1);
            if (t + 1 == NT) break;
#pragma unroll
            for (int m = 0; m < 8; m++) vx[m >> 1][m & 1] = lds128(sb + O_VX + (hf * 4 + (m >> 1)) * 2048 + L * 1024 + (m & 1) * 512 + l16);
            const uint32_t tag = (t + EP * (NT - 1) + 1) & 1;
            uint32_t ident = IDENT;
            asm volatile("" : "+r"(ident));
            mbar_wait(bar + B_SM, t & 1);
            TR(2);
            {
                const uint32_t ad = sb + O_SM + L * 640;
                const uint4 u = lds128(ad + l16), v = lds128(ad + 1280 + l16);
                const uint32_t x = lds32(ad + 512 + (l16 >> 2)), y = lds32(ad + 1280 + 512 + (l16 >> 2));
                mma8(s0, u.x, u.y, ident); mma8(s1, u.z, u.w, ident); mma8(s0, v.x, v.y, ident); mma8(s1, v.z, v.w, ident);
                sm[0] += bf_lo(x) + bf_lo(y); sm[1] += bf_hi(x) + bf_hi(y);
            }
            uint2 vm[4];
#pragma unroll
            for (int m = 0; m < 4; m++) vm[m] = lds64(sb + O_VM + (hf * 4 + m) * 512 + l16 + L * 8);
            float mx0 = fmaxf(fmaxf(fmaxf(s0[0], s0[2]), fmaxf(s1[0], s1[2])), sm[0]);
            float mx1 = fmaxf(fmaxf(fmaxf(s0[1], s0[3]), fmaxf(s1[1], s1[3])), sm[1]);
#pragma unroll
            for (int o = 4; o < 32; o <<= 1) { mx0 = fmaxf(mx0, __shfl_xor_sync(~0u, mx0, o)); mx1 = fmaxf(mx1, __shfl_xor_sync(~0u, mx1, o)); }
            mx0 *= -SC; mx1 *= -SC;
            s0[0] = ex2(fmaf(s0[0], SC, mx0)); s0[1] = ex2(fmaf(s0[1], SC, mx1));
            s0[2] = ex2(fmaf(s0[2], SC, mx0)); s0[3] = ex2(fmaf(s0[3], SC, mx1));
            const uint32_t pb0 = movm(pk(s0[0], s0[1])), pb1 = movm(pk(s0[2], s0[3]));
            s1[0] = ex2(fmaf(s1[0], SC, mx0)); s1[1] = ex2(fmaf(s1[1], SC, mx1));
            s1[2] = ex2(fmaf(s1[2], SC, mx0)); s1[3] = ex2(fmaf(s1[3], SC, mx1));
            const uint32_t pb2 = movm(pk(s1[0], s1[1])), pb3 = movm(pk(s1[2], s1[3]));
            sm[0] = ex2(fmaf(sm[0], SC, mx0)); sm[1] = ex2(fmaf(sm[1], SC, mx1));
            const uint32_t pm = movm(pk(sm[0], sm[1]));
            float o[4][4], l[4] = {0, 0, 0, 0};
            const uint32_t one = 0x3f803f80;
            mma8(l, one, one, pb0); mma8(l, one, one, pb1);
#pragma unroll
            for (int m = 0; m < 4; m++) { o[m][0] = o[m][1] = o[m][2] = o[m][3] = 0.f; mma16(o[m], vx[m][0].x, vx[m][0].y, vx[m][0].z, vx[m][0].w, pb0, pb1); }
            mma8(l, one, one, pb2); mma8(l, one, one, pb3);
#pragma unroll
            for (int m = 0; m < 4; m++) mma16(o[m], vx[m][1].x, vx[m][1].y, vx[m][1].z, vx[m][1].w, pb2, pb3);
            mma8(l, one, one, pm);
#pragma unroll
            for (int m = 0; m < 4; m++) mma8(o[m], vm[m].x, vm[m].y, pm);
            const float l0 = rcp(l[0]), l1 = rcp(l[1]);
#pragma unroll
            for (int m = 0; m < 4; m += 2)
                stsm4t(sb + O_OX + (hf * 4 + m) * 512 + (L ^ ((h >> 2) & 1)) * 256   + ((l16 & 0x100) << 1) + (l16 & 0xf0),
                       pk(o[m][0] * l0, o[m][1] * l1), pk(o[m][2] * l0, o[m][3] * l1), pk(o[m + 1][0] * l0, o[m + 1][1] * l1), pk(o[m + 1][2] * l0, o[m + 1][3] * l1));
            TR(3);
            char* const pdst = ex + poff;
            const char* const rsrc = ex + roff + l16;
            uint4 v[4] = {};
            bar_sync(6, 128);
            {
                uint4 bo[8], a1[8], z;
                const uint32_t wad = WOAD;
#pragma unroll
                for (int kk = 0; kk < 8; kk++) bo[kk] = ldsm4(sb + O_OX + kk * 512 + l16);
#pragma unroll
                for (int G = 0; G < 3; G++) {
                    float e[4][4];
#pragma unroll
                    for (int q = 0; q < 4; q++) e[q][0] = e[q][1] = e[q][2] = e[q][3] = 0.f;
#pragma unroll
                    for (int kk = 0; kk < 8; kk++) {
                        const uint4 f = G == 0 ? a0[kk] : a1[kk];
                        mma16(e[(kk & 1) * 2], f.x, f.y, f.z, f.w, bo[kk].x, bo[kk].y);
                        mma16(e[(kk & 1) * 2 + 1], f.x, f.y, f.z, f.w, bo[kk].z, bo[kk].w);
                        if (G == 2 && kk == EK) {
#pragma unroll
                            for (int i = 0; i < 4; i++) { v[i].x = ~tag; ldg_pkt_if(v[i], rsrc + i * 512, w < EARLY); }
                            sched_fence(rzero, 5);
                            bar_arrive(11, 384);
                        }
                        if (G == 1) a1[kk] = ldsm4t(wad + 32768 + kk * 2048);
                        if (G == 0 && kk == FK) {
                            sched_fence(rzero, 2);
#pragma unroll
                            for (int j = 0; j < 8; j++) a1[j] = ldsm4t(wad + 16384 + j * 2048);
                        }
                    }
                    if (G > 0) asm volatile("{.reg .pred p; setp.eq.u32 p, %5, 0; @p st.shared.v4.u32 [%0], {%1,%2,%3,%4};}" :: "r"(__float_as_uint(e[0][0])), "r"(z.x), "r"(z.y), "r"(z.z), "r"(z.w), "r"(rzero));
                    z = make_uint4((pk(e[0][0] + e[2][0], e[0][1] + e[2][1]) & ~1u) | tag, pk(e[0][2] + e[2][2], e[0][3] + e[2][3]),
                                   pk(e[1][0] + e[3][0], e[1][1] + e[3][1]), pk(e[1][2] + e[3][2], e[1][3] + e[3][3]));
                    stg_pkt(pdst + (G == 2 ? 16384 : G * 2048), z.x, z.y, z.z, z.w);
                    if (G == 0) { TR(9); TRD(t, 0); }
                    if (G < 2) sched_fence(rzero, 3 + G);
                }
            }
            TR(4);
            if (w < 3) {
                bar_arrive(7, 256);
                OPQ();
                const uint32_t tagm = tag;
                uint32_t m0v = 0;
                if (t + 1 <= LAG) {
                    const unsigned short* m = reinterpret_cast<const unsigned short*>(mem0) + ((l16 >> 3) & 6) * DM + 192 * w + 16 * (b >> 3) + (b & 7) + ((l16 >> 4) & 8);
                    m0v = m[0] | (m[DM] << 16);
                }
                if (DLY1) pause(DLY1);
                for (int n = 0; __any_sync(~0u, lop_bad(lop_bad(0, v[0].x, v[1].x, tagm), v[2].x, v[3].x, tagm) & 1); n++) {
#pragma unroll
                    for (int i = 0; i < 4; i++) ldg_pkt_retry(v[i], rsrc + i * 512, tagm);
                    fault_if(n > POLL_LIMIT, n);
                }
                TR(5); TRD(t, 1);
                float s[8];
                s[4] = (bf_lo(v[0].z) + bf_lo(v[1].z)) + (bf_lo(v[2].z) + bf_lo(v[3].z)); s[5] = (bf_hi(v[0].z) + bf_hi(v[1].z)) + (bf_hi(v[2].z) + bf_hi(v[3].z));
                s[6] = (bf_lo(v[0].w) + bf_lo(v[1].w)) + (bf_lo(v[2].w) + bf_lo(v[3].w)); s[7] = (bf_hi(v[0].w) + bf_hi(v[1].w)) + (bf_hi(v[2].w) + bf_hi(v[3].w));
                s[2] = (bf_lo(v[0].y) + bf_lo(v[1].y)) + (bf_lo(v[2].y) + bf_lo(v[3].y)); s[3] = (bf_hi(v[0].y) + bf_hi(v[1].y)) + (bf_hi(v[2].y) + bf_hi(v[3].y));
                s[0] = (bf_lo(v[0].x) + bf_lo(v[1].x)) + (bf_lo(v[2].x) + bf_lo(v[3].x)); s[1] = (bf_hi(v[0].x) + bf_hi(v[1].x)) + (bf_hi(v[2].x) + bf_hi(v[3].x));
#pragma unroll
                for (int j = 0; j < 4; j++) s[j] += __shfl_xor_sync(~0u, s[j + 4], 16);
#pragma unroll
                for (int j = 0; j < 2; j++) s[j] += __shfl_xor_sync(~0u, s[j + 2], 8);
#pragma unroll
                for (int j = 0; j < 2; j++) s[j] += __shfl_xor_sync(~0u, s[j], 4);
                char* const mem_w = ex + mem_off(w, 0);
                uint32_t res = t + 1 <= LAG && l16 >= 256 ? m0v : pk(s[0], s[1]);
                if ((l16 & 48) == 0) res = (res & ~1u) | tag;
                char* const pub = mem_w + (mem_off(0, b >> 3) - mem_off(0, 0)) + (b & 7) * 16 + (((l16 & 64) << 6) + ((l16 & 128) << 1) + ((l16 & 256) >> 1) + ((l16 >> 2) & 12));
                stg_word(pub, res, true);
                TR(6); TRD(t, 2);
                pause(DLY2);
                const char* src = mem_w + (side ^ page_par(0x180000)) * 4096 + l16;
                const uint32_t gdst = sb + O_MB + w * 6144 + l16;
                uint4 x[12];
#pragma unroll
                for (int i = 0; i < 12; i++) x[i] = ldg_pkt(src + (mem_off(0, i) - mem_off(0, 0)));
                for (int n = 0;; n++) {
                    uint32_t bad = 0;
#pragma unroll
                    for (int i = 0; i < 12; i += 2) bad = lop_bad(bad, x[i].x, x[i + 1].x, tagm);
                    if (!__any_sync(~0u, bad & 1)) break;
#pragma unroll
                    for (int i = 0; i < 12; i++) ldg_pkt_retry(x[i], src + (mem_off(0, i) - mem_off(0, 0)), tagm);
                    fault_if(n > POLL_LIMIT, n);
                }
#pragma unroll
                for (int i = 0; i < 12; i++) sts128(gdst + i * 512, x[i].x, x[i].y, x[i].z, x[i].w);
                TR(7); TRD(t, 3);
                fence_async_smem();
                bar_arrive(1 + w, 160);
                bar_arrive(12 + w, 160);
                TR(8);
            } else {
                mbar_wait(bar + B_X, (t + 1) & 1);
                bar_sync(7, 256);
                fence_async_smem();
                arm();
                __syncwarp();
                mbar_arrive_all3(bar + B_WIN, l16 >> 4);
                if (DLYO) pause(DLYO);
                store_o(t);
                pause(DLYP);
                cnt_look(g_cnt + (C_X + t + 2) * 8, 64 * (EP + 1), bar + 8, t + 2);
                __syncwarp();
                TR(5);
            }
        }
        if (w == 3) { bar_sync(7, 160); fence_async_smem(); store_o(NT - 1); asm volatile("cp.async.bulk.wait_group 0;" ::: "memory"); }
        cluster_sync();
    }
    TR_DUMP(b);
}

#define VL 12
#define VP 18
#define VC 19
#define VG 12
#define HB 3
#define HA 2
#define HW 0
namespace ka {
constexpr int O_WA = 196608;
constexpr int A_KB = 21504;
constexpr int O_RING = 194560;
constexpr int O_BAR = 230400;
constexpr int SMEM = O_BAR + 256 + 1024;
constexpr float SC = 0.23570226039551584f * 1.4426950408889634f;
}

template <int NP, int KB = 4096>
DEVI void row_task(const uint4* res, const uint4* part, uint4* xout, char* img, int pos, int lane, uint32_t tag) {
    const bool on = lane < 24;
    const int ln = on ? lane : 0;
    uint4 rv[3], pv[NP > 0 ? NP * 3 : 1];
#pragma unroll
    for (int i = 0; i < 3; i++) rv[i] = ldg128(res + i * 24 + ln);
#pragma unroll
    for (int i = 0; i < NP * 3; i++) pv[i] = ldg_pkt(part + i * 24 + ln);
    if (NP > 0) validate<NP * 3>(pv, part + ln, 384, tag);
#pragma unroll
    for (int q = 0; q < NP * 3 / 2; q++) {
        const uint4 y = pv[q + NP * 3 / 2];
        pv[q] = make_uint4(add2(pv[q].x, y.x), add2(pv[q].y, y.y), add2(pv[q].z, y.z), add2(pv[q].w, y.w));
    }
    float x[24];
    uint32_t w[12];
#pragma unroll
    for (int i = 0; i < 3; i++) {
        x[8 * i] = bf_lo(rv[i].x); x[8 * i + 1] = bf_hi(rv[i].x); x[8 * i + 2] = bf_lo(rv[i].y); x[8 * i + 3] = bf_hi(rv[i].y);
        x[8 * i + 4] = bf_lo(rv[i].z); x[8 * i + 5] = bf_hi(rv[i].z); x[8 * i + 6] = bf_lo(rv[i].w); x[8 * i + 7] = bf_hi(rv[i].w);
    }
    if (NP > 0) {
#pragma unroll
        for (int q = 0; q < NP * 3 / 2; q++) {
            const int i = q % 3;
            x[8 * i] += bf_lo(pv[q].x); x[8 * i + 1] += bf_hi(pv[q].x); x[8 * i + 2] += bf_lo(pv[q].y); x[8 * i + 3] += bf_hi(pv[q].y);
            x[8 * i + 4] += bf_lo(pv[q].z); x[8 * i + 5] += bf_hi(pv[q].z); x[8 * i + 6] += bf_lo(pv[q].w); x[8 * i + 7] += bf_hi(pv[q].w);
        }
#pragma unroll
        for (int j = 0; j < 12; j++) { w[j] = pk(x[2 * j], x[2 * j + 1]); x[2 * j] = bf_lo(w[j]); x[2 * j + 1] = bf_hi(w[j]); }
    }
    if (NP > 0) {
#pragma unroll
        for (int i = 0; i < 3; i++) stg128p(xout + i * 24 + ln, w[4 * i], w[4 * i + 1], w[4 * i + 2], w[4 * i + 3], on);
    }
    if (img) {
        const float x0 = __shfl_sync(~0u, x[0], 0);
        float s4[4] = {0, 0, 0, 0}, v4[4] = {0, 0, 0, 0};
#pragma unroll
        for (int j = 0; j < 24; j++) { x[j] -= x0; s4[j & 3] += x[j]; v4[j & 3] = fmaf(x[j], x[j], v4[j & 3]); }
        float s = on ? (s4[0] + s4[1]) + (s4[2] + s4[3]) : 0.f, v = on ? (v4[0] + v4[1]) + (v4[2] + v4[3]) : 0.f;
#pragma unroll
        for (int o = 1; o < 32; o <<= 1) { const float2 z = shfl2(s, v, o); s += z.x; v += z.y; }
        const float mean = s * (1.f / DM);
        const float rs = rsqrtf(fmaxf(fmaf(-mean, mean, v * (1.f / DM)), 0.f) + 1e-5f), sh = -mean * rs;
#pragma unroll
        for (int j = 0; j < 24; j++) x[j] = fmaf(x[j], rs, sh);
        char* dst = img + (ln >> 3) * KB + pos * 128 + (((ln ^ pos) & 7) << 4);
#pragma unroll
        for (int i = 0; i < 3; i++)
            stg128p(dst + i * (3 * KB), pk(x[8 * i], x[8 * i + 1]), pk(x[8 * i + 2], x[8 * i + 3]),
                    pk(x[8 * i + 4], x[8 * i + 5]), pk(x[8 * i + 6], x[8 * i + 7]), on);
    }
}

DEVI void rows_a(const uint4* xin, int f, int i, int lane, uint32_t ep, int warp) {
    for (int u = 0; u < LAG; u++) cnt_hint(g_cnt + (C_X + u + (f ? 0 : NSEG)) * 8, lane);
#pragma unroll 1
    for (int seg = 0; seg < NSEG; seg++) {
        const int j = seg + f * LAGA, u = seg + f * LAG, row = seg * 32 + i;
        hint_wait(g_cnt + (C_WA + j * 4 + f * 2 + (i & 1)) * 8, 24 * (ep + 1));
        TRG(u, 0);
        row_task<4, 8192>((f ? g_x + 2048 * 72 : xin) + row * 72, g_pa + ((j & (RING - 1)) * 64 + f * 32 + i) * 288,
                    g_x + (f * 4096 + row) * 72, reinterpret_cast<char*>(g_xt + u * 4608 + f * 256), i, lane, ring_tag<NTA>(j, ep));
        TRG(u, 1);
        cnt_add(g_cnt + (C_X + u) * 8, lane);
        TRG(u, 2);
    }
}

__global__ void __launch_bounds__(384, 1)
k_aux(const __nv_bfloat16* __restrict__ x0, const __nv_bfloat16* __restrict__ wqkv, const __nv_bfloat16* __restrict__ wo,
      const __nv_bfloat16* __restrict__ Wo, __nv_bfloat16* __restrict__ out, const Tune tune) {
    using namespace ka;
    extern __shared__ unsigned char smem_raw[];
    const uint32_t sb = (smem_u32(smem_raw) + 1023) & ~1023u;
    const int tid = threadIdx.x, lane = tid & 31, warp = __shfl_sync(~0u, tid >> 5, 0), g = lane >> 2, c = lane & 3;
    const int b = blockIdx.x;
    const uint32_t bar = sb + O_BAR;
    const uint32_t ep_ = ldg32(&g_epoch);

    TRG(79, 0);
    const uint4* xin = reinterpret_cast<const uint4*>(x0);
    if (warp >= 8 || b == 35) {
        asm volatile("setmaxnreg.dec.sync.aligned.u32 128;");
        const int rw = b < 24 ? (warp - 8) * 24 + b : b < 35 ? (warp - 8) * 11 + b - 24 : 128 + 2 * warp;
        if (b < 24 || b == 35 || rw < 32) {
#pragma unroll 1
            for (int row = b < 24 ? rw + 32 : rw; row < 2048; row += (row & 1) ? 23 : 1) {
                if (lane == 0 && b == 35 && row < 2024) prefetch_l2(xin + (row + 24) * 72, 1152);
                row_task<0>(xin + row * 72, nullptr, nullptr, reinterpret_cast<char*>(g_xa + (row >> 5) * 4608), (row & 1) * 16 + ((row & 31) >> 1), lane, 0);
                if (b < 35) { cnt_add(g_cnt + (C_N0 + (row >> 5)) * 8, lane); break; }
                if (row & 1) cnt_add<2>(g_cnt + (C_N0 + (row >> 5)) * 8, lane);
            }
        }
        const uint32_t ep = __shfl_sync(~0u, ep_, 0);
        if (rw < 32) {
            const int f = b < 24, i = rw;
#pragma unroll 1
            for (int seg = 0; seg < NSEG; seg++) {
                const int u = seg + f * LAG, row = seg * 32 + i;
                hint_wait(g_cnt + (C_WB + u * 4 + f * 2 + (i >> 4)) * 8, 24 * (ep + 1));
                TRG(u, 0);
                row_task<8>(g_x + (f * 4096 + row) * 72, g_pb + ((u & (RING - 1)) * 64 + f * 32 + i) * 576,
                            f ? reinterpret_cast<uint4*>(out) + row * 72 : g_x + (2048 + row) * 72,
                            f ? nullptr : reinterpret_cast<char*>(g_xa + (seg + LAGA) * 4608 + 2304), (i & 1) * 16 + (i >> 1), lane, ring_tag(u, ep));
                TRG(u, 1);
                cnt_add(g_cnt + (C_RB + f * NSEG + seg) * 8, lane);
                TRG(u, 2);
            }
            if (f && rw == 31) {
                asm volatile("griddepcontrol.wait;" ::: "memory");
                if (lane == 0) g_epoch = ep + 1;
            }
        } else if (rw < 64 && b < 24) rows_a(xin, 0, rw - 32, lane, ep, warp);
        return;
    }

    if (b < 24) {
        if (warp >= 4) {
            const int kq = b / 6, nq = b % 6;
            uint4 v[17];
#pragma unroll
            for (int q = 0; q < 17; q++) {
                const int it = q * 4 + warp - 4, kr = (it / 3) * 8 + g, s = kq * 11 + (kr >> 4), a = s >> 2, j = s & 3, e = kr & 15;
                const int head = 3 * a + (j < 3 ? j : e >> 1), row = head * 18 + (j < 3 ? e : 16 + (e & 1));
                v[q] = make_uint4(0, 0, 0, 0);
                if (it < 66 && head < 32 && (j < 3 || e < 6)) v[q] = *reinterpret_cast<const uint4*>(wo + row * DM + nq * 96 + (it % 3) * 32 + c * 8);
            }
#pragma unroll
            for (int q = 0; q < 17; q++) {
                const int it = q * 4 + warp - 4;
                const uint32_t ad = sb + O_WA + (it % 3) * 4 * 2816 + (it / 3) * 128 + lane * 4;
                if (it < 66) { sts32(ad, v[q].x); sts32(ad + 2816, v[q].y); sts32(ad + 2 * 2816, v[q].z); sts32(ad + 3 * 2816, v[q].w); }
            }
        } else {
            const int kg = b / 3, ng = b % 3;
            delay(DLYB);
#pragma unroll 1
            for (int bt = 0; bt < 4; bt++) {
                uint4 v[24];
#pragma unroll
                for (int q = 0; q < 24; q++)
                    v[q] = *reinterpret_cast<const uint4*>(Wo + (size_t)(kg * 512 + (bt * 4 + q / 6) * 32 + warp * 8 + g) * DM + ng * 192 + (q % 6) * 32 + c * 8);
#pragma unroll
                for (int q = 0; q < 24; q++) {
                    const uint32_t ad = sb + (q % 6) * 4 * 8192 + ((bt * 4 + q / 6) * 4 + warp) * 128 + lane * 4;
                    sts32(ad, v[q].x); sts32(ad + 8192, v[q].y); sts32(ad + 2 * 8192, v[q].z); sts32(ad + 3 * 8192, v[q].w);
                }
            }
        }
        fence_async_smem();
        bar_sync(2 + (warp >> 2), 128);
    } else {
        for (int i = tid; i < 2048; i += 256) sts128(sb + O_RING + i * 16, 0, 0, 0, 0);
        if (tid < 17) mbar_init(bar + tid * 8, tid >= 4 && tid < 8 ? 4 : 1);
        fence_async_smem();
        bar_sync(1, 256);
    }
    TRG(79, 1);
    const uint32_t ep = __shfl_sync(~0u, ep_, 0);
    const int wq = warp & 3;

    if (warp < 4) {
        asm volatile("setmaxnreg.inc.sync.aligned.u32 256;");
        if (b < 24) {
            const int kg = b / 3, ng = b % 3;
            const uint32_t blo = ((sb >> 4) & 0x3fff) | (8u << 16);
            uint4 a[32];
            uint32_t seen = 0;
            bool pre = false;
#pragma unroll 1
            for (int u = 0; u < NT; u++) {
                const uint32_t tag = ring_tag(u, ep);
                const uint4* src = g_o + (((u & (RING - 1)) * 256 + kg * 32) * 4 + wq) * 32 + lane;
                if (!pre) {
                    if (!__all_sync(~0u, seen >= 12 * (ep + 1))) hint_wait(g_cnt + (C_O + u * 8 + kg) * 8, 12 * (ep + 1));
#pragma unroll
                    for (int i = 0; i < VG; i++) a[i] = ldg_pkt(src + i * 128);
                }
                TRG(u, 0);
                float d[96];
                validate<VG>(a, src, 2048, tag);
                wg_fence();
#pragma unroll
                for (int i = 0; i < 32; i++) {
                    if (i == VL) {
                        if (!pre) {
#pragma unroll
                            for (int j = VG; j < VP; j++) a[j] = ldg_pkt(src + j * 128);
                        }
#pragma unroll
                        for (int j = VP; j < 32; j++) a[j] = ldg_pkt(src + j * 128);
                    }
                    if (i == VG) { validate<32 - VG>(a + VG, src + VG * 128, 2048, tag); wg_fence(); }
                    wgmma_rs192t(d, a[i].x, a[i].y, a[i].z, a[i].w, mkdesc(blo + i * 16, 512), i > 0);
                    if (i == VC - 1 || i == 23 || i == 31) wg_commit();
                }
                const unsigned* cn = g_cnt + (C_O + min(u + 1, NT - 1) * 8 + kg) * 8;
                const uint4* nx = g_o + ((((u + 1) & (RING - 1)) * 256 + kg * 32) * 4 + wq) * 32 + lane;
                auto look = [&]() {
                    pre = __all_sync(~0u, seen >= 12 * (ep + 1));
                    if (pre) {
#pragma unroll
                        for (int i = 0; i < VP; i++) a[i] = ldg_pkt(nx + i * 128);
                    } else seen = ldg_word(cn);
                };
                wg_wait<2>();
                seen = ldg_word(cn);
                wg_wait<1>();
                look();
                wg_wait<0>();
                if (!pre) look();
                TRG(u, 1);
                uint4* dst = g_pb + (((u & (RING - 1)) * 64 + wq * 16 + g) * 8 + kg) * 72 + ng * 24 + c;
#pragma unroll
                for (int m = 0; m < 6; m++) {
                    if (m == HB) cnt_hint(g_cnt + (C_WB + u * 4 + wq) * 8, lane);
                    stg128(dst + 4 * m, (pk(d[16 * m], d[16 * m + 1]) & ~1u) | tag, pk(d[16 * m + 4], d[16 * m + 5]), pk(d[16 * m + 8], d[16 * m + 9]), pk(d[16 * m + 12], d[16 * m + 13]));
                    stg128(dst + 4 * m + 8 * 576, (pk(d[16 * m + 2], d[16 * m + 3]) & ~1u) | tag, pk(d[16 * m + 6], d[16 * m + 7]), pk(d[16 * m + 10], d[16 * m + 11]), pk(d[16 * m + 14], d[16 * m + 15]));
                }
                TRG(u, 3);
            }
        } else {
            const int a = b - 24, f = wq >> 1;
            const uint32_t blo = ((sb >> 4) & 0x3fff) | (8u << 16), alo = (((sb + O_RING) >> 4) & 0x3fff) | (1u << 16);
            const bool m0 = 2 * c <= g, m1 = 2 * c + 1 <= g;
            const uint32_t M = (m0 ? 0xffffu : 0u) | (m1 ? 0xffff0000u : 0u);
            uint32_t kh[7], vh[7];
#pragma unroll
            for (int i = 0; i < 7; i++) kh[i] = vh[i] = 0;
            int it = 0;
#pragma unroll 1
            for (int u = 0; u < NTA; u++) {
                float d[84];
#pragma unroll 1
                for (int kb = 0; kb < 9; kb++, it++) {
                    mbar_wait(bar + (it & 3) * 8, (it >> 2) & 1);
                    if (u == 0) mbar_wait(bar + 64 + kb * 8, 0);
                    if (kb == 0) TRG(u, 0);
                    wg_fence();
#pragma unroll
                    for (int q = 0; q < 4; q++)
                        wgmma_ss168t(d, mkdesc(alo + (it & 3) * 512 + q * 2, km::DESC_HI), mkdesc(blo + kb * (A_KB >> 4) + q * 16, 64), kb + q > 0);
                    wg_commit();
                    wg_wait<1>();
                    mbar_arrive(bar + 32 + ((it - 1) & 3) * 8, lane == 0 && kb > 0);
                }
                wg_wait<0>();
                mbar_arrive(bar + 32 + ((it - 1) & 3) * 8, lane == 0);
                TRG(u, 1);
                const bool first = u == f * LAGA;
                const uint32_t tag = ring_tag<NTA>(u, ep);
                const uint32_t qt0 = pk(d[72], d[73]), qt1 = pk(d[74], d[75]), kt0 = pk(d[76], d[77]), kt1 = pk(d[78], d[79]);
                const uint32_t vt0 = movm(pk(d[80], d[81])), vt1 = movm(pk(d[82], d[83]));
                float ot[4] = {0, 0, 0, 0};
                uint4* dst = g_oa + (((u & (RING - 1)) * 4 + wq) * 44 + a * 4) * 32 + lane;
#pragma unroll
                for (int h = 0; h < 3; h++) {
                    const float* q = d + 8 * h; const float* k = d + 24 + 8 * h; const float* v = d + 48 + 8 * h;
                    const uint32_t q0 = pk(q[0], q[1]), q1 = pk(q[2], q[3]), q2 = pk(q[4], q[5]), q3 = pk(q[6], q[7]);
                    const uint32_t k0 = pk(k[0], k[1]), k1 = pk(k[4], k[5]), k2 = pk(k[2], k[3]), k3 = pk(k[6], k[7]);
                    const uint32_t v0 = movm(pk(v[0], v[1])), v1 = movm(pk(v[2], v[3])), v2 = movm(pk(v[4], v[5])), v3 = movm(pk(v[6], v[7]));
                    const uint32_t t0 = c == h ? qt0 : 0, t1 = c == h ? qt1 : 0;
                    float sp[4] = {0, 0, 0, 0}, sl[4] = {0, 0, 0, 0}, sh[4] = {0, 0, 0, 0};
                    mma16(sp, q0, q1, q2, q3, kh[2 * h], kh[2 * h + 1]); mma16(sl, q0, q1, q2, q3, k0, k1); mma16(sh, q0, q1, q2, q3, k2, k3);
                    mma8(sp, t0, t1, kh[6]); mma8(sl, t0, t1, kt0); mma8(sh, t0, t1, kt1);
                    float x0_ = m0 ? sl[0] : first ? -INFINITY : sp[0], x1_ = m1 ? sl[1] : first ? -INFINITY : sp[1];
                    float y0_ = m0 ? sh[2] : sl[2], y1_ = m1 ? sh[3] : sl[3];
                    float mx = fmaxf(x0_, x1_), my = fmaxf(y0_, y1_);
#pragma unroll
                    for (int o = 1; o < 4; o <<= 1) { mx = fmaxf(mx, __shfl_xor_sync(~0u, mx, o)); my = fmaxf(my, __shfl_xor_sync(~0u, my, o)); }
                    mx *= -SC; my *= -SC;
                    x0_ = ex2(fmaf(x0_, SC, mx)); x1_ = ex2(fmaf(x1_, SC, mx)); y0_ = ex2(fmaf(y0_, SC, my)); y1_ = ex2(fmaf(y1_, SC, my));
                    float lx = x0_ + x1_, ly = y0_ + y1_;
#pragma unroll
                    for (int o = 1; o < 4; o <<= 1) { lx += __shfl_xor_sync(~0u, lx, o); ly += __shfl_xor_sync(~0u, ly, o); }
                    lx = rcp(lx); ly = rcp(ly);
                    const uint32_t px = pk(x0_ * lx, x1_ * lx), py = pk(y0_ * ly, y1_ * ly);
                    const uint32_t hm = (g >> 1) == h ? ~0u : 0u;
                    float o0[4] = {0, 0, 0, 0}, o1[4] = {0, 0, 0, 0};
                    mma16(o0, px & M, py & ~M, 0, py & M, v0, v1); mma16(o1, px & M, py & ~M, 0, py & M, v2, v3);
                    mma16(ot, px & M, py & ~M, 0, py & M, vt0 & hm, vt1 & hm);
                    mma8(o0, px & ~M, 0, vh[2 * h]); mma8(o1, px & ~M, 0, vh[2 * h + 1]); mma8(ot, px & ~M, 0, vh[6] & hm);
                    if (h == HA) cnt_hint(g_cnt + (C_A + u * 4 + wq) * 8, lane);
                    stg128(dst + h * 32, (pk(o0[0], o0[1]) & ~1u) | tag, pk(o0[2], o0[3]), pk(o1[0], o1[1]), pk(o1[2], o1[3]));
                    kh[2 * h] = k2; kh[2 * h + 1] = k3; vh[2 * h] = v1; vh[2 * h + 1] = v3;
                }
                kh[6] = kt1; vh[6] = vt1;
                stg128(dst + 96, (pk(ot[0], ot[1]) & ~1u) | tag, pk(ot[2], ot[3]), 0, 0);
                TRG(u, 2);
            }
        }
    } else {
        asm volatile("setmaxnreg.dec.sync.aligned.u32 120;");
        if (b < 24) {
            const int kq = b / 6, nq = b % 6;
            const uint32_t blo = (((sb + O_WA) >> 4) & 0x3fff) | (8u << 16);
#pragma unroll 1
            for (int u = 0; u < NTA; u++) {
                hint_wait(g_cnt + (C_A + u * 4 + wq) * 8, 11 * (ep + 1));
                const uint32_t tag = ring_tag<NTA>(u, ep);
                TRG(u, 0);
                const uint4* src = g_oa + (((u & (RING - 1)) * 4 + wq) * 44 + kq * 11) * 32 + lane;
                uint4 a[11];
                float d[48];
#pragma unroll
                for (int i = 0; i < 11; i++) a[i] = ldg_pkt(src + i * 32);
                validate<11>(a, src, 512, tag);
                wg_fence();
#pragma unroll
                for (int i = 0; i < 11; i++) wgmma_rs96t(d, a[i].x, a[i].y, a[i].z, a[i].w, mkdesc(blo + i * 16, 176), i > 0);
                wg_commit();
                wg_wait<0>();
                TRG(u, 1);
                uint4* dst = g_pa + (((u & (RING - 1)) * 64 + (wq >> 1) * 32 + 2 * g + (wq & 1)) * 4 + kq) * 72 + nq * 12 + c;
#pragma unroll
                for (int m = 0; m < 3; m++) {
                    if (m == HW) cnt_hint(g_cnt + (C_WA + u * 4 + wq) * 8, lane);
                    stg128(dst + 4 * m, (pk(d[16 * m], d[16 * m + 1]) & ~1u) | tag, pk(d[16 * m + 4], d[16 * m + 5]), pk(d[16 * m + 8], d[16 * m + 9]), pk(d[16 * m + 12], d[16 * m + 13]));
                    stg128(dst + 4 * m + 16 * 288, (pk(d[16 * m + 2], d[16 * m + 3]) & ~1u) | tag, pk(d[16 * m + 6], d[16 * m + 7]), pk(d[16 * m + 10], d[16 * m + 11]), pk(d[16 * m + 14], d[16 * m + 15]));
                }
                TRG(u, 3);
            }
        } else if (warp == 4) {
            mbar_expect(bar + 64 + lane * 8, A_KB, lane < 9);
            int it = 0;
#pragma unroll 1
            for (int u = 0; u < NTA; u++) {
                if (u == 0) { cnt_wait(g_cnt + C_W * 8, 96 * (ep + 1)); TRG(78, 0); }
                if (u < NSEG) cnt_wait(g_cnt + (C_N0 + u) * 8, 32 * (ep + 1));
                if (u > LAGA + LAG) cnt_wait(g_cnt + (C_RB + NSEG + u - LAGA - LAG - 1) * 8, 32 * (ep + 1));
                if (u >= LAGA) cnt_wait(g_cnt + (C_RB + u - LAGA) * 8, 32 * (ep + 1));
                TRG(u, 0);
                asm volatile("fence.proxy.async.global;" ::: "memory");
                const bool on = lane == 0 ? u < NSEG : lane == 1 && u >= LAGA;
#pragma unroll 1
                for (int kb = 0; kb < 9; kb++, it++) {
                    if (it >= 4) mbar_wait(bar + 32 + (it & 3) * 8, ((it >> 2) - 1) & 1);
                    mbar_expect(bar + (it & 3) * 8, u < NSEG && u >= LAGA ? 8192 : 4096, lane == 0);
                    asm volatile("{.reg .pred p; setp.ne.u32 p, %3, 0; @p cp.async.bulk.shared::cluster.global.mbarrier::complete_tx::bytes [%0], [%1], 4096, [%2];}"
                        :: "r"(sb + O_RING + (it & 3) * 8192 + (lane & 1) * 4096), "l"(g_xa + u * 4608 + (lane & 1) * 2304 + kb * 256), "r"(bar + (it & 3) * 8), "r"((uint32_t)on) : "memory");
                    if (u == 0) asm volatile("{.reg .pred p; setp.ne.u32 p, %4, 0; @p cp.async.bulk.shared::cluster.global.mbarrier::complete_tx::bytes [%0], [%1], %3, [%2];}"
                        :: "r"(sb + lane * A_KB), "l"(g_wa + ((b - 24) * 9 + lane) * (A_KB / 16)), "r"(bar + 64 + lane * 8), "n"(A_KB),
                           "r"((uint32_t)(lane < 9 && kb == (lane < 4 ? lane : lane < 6 ? 3 : lane - 2))) : "memory");
                }
            }
        } else if ((warp - 5) * 11 + b - 24 < 32) rows_a(xin, 1, (warp - 5) * 11 + b - 24, lane, ep, warp);
    }
}

static Tune h_tune = {{0, 9, 1, 2, 0, 6000, 0, 12, 10000, 0}};

extern "C" void kernel_launch(void* const* d_in, const int* in_sizes, int n_in, void* d_out, int out_size) {
    const __nv_bfloat16* x = (const __nv_bfloat16*)d_in[0];
    const __nv_bfloat16* wqkv = (const __nv_bfloat16*)d_in[1];
    const __nv_bfloat16* wo = (const __nv_bfloat16*)d_in[2];
    const __nv_bfloat16* mem0 = (const __nv_bfloat16*)d_in[4];
    const __nv_bfloat16* Wq = (const __nv_bfloat16*)d_in[5];
    const __nv_bfloat16* Wk = (const __nv_bfloat16*)d_in[6];
    const __nv_bfloat16* Wv = (const __nv_bfloat16*)d_in[7];
    const __nv_bfloat16* Wo = (const __nv_bfloat16*)d_in[8];
    cudaFuncSetAttribute(k_main, cudaFuncAttributeMaxDynamicSharedMemorySize, km::SMEM);
    cudaFuncSetAttribute(k_aux, cudaFuncAttributeMaxDynamicSharedMemorySize, ka::SMEM);
    cudaStream_t s = cudaStreamPerThread;
    k_main<<<96, 384, km::SMEM, s>>>(x, wqkv, wo, mem0, Wq, Wk, Wv, Wo, h_tune);
    cudaLaunchConfig_t cfg = {};
    cudaLaunchAttribute at[1];
    at[0].id = cudaLaunchAttributeProgrammaticStreamSerialization;
    at[0].val.programmaticStreamSerializationAllowed = 1;
    cfg.stream = s; cfg.attrs = at; cfg.numAttrs = 1;
    cfg.gridDim = dim3(36); cfg.blockDim = dim3(384); cfg.dynamicSmemBytes = ka::SMEM;
    cudaLaunchKernelEx(&cfg, k_aux, x, wqkv, wo, Wo, (__nv_bfloat16*)d_out, h_tune);
}
```

```cpp
#include <cuda_runtime.h>
#include <cuda_bf16.h>
#include <stdint.h>

#define LAG 7
constexpr int NSEG = 64;
constexpr int NT = NSEG + LAG;
#define AHEAD 1
constexpr int LAGA = LAG + AHEAD;
constexpr int NTA = NSEG + LAGA;
#define RING_ 8
constexpr int RING = RING_;
constexpr int DM = 576;

__device__ __align__(1024) uint4 g_xt[NT * 2 * 9 * 256];
__device__ __align__(1024) uint4 g_o[RING * 4 * 256 * 32];
__device__ __align__(1024) uint4 g_ex[2 * 131072];
__device__ unsigned g_side[96];
__device__ __align__(1024) uint4 g_pb[RING * 64 * 8 * 72];
__device__ __align__(1024) uint4 g_pa[RING * 64 * 4 * 72];
__device__ __align__(1024) uint4 g_oa[RING * 4 * 44 * 32];
__device__ __align__(1024) uint4 g_xa[NTA * 2 * 9 * 256];
__device__ __align__(1024) uint4 g_wa[11 * 9 * 21 * 64];
__device__ __align__(1024) uint4 g_x[3 * 2048 * 72];

constexpr int C_X = 0;
constexpr int C_O = C_X + NT;
constexpr int C_WB = C_O + NT * 8;
constexpr int C_RB = C_WB + NT * 4;
constexpr int C_A = C_RB + 2 * NSEG;
constexpr int C_WA = C_A + NTA * 4;
constexpr int C_N0 = C_WA + NTA * 4;
constexpr int C_W = C_N0 + NSEG;
constexpr int C_DONE = C_W + 1;
constexpr int C_TOTAL = C_DONE + 1;
__device__ __align__(1024) unsigned g_cnt[C_TOTAL * 8];
__device__ unsigned g_epoch;

struct Tune { uint32_t v[10]; };
#define TR(i)
#define TR1(i)
#define TR_ON(t)
#define TR_INIT(base)
#define TR_DUMP(slot)
#define TRG(t, i)
constexpr int TR_BYTES = 0;

#define DEVI __device__ __forceinline__
DEVI uint32_t smem_u32(const void* p) { return (uint32_t)__cvta_generic_to_shared(p); }
DEVI uint32_t pk(float lo, float hi) { uint32_t r; asm("cvt.rn.bf16x2.f32 %0, %1, %2;" : "=r"(r) : "f"(hi), "f"(lo)); return r; }
DEVI float bf_lo(uint32_t u) { return __uint_as_float(u << 16); }
DEVI float bf_hi(uint32_t u) { return __uint_as_float(u & 0xffff0000u); }
DEVI uint32_t add2(uint32_t a, uint32_t b) { uint32_t d; asm("add.rn.bf16x2 %0, %1, %2;" : "=r"(d) : "r"(a), "r"(b)); return d; }
DEVI uint32_t movm(uint32_t a) { uint32_t d; asm volatile("movmatrix.sync.aligned.m8n8.trans.b16 %0, %1;" : "=r"(d) : "r"(a)); return d; }
DEVI float2 shfl2(float a, float b, int o) {
    float2 r; asm volatile("shfl.sync.bfly.b32 %0, %2, %4, 31, -1; shfl.sync.bfly.b32 %1, %3, %4, 31, -1;" : "=&f"(r.x), "=f"(r.y) : "f"(a), "f"(b), "r"(o)); return r;
}
DEVI float ex2(float x) { float y; asm("ex2.approx.ftz.f32 %0, %1;" : "=f"(y) : "f"(x)); return y; }
DEVI float rcp(float x) { float y; asm("rcp.approx.ftz.f32 %0, %1;" : "=f"(y) : "f"(x)); return y; }
DEVI void mma16(float (&d)[4], uint32_t a0, uint32_t a1, uint32_t a2, uint32_t a3, uint32_t b0, uint32_t b1) {
    asm volatile("mma.sync.aligned.m16n8k16.row.col.f32.bf16.bf16.f32 {%0,%1,%2,%3}, {%4,%5,%6,%7}, {%8,%9}, {%0,%1,%2,%3};"
        : "+f"(d[0]), "+f"(d[1]), "+f"(d[2]), "+f"(d[3]) : "r"(a0), "r"(a1), "r"(a2), "r"(a3), "r"(b0), "r"(b1));
}
DEVI void mma8(float (&d)[4], uint32_t a0, uint32_t a1, uint32_t b0) {
    asm volatile("mma.sync.aligned.m16n8k8.row.col.f32.bf16.bf16.f32 {%0,%1,%2,%3}, {%4,%5}, {%6}, {%0,%1,%2,%3};"
        : "+f"(d[0]), "+f"(d[1]), "+f"(d[2]), "+f"(d[3]) : "r"(a0), "r"(a1), "r"(b0));
}
DEVI uint4 lds128(uint32_t a) { uint4 v; asm volatile("ld.shared.v4.u32 {%0,%1,%2,%3}, [%4];" : "=r"(v.x), "=r"(v.y), "=r"(v.z), "=r"(v.w) : "r"(a) : "memory"); return v; }
DEVI uint2 lds64(uint32_t a) { uint2 v; asm volatile("ld.shared.v2.u32 {%0,%1}, [%2];" : "=r"(v.x), "=r"(v.y) : "r"(a) : "memory"); return v; }
DEVI uint32_t lds32(uint32_t a) { uint32_t v; asm volatile("ld.shared.u32 %0, [%1];" : "=r"(v) : "r"(a) : "memory"); return v; }
DEVI uint32_t lds32v(uint32_t a) { uint32_t v; asm volatile("ld.volatile.shared.u32 %0, [%1];" : "=r"(v) : "r"(a) : "memory"); return v; }
DEVI uint4 lds128v(uint32_t a) { uint4 v; asm volatile("ld.volatile.shared.v4.u32 {%0,%1,%2,%3}, [%4];" : "=r"(v.x), "=r"(v.y), "=r"(v.z), "=r"(v.w) : "r"(a) : "memory"); return v; }
DEVI uint32_t lds16(uint32_t a) { uint32_t v; asm volatile("ld.shared.u16 %0, [%1];" : "=r"(v) : "r"(a) : "memory"); return v; }
DEVI uint4 ldsm4(uint32_t a) { uint4 v; asm volatile("ldmatrix.sync.aligned.m8n8.x4.shared.b16 {%0,%1,%2,%3}, [%4];" : "=r"(v.x), "=r"(v.y), "=r"(v.z), "=r"(v.w) : "r"(a) : "memory"); return v; }
DEVI uint4 ldsm4p(uint32_t a, bool pred) {
    uint4 v; asm volatile("{.reg .pred p; setp.ne.u32 p, %5, 0; @p ldmatrix.sync.aligned.m8n8.x4.shared.b16 {%0,%1,%2,%3}, [%4];}" : "=r"(v.x), "=r"(v.y), "=r"(v.z), "=r"(v.w) : "r"(a), "r"((uint32_t)pred) : "memory"); return v;
}
DEVI uint4 ldsm4t(uint32_t a) { uint4 v; asm volatile("ldmatrix.sync.aligned.m8n8.x4.trans.shared.b16 {%0,%1,%2,%3}, [%4];" : "=r"(v.x), "=r"(v.y), "=r"(v.z), "=r"(v.w) : "r"(a) : "memory"); return v; }
DEVI uint2 ldsm2(uint32_t a) { uint2 v; asm volatile("ldmatrix.sync.aligned.m8n8.x2.shared.b16 {%0,%1}, [%2];" : "=r"(v.x), "=r"(v.y) : "r"(a) : "memory"); return v; }
DEVI void stsm4t(uint32_t a, uint32_t x, uint32_t y, uint32_t z, uint32_t w) { asm volatile("stmatrix.sync.aligned.m8n8.x4.trans.shared.b16 [%0], {%1,%2,%3,%4};" :: "r"(a), "r"(x), "r"(y), "r"(z), "r"(w) : "memory"); }
DEVI void sts128(uint32_t a, uint32_t x, uint32_t y, uint32_t z, uint32_t w) { asm volatile("st.shared.v4.u32 [%0], {%1,%2,%3,%4};" :: "r"(a), "r"(x), "r"(y), "r"(z), "r"(w) : "memory"); }
DEVI void sts64(uint32_t a, uint32_t x, uint32_t y) { asm volatile("st.shared.v2.u32 [%0], {%1,%2};" :: "r"(a), "r"(x), "r"(y) : "memory"); }
DEVI void sts32(uint32_t a, uint32_t x) { asm volatile("st.shared.u32 [%0], %1;" :: "r"(a), "r"(x) : "memory"); }
DEVI void sts32p(uint32_t a, uint32_t x, bool pred) { asm volatile("{.reg .pred p; setp.ne.u32 p, %2, 0; @p st.shared.u32 [%0], %1;}" :: "r"(a), "r"(x), "r"((uint32_t)pred) : "memory"); }
DEVI void sta128(uint32_t a, uint32_t x, uint32_t y, uint32_t z, uint32_t w, uint32_t bar) {
    asm volatile("st.async.weak.shared::cluster.mbarrier::complete_tx::bytes.v4.b32 [%0], {%1,%2,%3,%4}, [%5];" :: "r"(a), "r"(x), "r"(y), "r"(z), "r"(w), "r"(bar) : "memory");
}
DEVI void sta128p(uint32_t a, uint32_t x, uint32_t y, uint32_t z, uint32_t w, uint32_t bar, bool pred) {
    asm volatile("{.reg .pred p; setp.ne.u32 p, %6, 0; @p st.async.weak.shared::cluster.mbarrier::complete_tx::bytes.v4.b32 [%0], {%1,%2,%3,%4}, [%5];}" :: "r"(a), "r"(x), "r"(y), "r"(z), "r"(w), "r"(bar), "r"((uint32_t)pred) : "memory");
}
DEVI void sta64(uint32_t a, uint32_t x, uint32_t y, uint32_t bar) {
    asm volatile("st.async.weak.shared::cluster.mbarrier::complete_tx::bytes.v2.b32 [%0], {%1,%2}, [%3];" :: "r"(a), "r"(x), "r"(y), "r"(bar) : "memory");
}
DEVI void sta32(uint32_t a, uint32_t x, uint32_t bar) {
    asm volatile("st.async.weak.shared::cluster.mbarrier::complete_tx::bytes.b32 [%0], %1, [%2];" :: "r"(a), "r"(x), "r"(bar) : "memory");
}
DEVI uint4 ldg_pkt(const void* p) {
    uint4 v;
    asm volatile("ld.relaxed.gpu.global.v4.u32 {%0,%1,%2,%3}, [%4];" : "=r"(v.x), "=r"(v.y), "=r"(v.z), "=r"(v.w) : "l"(p) : "memory");
    return v;
}
DEVI void ldg_pkt_if(uint4& v, const void* p, bool pred) {
    asm volatile("{.reg .pred p; setp.ne.u32 p, %5, 0; @p ld.relaxed.gpu.global.v4.u32 {%0,%1,%2,%3}, [%4];}"
        : "+r"(v.x), "+r"(v.y), "+r"(v.z), "+r"(v.w) : "l"(p), "r"((uint32_t)pred) : "memory");
}
DEVI void ldg_pkt_retry(uint4& v, const void* p, uint32_t tag) {
    asm volatile("{.reg .pred p; .reg .b32 t; lop3.b32 t, %0, %5, 1, 0x28; setp.ne.u32 p, t, 0; @p ld.relaxed.gpu.global.v4.u32 {%0,%1,%2,%3}, [%4];}"
        : "+r"(v.x), "+r"(v.y), "+r"(v.z), "+r"(v.w) : "l"(p), "r"(tag) : "memory");
}
DEVI void stg_pkt(void* p, uint32_t x, uint32_t y, uint32_t z, uint32_t w) {
    asm volatile("st.relaxed.gpu.global.v4.u32 [%0], {%1,%2,%3,%4};" :: "l"(p), "r"(x), "r"(y), "r"(z), "r"(w) : "memory");
}
DEVI uint32_t ldg_word(const void* p) { uint32_t v; asm volatile("ld.relaxed.gpu.global.u32 %0, [%1];" : "=r"(v) : "l"(p) : "memory"); return v; }
DEVI void stg_word(void* p, uint32_t x, bool pred) {
    asm volatile("{.reg .pred p; setp.ne.u32 p, %2, 0; @p st.relaxed.gpu.global.u32 [%0], %1;}" :: "l"(p), "r"(x), "r"((uint32_t)pred) : "memory");
}
DEVI uint2 ldg64nc(const void* p) { uint2 v; asm volatile("ld.global.nc.L1::no_allocate.v2.u32 {%0,%1}, [%2];" : "=r"(v.x), "=r"(v.y) : "l"(p)); return v; }
DEVI void prefetch_l2(const void* p, uint32_t bytes) { asm volatile("cp.async.bulk.prefetch.L2.global [%0], %1;" :: "l"(p), "r"(bytes) : "memory"); }
DEVI uint4 ldg128(const void* p) { uint4 v; asm volatile("ld.global.cg.v4.u32 {%0,%1,%2,%3}, [%4];" : "=r"(v.x), "=r"(v.y), "=r"(v.z), "=r"(v.w) : "l"(p) : "memory"); return v; }
DEVI uint2 ldg64(const void* p) { uint2 v; asm volatile("ld.global.cg.v2.u32 {%0,%1}, [%2];" : "=r"(v.x), "=r"(v.y) : "l"(p) : "memory"); return v; }
DEVI uint32_t ldg32(const void* p) { uint32_t v; asm volatile("ld.global.cg.u32 %0, [%1];" : "=r"(v) : "l"(p) : "memory"); return v; }
DEVI void stg128(void* p, uint32_t x, uint32_t y, uint32_t z, uint32_t w) { asm volatile("st.global.cg.v4.u32 [%0], {%1,%2,%3,%4};" :: "l"(p), "r"(x), "r"(y), "r"(z), "r"(w) : "memory"); }
DEVI void stg128p(void* p, uint32_t x, uint32_t y, uint32_t z, uint32_t w, bool pred) { asm volatile("{.reg .pred p; setp.ne.u32 p, %5, 0; @p st.global.cg.v4.u32 [%0], {%1,%2,%3,%4};}" :: "l"(p), "r"(x), "r"(y), "r"(z), "r"(w), "r"((uint32_t)pred) : "memory"); }
DEVI void stg64(void* p, uint32_t x, uint32_t y) { asm volatile("st.global.cg.v2.u32 [%0], {%1,%2};" :: "l"(p), "r"(x), "r"(y) : "memory"); }
DEVI void stg32(void* p, uint32_t x) { asm volatile("st.global.cg.u32 [%0], %1;" :: "l"(p), "r"(x) : "memory"); }
DEVI void cp16(uint32_t dst, const void* src) { asm volatile("cp.async.cg.shared.global [%0], [%1], 16;" :: "r"(dst), "l"(src) : "memory"); }
DEVI void cp16_if(uint32_t dst, const void* src, bool pred) { asm volatile("{.reg .pred p; setp.ne.u32 p, %2, 0; @p cp.async.cg.shared.global [%0], [%1], 16;}" :: "r"(dst), "l"(src), "r"((uint32_t)pred) : "memory"); }
DEVI void cp_commit() { asm volatile("cp.async.commit_group;" ::: "memory"); }
DEVI void cp4(uint32_t dst, const void* src) { asm volatile("cp.async.ca.shared.global [%0], [%1], 4;" :: "r"(dst), "l"(src) : "memory"); }
template <int N> DEVI void cp_wait() { asm volatile("cp.async.wait_group %0;" :: "n"(N) : "memory"); }
DEVI void cp_wait_all() { asm volatile("cp.async.wait_all;" ::: "memory"); }
DEVI void bar_sync(int id, int n) { asm volatile("bar.sync %0, %1;" :: "r"(id), "r"(n) : "memory"); }
DEVI void bar_arrive(int id, int n) { asm volatile("bar.arrive %0, %1;" :: "r"(id), "r"(n) : "memory"); }
DEVI void fence_async_smem() { asm volatile("fence.proxy.async.shared::cta;" ::: "memory"); }
DEVI void fence_async_global() { asm volatile("fence.proxy.async.global;" ::: "memory"); }
DEVI void mbar_init(uint32_t b, int n) { asm volatile("mbarrier.init.shared.b64 [%0], %1;" :: "r"(b), "r"(n) : "memory"); }
DEVI void mbar_expect(uint32_t b, uint32_t bytes, bool pred) {
    asm volatile("{.reg .pred p; setp.ne.u32 p, %2, 0; @p mbarrier.arrive.expect_tx.shared.b64 _, [%0], %1;}" :: "r"(b), "r"(bytes), "r"((uint32_t)pred) : "memory");
}
DEVI void mbar_arrive(uint32_t b, bool pred) { asm volatile("{.reg .pred p; setp.ne.u32 p, %1, 0; @p mbarrier.arrive.shared.b64 _, [%0];}" :: "r"(b), "r"((uint32_t)pred) : "memory"); }
DEVI void mbar_arrive_all3(uint32_t b, uint32_t lane) {
    asm volatile("{.reg .pred p; .reg .u32 a; setp.lt.u32 p, %1, 3; @p mapa.shared::cluster.u32 a, %0, %1; @p mbarrier.arrive.relaxed.cluster.shared::cluster.b64 _, [a];}" :: "r"(b), "r"(lane) : "memory");
}
#define FAULT "or.b32 n, n, 1; st.volatile.shared.u32 [n], n;\n"
#define LIM1 "400000"
#define LIM2 "2000000"
DEVI void fault_if(bool p, uint32_t n) { asm volatile("{.reg .pred p; setp.ne.u32 p, %0, 0; @p st.volatile.shared.u32 [%1], %1;}" :: "r"((uint32_t)p), "r"(n | 1) : "memory"); }
DEVI void mbar_wait(uint32_t b, uint32_t parity) {
    asm volatile("{.reg .pred p; .reg .u32 n;\n"
        "mbarrier.try_wait.parity.shared::cta.b64 p, [%0], %1;\n"
        "@p bra.uni D%=;\n"
        "mov.u32 n, 0;\n"
        "W%=: mbarrier.try_wait.parity.shared::cta.b64 p, [%0], %1;\n"
        "@p bra.uni D%=;\n"
        "add.u32 n, n, 1; setp.lt.u32 p, n, " LIM1 "; @p bra.uni W%=;\n"
        FAULT
        "D%=:}" :: "r"(b), "r"(parity) : "memory");
}
constexpr int POLL_LIMIT = 2000000;
DEVI void cnt_wait(const unsigned* c, unsigned target) {
    asm volatile("{.reg .pred p; .reg .u32 n, v;\n"
        "ld.acquire.gpu.global.u32 v, [%0];\n"
        "setp.ge.u32 p, v, %1; vote.sync.all.pred p, p, 0xffffffff; @p bra.uni D%=;\n"
        "mov.u32 n, 0;\n"
        "W%=: ld.acquire.gpu.global.u32 v, [%0];\n"
        "setp.ge.u32 p, v, %1; vote.sync.all.pred p, p, 0xffffffff; @p bra.uni D%=;\n"
        "add.u32 n, n, 1; setp.lt.u32 p, n, " LIM2 "; @p bra.uni W%=;\n"
        FAULT
        "D%=:}" :: "l"(c), "r"(target) : "memory");
}
DEVI void hint_wait(const unsigned* c, unsigned target) {
    asm volatile("{.reg .pred p; .reg .u32 n, v;\n"
        "ld.relaxed.gpu.global.u32 v, [%0];\n"
        "setp.ge.u32 p, v, %1; vote.sync.all.pred p, p, 0xffffffff; @p bra.uni D%=;\n"
        "mov.u32 n, 0;\n"
        "W%=: ld.relaxed.gpu.global.u32 v, [%0];\n"
        "setp.ge.u32 p, v, %1; vote.sync.all.pred p, p, 0xffffffff; @p bra.uni D%=;\n"
        "add.u32 n, n, 1; setp.lt.u32 p, n, " LIM2 "; @p bra.uni W%=;\n"
        FAULT
        "D%=:}" :: "l"(c), "r"(target) : "memory");
}
DEVI void cnt_look(const unsigned* c, unsigned target, uint32_t flag, uint32_t val) {
    asm volatile("{.reg .pred q; .reg .u32 v; ld.acquire.gpu.global.u32 v, [%0]; setp.ge.u32 q, v, %1; @q st.release.cta.shared.u32 [%2], %3;}"
        :: "l"(c), "r"(target), "r"(flag), "r"(val) : "memory");
}
DEVI uint32_t lds_acq(uint32_t a) { uint32_t v; asm volatile("ld.acquire.cta.shared.u32 %0, [%1];" : "=r"(v) : "r"(a) : "memory"); return v; }
template <int N = 1> DEVI void cnt_add(unsigned* c, int lane) {
    asm volatile("{.reg .pred p; setp.eq.u32 p, %1, 0; fence.acq_rel.gpu; bar.warp.sync 0xffffffff; @p red.relaxed.gpu.global.add.u32 [%0], %2;}" :: "l"(c + lane), "r"(lane), "n"(N) : "memory");
}
DEVI void cnt_hint(unsigned* c, int lane) {
    asm volatile("{.reg .pred p; setp.eq.u32 p, %1, 0; @p red.relaxed.gpu.global.add.u32 [%0], 1;}" :: "l"(c + lane), "r"(lane) : "memory");
}
template <int N = NT> DEVI uint32_t ring_tag(unsigned u, uint32_t ep) { return (u / RING + ep * ((N - 1 - u % RING) / RING + 1) + 1) & 1; }
static_assert(RING >= LAGA && RING > LAG, "ring too short");
DEVI uint32_t lop_bad(uint32_t acc, uint32_t x, uint32_t y, uint32_t tag) {
    uint32_t d; asm("{.reg .b32 t; lop3.b32 t, %2, %3, %4, 0x7e; or.b32 %0, t, %1;}" : "=r"(d) : "r"(acc), "r"(x), "r"(y), "r"(tag)); return d;
}
template <int N> DEVI void validate(uint4* v, const void* p, int step, uint32_t tag) {
    for (int n = 0;; n++) {
        uint32_t bad = 0;
#pragma unroll
        for (int i = 0; i < N; i += 2) bad = lop_bad(bad, v[i].x, v[i + 1 < N ? i + 1 : i].x, tag);
        if (!__any_sync(~0u, bad & 1)) break;
#pragma unroll
        for (int i = 0; i < N; i++) ldg_pkt_retry(v[i], static_cast<const char*>(p) + i * step, tag);
        fault_if(n > POLL_LIMIT, n);
    }
}
DEVI uint32_t page_par(uint32_t off) { return __popc((off >> 12) & 0xb2) & 1; }
DEVI uint32_t inbox_off(int b) { return (b >> 1) * 32768 + (b & 1) * 8192; }
DEVI uint32_t mem_off(int w, int i) { return 0x180000 + w * 1024 + (i & 1) * 512 + (i & 3) * 16384 + (i < 4 ? 0 : i < 8 ? 0x30000 : 0x40000); }
DEVI void sched_fence(uint32_t zero, uint32_t id) { asm volatile("{.reg .pred p; setp.ne.u32 p, %0, %1; @p bra.uni D%=; exit; D%=:}" :: "r"(zero), "r"(id) : "memory"); }
DEVI uint32_t clk() { uint32_t c; asm volatile("mov.u32 %0, %%clock;" : "=r"(c) :: "memory"); return c; }
DEVI void delay(uint32_t n) {
    if (n) asm volatile("{.reg .pred p; .reg .u32 c, e; mov.u32 e, %%clock;\n W%=: mov.u32 c, %%clock; sub.u32 c, c, e; setp.lt.u32 p, c, %0; @p bra.uni W%=;}" :: "r"(n) : "memory");
}
DEVI void pause(uint32_t n) {
    asm volatile("{.reg .pred p; .reg .f32 x; .reg .s32 c; cvt.rn.f32.u32 x, %0;\n"
        "W%=: add.f32 x, x, 0fBF800000; mul.f32 x, x, x; sqrt.approx.ftz.f32 x, x; setp.gt.f32 p, x, 0f3F000000; @p bra.uni W%=;\n"
        "setp.lt.f32 p, x, 0fC1000000; @p st.volatile.shared.f32 [%0], x;}" :: "r"(n) : "memory");
}
DEVI void delay_until(uint32_t t0, uint32_t n) {
    asm volatile("{.reg .pred p; .reg .u32 c;\n W%=: mov.u32 c, %%clock; sub.u32 c, c, %1; setp.lt.u32 p, c, %0; @p bra.uni W%=;}" :: "r"(n), "r"(t0) : "memory");
}
DEVI void wg_fence() { asm volatile("wgmma.fence.sync.aligned;" ::: "memory"); }
DEVI void wg_commit() { asm volatile("wgmma.commit_group.sync.aligned;" ::: "memory"); }
template <int N> DEVI void wg_wait() { asm volatile("wgmma.wait_group.sync.aligned %0;" :: "n"(N) : "memory"); }
DEVI uint64_t mkdesc(uint32_t lo, uint32_t hi) { uint64_t d; asm("mov.b64 %0, {%1,%2};" : "=l"(d) : "r"(lo), "r"(hi)); return d; }
DEVI void cluster_arrive() { asm volatile("barrier.cluster.arrive.relaxed.aligned;" ::: "memory"); }
DEVI void cluster_wait() { asm volatile("barrier.cluster.wait.aligned;" ::: "memory"); }
DEVI void cluster_sync() { asm volatile("barrier.cluster.arrive.aligned;\n barrier.cluster.wait.aligned;" ::: "memory"); }
DEVI void wgmma_ss16t(float (&d)[8], uint64_t da, uint64_t db, int acc) {
    asm volatile("{.reg .pred p; setp.ne.b32 p, %10, 0;\n"
        "wgmma.mma_async.sync.aligned.m64n16k16.f32.bf16.bf16 {%0,%1,%2,%3,%4,%5,%6,%7}, %8, %9, p, 1, 1, 0, 1;}"
        : "+f"(d[0]), "+f"(d[1]), "+f"(d[2]), "+f"(d[3]), "+f"(d[4]), "+f"(d[5]), "+f"(d[6]), "+f"(d[7])
        : "l"(da), "l"(db), "r"(acc));
}
DEVI void wgmma_ss16a(float (&d)[8], uint64_t da, uint64_t db, int acc) {
    asm volatile("{.reg .pred p; setp.ne.b32 p, %10, 0;\n"
        "wgmma.mma_async.sync.aligned.m64n16k16.f32.bf16.bf16 {%0,%1,%2,%3,%4,%5,%6,%7}, %8, %9, p, 1, 1, 1, 0;}"
        : "+f"(d[0]), "+f"(d[1]), "+f"(d[2]), "+f"(d[3]), "+f"(d[4]), "+f"(d[5]), "+f"(d[6]), "+f"(d[7])
        : "l"(da), "l"(db), "r"(acc));
}
DEVI void wgmma_ss64(float (&d)[32], uint64_t da, uint64_t db, int acc) {
    asm volatile("{.reg .pred p; setp.ne.b32 p, %34, 0;\n"
        "wgmma.mma_async.sync.aligned.m64n64k16.f32.bf16.bf16 {%0,%1,%2,%3,%4,%5,%6,%7,%8,%9,%10,%11,%12,%13,%14,%15,%16,%17,%18,%19,%20,%21,%22,%23,%24,%25,%26,%27,%28,%29,%30,%31}, %32, %33, p, 1, 1, 0, 0;}"
        : "+f"(d[0]), "+f"(d[1]), "+f"(d[2]), "+f"(d[3]), "+f"(d[4]), "+f"(d[5]), "+f"(d[6]), "+f"(d[7]), "+f"(d[8]), "+f"(d[9]), "+f"(d[10]), "+f"(d[11]), "+f"(d[12]), "+f"(d[13]), "+f"(d[14]), "+f"(d[15]), "+f"(d[16]), "+f"(d[17]), "+f"(d[18]), "+f"(d[19]), "+f"(d[20]), "+f"(d[21]), "+f"(d[22]), "+f"(d[23]), "+f"(d[24]), "+f"(d[25]), "+f"(d[26]), "+f"(d[27]), "+f"(d[28]), "+f"(d[29]), "+f"(d[30]), "+f"(d[31])
        : "l"(da), "l"(db), "r"(acc));
}
DEVI void wgmma_rs16t(float (&d)[8], uint32_t a0, uint32_t a1, uint32_t a2, uint32_t a3, uint64_t db, int acc) {
    asm volatile("{.reg .pred p; setp.ne.b32 p, %13, 0;\n"
        "wgmma.mma_async.sync.aligned.m64n16k16.f32.bf16.bf16 {%0,%1,%2,%3,%4,%5,%6,%7}, {%8,%9,%10,%11}, %12, p, 1, 1, 1;}"
        : "+f"(d[0]), "+f"(d[1]), "+f"(d[2]), "+f"(d[3]), "+f"(d[4]), "+f"(d[5]), "+f"(d[6]), "+f"(d[7])
        : "r"(a0), "r"(a1), "r"(a2), "r"(a3), "l"(db), "r"(acc));
}
DEVI void wgmma_rs64(float (&d)[32], uint32_t a0, uint32_t a1, uint32_t a2, uint32_t a3, uint64_t db, int acc) {
    asm volatile("{.reg .pred p; setp.ne.b32 p, %37, 0;\n"
        "wgmma.mma_async.sync.aligned.m64n64k16.f32.bf16.bf16 {%0,%1,%2,%3,%4,%5,%6,%7,%8,%9,%10,%11,%12,%13,%14,%15,%16,%17,%18,%19,%20,%21,%22,%23,%24,%25,%26,%27,%28,%29,%30,%31}, {%32,%33,%34,%35}, %36, p, 1, 1, 0;}"
        : "+f"(d[0]), "+f"(d[1]), "+f"(d[2]), "+f"(d[3]), "+f"(d[4]), "+f"(d[5]), "+f"(d[6]), "+f"(d[7]), "+f"(d[8]), "+f"(d[9]), "+f"(d[10]), "+f"(d[11]), "+f"(d[12]), "+f"(d[13]), "+f"(d[14]), "+f"(d[15]), "+f"(d[16]), "+f"(d[17]), "+f"(d[18]), "+f"(d[19]), "+f"(d[20]), "+f"(d[21]), "+f"(d[22]), "+f"(d[23]), "+f"(d[24]), "+f"(d[25]), "+f"(d[26]), "+f"(d[27]), "+f"(d[28]), "+f"(d[29]), "+f"(d[30]), "+f"(d[31])
        : "r"(a0), "r"(a1), "r"(a2), "r"(a3), "l"(db), "r"(acc));
}
DEVI void wgmma_ss168t(float (&d)[84], uint64_t da, uint64_t db, int acc) {
    asm volatile("{.reg .pred p; setp.ne.b32 p, %86, 0;\n"
        "wgmma.mma_async.sync.aligned.m64n168k16.f32.bf16.bf16 {%0,%1,%2,%3,%4,%5,%6,%7,%8,%9,%10,%11,%12,%13,%14,%15,%16,%17,%18,%19,%20,%21,%22,%23,%24,%25,%26,%27,%28,%29,%30,%31,%32,%33,%34,%35,%36,%37,%38,%39,%40,%41,%42,%43,%44,%45,%46,%47,%48,%49,%50,%51,%52,%53,%54,%55,%56,%57,%58,%59,%60,%61,%62,%63,%64,%65,%66,%67,%68,%69,%70,%71,%72,%73,%74,%75,%76,%77,%78,%79,%80,%81,%82,%83}, %84, %85, p, 1, 1, 0, 1;}"
        : "+f"(d[0]), "+f"(d[1]), "+f"(d[2]), "+f"(d[3]), "+f"(d[4]), "+f"(d[5]), "+f"(d[6]), "+f"(d[7]), "+f"(d[8]), "+f"(d[9]), "+f"(d[10]), "+f"(d[11]), "+f"(d[12]), "+f"(d[13]), "+f"(d[14]), "+f"(d[15]), "+f"(d[16]), "+f"(d[17]), "+f"(d[18]), "+f"(d[19]), "+f"(d[20]), "+f"(d[21]), "+f"(d[22]), "+f"(d[23]), "+f"(d[24]), "+f"(d[25]), "+f"(d[26]), "+f"(d[27]), "+f"(d[28]), "+f"(d[29]), "+f"(d[30]), "+f"(d[31]), "+f"(d[32]), "+f"(d[33]), "+f"(d[34]), "+f"(d[35]), "+f"(d[36]), "+f"(d[37]), "+f"(d[38]), "+f"(d[39]), "+f"(d[40]), "+f"(d[41]), "+f"(d[42]), "+f"(d[43]), "+f"(d[44]), "+f"(d[45]), "+f"(d[46]), "+f"(d[47]), "+f"(d[48]), "+f"(d[49]), "+f"(d[50]), "+f"(d[51]), "+f"(d[52]), "+f"(d[53]), "+f"(d[54]), "+f"(d[55]), "+f"(d[56]), "+f"(d[57]), "+f"(d[58]), "+f"(d[59]), "+f"(d[60]), "+f"(d[61]), "+f"(d[62]), "+f"(d[63]), "+f"(d[64]), "+f"(d[65]), "+f"(d[66]), "+f"(d[67]), "+f"(d[68]), "+f"(d[69]), "+f"(d[70]), "+f"(d[71]), "+f"(d[72]), "+f"(d[73]), "+f"(d[74]), "+f"(d[75]), "+f"(d[76]), "+f"(d[77]), "+f"(d[78]), "+f"(d[79]), "+f"(d[80]), "+f"(d[81]), "+f"(d[82]), "+f"(d[83])
        : "l"(da), "l"(db), "r"(acc));
}
DEVI void wgmma_rs96t(float (&d)[48], uint32_t a0, uint32_t a1, uint32_t a2, uint32_t a3, uint64_t db, int acc) {
    asm volatile("{.reg .pred p; setp.ne.b32 p, %53, 0;\n"
        "wgmma.mma_async.sync.aligned.m64n96k16.f32.bf16.bf16 {%0,%1,%2,%3,%4,%5,%6,%7,%8,%9,%10,%11,%12,%13,%14,%15,%16,%17,%18,%19,%20,%21,%22,%23,%24,%25,%26,%27,%28,%29,%30,%31,%32,%33,%34,%35,%36,%37,%38,%39,%40,%41,%42,%43,%44,%45,%46,%47}, {%48,%49,%50,%51}, %52, p, 1, 1, 1;}"
        : "+f"(d[0]), "+f"(d[1]), "+f"(d[2]), "+f"(d[3]), "+f"(d[4]), "+f"(d[5]), "+f"(d[6]), "+f"(d[7]), "+f"(d[8]), "+f"(d[9]), "+f"(d[10]), "+f"(d[11]), "+f"(d[12]), "+f"(d[13]), "+f"(d[14]), "+f"(d[15]), "+f"(d[16]), "+f"(d[17]), "+f"(d[18]), "+f"(d[19]), "+f"(d[20]), "+f"(d[21]), "+f"(d[22]), "+f"(d[23]), "+f"(d[24]), "+f"(d[25]), "+f"(d[26]), "+f"(d[27]), "+f"(d[28]), "+f"(d[29]), "+f"(d[30]), "+f"(d[31]), "+f"(d[32]), "+f"(d[33]), "+f"(d[34]), "+f"(d[35]), "+f"(d[36]), "+f"(d[37]), "+f"(d[38]), "+f"(d[39]), "+f"(d[40]), "+f"(d[41]), "+f"(d[42]), "+f"(d[43]), "+f"(d[44]), "+f"(d[45]), "+f"(d[46]), "+f"(d[47])
        : "r"(a0), "r"(a1), "r"(a2), "r"(a3), "l"(db), "r"(acc));
}
DEVI void wgmma_rs192t(float (&d)[96], uint32_t a0, uint32_t a1, uint32_t a2, uint32_t a3, uint64_t db, int acc) {
    asm volatile("{.reg .pred p; setp.ne.b32 p, %101, 0;\n"
        "wgmma.mma_async.sync.aligned.m64n192k16.f32.bf16.bf16 {%0,%1,%2,%3,%4,%5,%6,%7,%8,%9,%10,%11,%12,%13,%14,%15,%16,%17,%18,%19,%20,%21,%22,%23,%24,%25,%26,%27,%28,%29,%30,%31,%32,%33,%34,%35,%36,%37,%38,%39,%40,%41,%42,%43,%44,%45,%46,%47,%48,%49,%50,%51,%52,%53,%54,%55,%56,%57,%58,%59,%60,%61,%62,%63,%64,%65,%66,%67,%68,%69,%70,%71,%72,%73,%74,%75,%76,%77,%78,%79,%80,%81,%82,%83,%84,%85,%86,%87,%88,%89,%90,%91,%92,%93,%94,%95}, {%96,%97,%98,%99}, %100, p, 1, 1, 1;}"
        : "+f"(d[0]), "+f"(d[1]), "+f"(d[2]), "+f"(d[3]), "+f"(d[4]), "+f"(d[5]), "+f"(d[6]), "+f"(d[7]), "+f"(d[8]), "+f"(d[9]), "+f"(d[10]), "+f"(d[11]), "+f"(d[12]), "+f"(d[13]), "+f"(d[14]), "+f"(d[15]), "+f"(d[16]), "+f"(d[17]), "+f"(d[18]), "+f"(d[19]), "+f"(d[20]), "+f"(d[21]), "+f"(d[22]), "+f"(d[23]), "+f"(d[24]), "+f"(d[25]), "+f"(d[26]), "+f"(d[27]), "+f"(d[28]), "+f"(d[29]), "+f"(d[30]), "+f"(d[31]), "+f"(d[32]), "+f"(d[33]), "+f"(d[34]), "+f"(d[35]), "+f"(d[36]), "+f"(d[37]), "+f"(d[38]), "+f"(d[39]), "+f"(d[40]), "+f"(d[41]), "+f"(d[42]), "+f"(d[43]), "+f"(d[44]), "+f"(d[45]), "+f"(d[46]), "+f"(d[47]), "+f"(d[48]), "+f"(d[49]), "+f"(d[50]), "+f"(d[51]), "+f"(d[52]), "+f"(d[53]), "+f"(d[54]), "+f"(d[55]), "+f"(d[56]), "+f"(d[57]), "+f"(d[58]), "+f"(d[59]), "+f"(d[60]), "+f"(d[61]), "+f"(d[62]), "+f"(d[63]), "+f"(d[64]), "+f"(d[65]), "+f"(d[66]), "+f"(d[67]), "+f"(d[68]), "+f"(d[69]), "+f"(d[70]), "+f"(d[71]), "+f"(d[72]), "+f"(d[73]), "+f"(d[74]), "+f"(d[75]), "+f"(d[76]), "+f"(d[77]), "+f"(d[78]), "+f"(d[79]), "+f"(d[80]), "+f"(d[81]), "+f"(d[82]), "+f"(d[83]), "+f"(d[84]), "+f"(d[85]), "+f"(d[86]), "+f"(d[87]), "+f"(d[88]), "+f"(d[89]), "+f"(d[90]), "+f"(d[91]), "+f"(d[92]), "+f"(d[93]), "+f"(d[94]), "+f"(d[95])
        : "r"(a0), "r"(a1), "r"(a2), "r"(a3), "l"(db), "r"(acc));
}

#define TRD(t, i)
namespace km {
#define NSS 6
#define RG "184"
#define RW "136"
#define NFL 2
#define EK 7
#define FK 3
#define LDP 3
#define SND 1
constexpr int O_H = 0;
constexpr int O_MB = 73728;
constexpr int O_VX = 96768;
constexpr int O_KX = 113152;
constexpr int O_QX = 119296;
constexpr int O_VM = 125440;
constexpr int O_KM = 129536;
constexpr int O_QM = 131072;
constexpr int O_SM = 132608;
constexpr int O_ST = 135168;
constexpr int O_OX = 145408;
constexpr int O_WO = 149504;
constexpr int O_OS = O_WO;
constexpr int O_WS = O_WO + 49152;
constexpr int O_RL = 110592;
constexpr int O_BAR = O_WS + NSS * 4096;
constexpr int SMEM = O_BAR + 128 + 1024 + TR_BYTES;
enum { B_X = 0, B_WIN = 16, B_VX = 24, B_SM = 32, B_ST = 40, B_EP = 56 };
#define DLY1 (tune.v[0] + tune.v[4] * w)
#define DLY2 tune.v[1]
#define EARLY tune.v[2]
#define DLYO tune.v[3]
#define DLY0 tune.v[5]
#define DLYX tune.v[6]
#define DLYP tune.v[7]
#define DLYW tune.v[8]
#define DLYB tune.v[9]
constexpr uint32_t DESC_HI = (1024 >> 4) | (1u << 30);
constexpr float SC = 0.08838834764831845f * 1.4426950408889634f;
}

__global__ void __cluster_dims__(3, 1, 1) __launch_bounds__(384, 1)
k_main(const __nv_bfloat16* __restrict__ x0, const __nv_bfloat16* __restrict__ wqkv, const __nv_bfloat16* __restrict__ wo,
       const __nv_bfloat16* __restrict__ mem0, const __nv_bfloat16* __restrict__ Wq, const __nv_bfloat16* __restrict__ Wk,
       const __nv_bfloat16* __restrict__ Wv, const __nv_bfloat16* __restrict__ Wo, const Tune tune) {
    using namespace km;
    extern __shared__ unsigned char smem_raw[];
    const uint32_t sb = (smem_u32(smem_raw) + 1023) & ~1023u;
    const int tid = threadIdx.x, lane = tid & 31, warp = __shfl_sync(~0u, tid >> 5, 0);
    uint32_t l16 = __shfl_sync(~0u, lane * 16, lane);
#define OPQ() asm volatile("" : "+r"(l16))
    const int b = blockIdx.x, h = b / 3, r = b % 3;
    const int nq = r == 2 ? 2 : 3;
    const uint32_t bar = sb + O_BAR;
    asm volatile("griddepcontrol.launch_dependents;");
    const uint32_t t_start = clk();
    if (warp == 0 && b < 72) {
        if (lane == 0) { mbar_init(bar + 96, 1); fence_async_smem(); mbar_expect(bar + 96, 8 * 3456, true); }
        __syncwarp();
        if (lane < 8) asm volatile("cp.async.bulk.shared::cluster.global.mbarrier::complete_tx::bytes [%0], [%1], 3456, [%2];" :: "r"(sb + O_RL + lane * 3472), "l"(wqkv + (b * 8 + lane) * 1728), "r"(bar + 96) : "memory");
    }
    if (tid == 352) {
        prefetch_l2(x0 + b * (2 * DM), 2 * 1152); prefetch_l2(wo + b * (6 * DM), 6 * 1152);
    }
    if (tid == 320) sts32(bar + 64, ldg32(&g_epoch));
#define EP lds32(bar + 64)
    TR_INIT(bar + 128);
    TRG(79, 0);
    uint32_t roff0, roff1;
    {
        uint32_t y0, y1;
        asm("mapa.shared::cluster.u32 %0, %1, %2;" : "=r"(y0) : "r"(sb), "r"((r + 1) % 3));
        asm("mapa.shared::cluster.u32 %0, %1, %2;" : "=r"(y1) : "r"(sb), "r"((r + 2) % 3));
        roff0 = y0 - sb; roff1 = y1 - sb;
    }
#define IDENT (((l16 >> 7) == ((l16 >> 4) & 3) ? 0x3f80u : 0u) << ((l16 >> 2) & 16))
#define LSWAP ((l16 & 0x70) | ((l16 & 0x80) << 1) | ((l16 & 0x100) >> 1))
    const uint32_t nv_remote = 8 - (8 - 2 * nq);

    auto fetch_tile = [&](int u) {
        fence_async_global();
        TRG(u, 0);
        const bool a0 = u < NSEG, a1 = u >= LAG;
        mbar_expect(bar + B_X, ((int)a0 + (int)a1) * 36864, l16 == 0);
        const uint32_t off = r * 24576 + (l16 << 9) + (a0 ? 0 : 4096);
        asm volatile("{.reg .pred p; setp.lt.u32 p, %5, %6;\n"
            "@p cp.async.bulk.shared::cluster.global.mbarrier::complete_tx::bytes.multicast::cluster [%0], [%1], %4, [%2], %3;}"
            :: "r"(sb + O_H + off), "l"(reinterpret_cast<const char*>(g_xt + u * 4608) + off), "r"(bar + B_X), "h"((uint16_t)7),
               "r"(a0 && a1 ? 24576 : 4096), "r"(l16), "r"(a0 && a1 ? 16 : 48) : "memory");
    };

    int warp_ = warp;
    asm volatile("" : "+r"(warp_));
    if (warp_ < 8) {
        const int ci = tid & 15, slot = ci >> 1, d0 = tid >> 4;
        const __nv_bfloat16* src = slot < nq ? Wq + (3 * r + slot) * 16 : slot < 2 * nq ? Wk + (3 * r + slot - nq) * 16 : Wv + (2 * r + slot - 2 * nq) * 16;
        src += h * 128 + (ci & 1) * 8 + d0 * 4096;
        if (b < 72) {
            bar_sync(10, 256);
            mbar_wait(bar + 96, 0);
            TR1(4);
#pragma unroll 2
            for (int ag = tid >> 3; ag < 231; ag += 32) {
                const int a = ag / 21, gr = ag % 21, tl = gr >= 18;
                const int head = 3 * a + (tl ? 0 : (gr % 6) >> 1), nw = tl ? min(3, 32 - head) : head < 32 ? 4 : 0;
                const uint32_t p = sb + O_RL + (tid & 7) * 3472 + (tl ? gr - 18 : gr / 6) * 1152 + head * 36 + (tl ? 32 : (gr & 1) * 16), step = tl ? 36 : 4;
                uint32_t v[4];
#pragma unroll
                for (int i = 0; i < 4; i++) { v[i] = lds32(p + i * step); if (i >= nw) v[i] = 0; }
                stg128(g_wa + ((a * 9 + (b >> 3)) * 21 + gr) * 64 + (b & 7) * 8 + (tid & 7), v[0], v[1], v[2], v[3]);
            }
        }
        {
            bar_arrive(15, 288);
            TR1(5);
            delay_until(t_start, DLY0);
            uint32_t dst = sb + d0 * 256 + ((ci ^ (d0 & 7)) << 4);
#pragma unroll 1
            for (int q = 0; q < 12; q++, dst += 12288, src += 3 * 65536) {
#pragma unroll
                for (int i = 0; i < 3; i++) cp16(dst + i * 4096, src + i * 65536);
                cp_commit();
                cp_wait<NFL - 1>();
                if (q == 7) bar_sync(10, 256);
            }
            cp_wait_all();
            bar_sync(10, 256);
        }
        TR1(1);
    }
    if (warp < 8) {
        asm volatile("setmaxnreg.inc.sync.aligned.u32 " RG ";");
        constexpr int SSP = 36 / NSS;
#define IS_SS(kk) ((kk) % SSP == 3)
#define AI(kk) (4 * ((kk) - ((kk) + SSP - 4) / SSP))
        uint32_t a[144 - 4 * NSS];
        {
            const int mi = lane >> 3;
            const uint32_t ad = sb + ((mi >> 1) * 8 + (lane & 7)) * 256 + (((warp * 2 + (mi & 1)) ^ (lane & 7)) << 4);
#pragma unroll
            for (int kk = 0; kk < 36; kk++) {
                const uint4 f = ldsm4t(ad + kk * 4096);
                if (IS_SS(kk)) {
                    const uint32_t o0 = sb + O_WS + (kk / SSP) * 4096 + warp * 512 + lane * 4;
                    sts32(o0, f.x); sts32(o0 + 256, f.y); sts32(o0 + 128, f.z); sts32(o0 + 384, f.w);
                } else { a[AI(kk)] = f.x; a[AI(kk) + 1] = f.y; a[AI(kk) + 2] = f.z; a[AI(kk) + 3] = f.w; }
            }
            TR1(2);
            bar_sync(9, 384);
#pragma unroll
            for (int i = 0; i < 9; i++) sts128(sb + O_H + i * 8192 + 4096 + tid * 16, 0, 0, 0, 0);
#pragma unroll
            for (int i = 0; i < 8; i++) if (i * 256 + tid < (O_OX - O_KX) / 16) sts128(sb + O_KX + i * 4096 + tid * 16, 0, 0, 0, 0);
            fence_async_smem();
            cluster_sync();
        }
        TR1(3);
        const int kind = warp < nq ? 0 : warp < 2 * nq ? 1 : 2;
        const int sl = kind == 0 ? warp : kind == 1 ? warp - nq : 2 * r + warp - 2 * nq;
        const uint32_t adX0 = sb + (kind == 0 ? O_QX : kind == 1 ? O_KX : O_VX) + sl * 2048;
        const uint32_t adM0 = sb + (kind == 0 ? O_QM : kind == 1 ? O_KM : O_VM) + sl * 512;
        const uint32_t hlo = (((sb + O_H) >> 4) & 0x3fff) | (1u << 16);
        const uint32_t mlo = (((sb + O_MB) >> 4) & 0x3fff) | (16u << 16);
        const uint32_t wlo = (((sb + O_WS + (warp >> 2) * 2048) >> 4) & 0x3fff) | (8u << 16);
        const int L = (warp >> 1) & 1, qh = warp & 1;
        const uint32_t st = sb + O_ST + warp * 1280;

#pragma unroll 1
        for (int t = -1;; t++) {
            TR_ON(t);
            OPQ();
            const uint32_t adX = adX0 + l16, adM = adM0 + l16, l8 = l16 >> 1;
            const uint32_t lq = LSWAP;
            if (t >= 0) {
                float d0[8], d1[8];
                {
#pragma unroll
                    for (int G = 0; G < 3; G++) {
                        if (warp < 4) bar_sync(1 + G, 160); else bar_sync(12 + G, 160);
                        if (G == 0) wg_fence();
#pragma unroll
                        for (int q = 0; q < 12; q++) {
                            const int kk = 12 * G + q;
                            const uint64_t db = mkdesc(mlo + kk * 32, 8);
                            if (IS_SS(kk)) wgmma_ss16t((kk & 1) ? d1 : d0, mkdesc(wlo + (kk / SSP) * 256, 16), db, 1);
                            else wgmma_rs16t((kk & 1) ? d1 : d0, a[AI(kk)], a[AI(kk) + 1], a[AI(kk) + 2], a[AI(kk) + 3], db, kk >= 2);
                            if (kk == 0) TR(0);
                        }
                    }
                    wg_commit();
                }
#define PM(i) pk(d0[2 * (i)] + d1[2 * (i)], d0[2 * (i) + 1] + d1[2 * (i) + 1])
                if (warp >= 4) {
                    wg_wait<0>();
                    TR(1);
                    const uint32_t p0 = PM(0), p1 = PM(1), p2 = PM(2), p3 = PM(3);
                    if (kind == 2) {
                        sts128(adM, p0, p1, p2, p3);
                        bar_arrive(4, 384);
                        sta128(adM + roff0, p0, p1, p2, p3, bar + B_SM + roff0);
                        sta128(adM + roff1, p0, p1, p2, p3, bar + B_SM + roff1);
                    } else {
                        stsm4t(adM, p0, p1, p2, p3);
                        bar_arrive(4, 384);
                    }
                } else {
                    uint4 q[3], k[3][2];
                    mbar_wait(bar + B_EP, t & 1);
#pragma unroll
                    for (int m = 0; m < LDP; m++) {
                        q[m] = ldsm4(sb + O_QX + m * 2048 + warp * 512 + lq);
                        k[m][0] = ldsm4(sb + O_KX + m * 2048 + L * 1024 + l16); k[m][1] = ldsm4(sb + O_KX + m * 2048 + L * 1024 + 512 + l16);
                    }
                    wg_wait<0>();
                    TR(1);
                    stsm4t(adM, PM(0), PM(1), PM(2), PM(3));
                    bar_arrive(4, 384);
                    sched_fence(gridDim.y, 6);
#pragma unroll
                    for (int m = LDP; m < 3; m++) {
                        q[m] = ldsm4(sb + O_QX + m * 2048 + warp * 512 + lq);
                        k[m][0] = ldsm4(sb + O_KX + m * 2048 + L * 1024 + l16); k[m][1] = ldsm4(sb + O_KX + m * 2048 + L * 1024 + 512 + l16);
                    }
                    float s[5][4];
                    {
                        float y[4] = {0, 0, 0, 0};
#pragma unroll
                        for (int n = 0; n < 5; n++) s[n][0] = s[n][1] = s[n][2] = s[n][3] = 0.f;
#pragma unroll
                        for (int m = 0; m < 3; m++) {
                            mma16(s[0], q[m].x, q[m].y, q[m].z, q[m].w, k[m][0].x, k[m][0].y); mma16(s[1], q[m].x, q[m].y, q[m].z, q[m].w, k[m][0].z, k[m][0].w);
                            mma16(s[2], q[m].x, q[m].y, q[m].z, q[m].w, k[m][1].x, k[m][1].y); mma16(s[3], q[m].x, q[m].y, q[m].z, q[m].w, k[m][1].z, k[m][1].w);
                        }
                        auto send = [&]() {
                            uint32_t w0 = pk(s[0][0], s[0][1]), w1 = pk(s[0][2], s[0][3]), w2 = pk(s[1][0], s[1][1]), w3 = pk(s[1][2], s[1][3]);
                            sta128(st + l16 + 5120 + roff0, w0, w1, w2, w3, bar + B_ST + roff0);
                            sta128(st + l16 + roff1, w0, w1, w2, w3, bar + B_ST + roff1);
                            w0 = pk(s[2][0], s[2][1]); w1 = pk(s[2][2], s[2][3]); w2 = pk(s[3][0], s[3][1]); w3 = pk(s[3][2], s[3][3]);
                            sta128p(st + l16 + 5120 + 512 + roff0, w0, w1, w2, w3, bar + B_ST + roff0, qh);
                            sta128p(st + l16 + 512 + roff1, w0, w1, w2, w3, bar + B_ST + roff1, qh);
                        };
                        sched_fence(gridDim.y, 7);
                        bar_sync(5, 256);
                        const uint4 k01 = ldsm4(sb + O_KM + L * 256 + l16 + (l16 & 256));
                        const uint2 k2 = ldsm2(sb + O_KM + 1024 + L * 256 + l16);
                        if (SND == 0) send();
                        mma16(s[4], q[0].x, q[0].y, q[0].z, q[0].w, k01.x, k01.y);
                        mma16(y, q[1].x, q[1].y, q[1].z, q[1].w, k01.z, k01.w);
                        mma16(s[4], q[2].x, q[2].y, q[2].z, q[2].w, k2.x, k2.y);
#pragma unroll
                        for (int j = 0; j < 4; j++) s[4][j] += y[j];
                        const uint32_t w0 = pk(s[4][0], s[4][1]), w1 = pk(s[4][2], s[4][3]);
                        sta64(st + l8 + 5120 + 1024 + roff0, w0, w1, bar + B_ST + roff0);
                        sta64(st + l8 + 1024 + roff1, w0, w1, bar + B_ST + roff1);
                        if (SND == 1) send();
                        TR(2);
                        const int lim = 16 * qh + (int)(l16 >> 6) - (int)((l16 >> 3) & 6);
#pragma unroll
                        for (int n = 0; n < 4; n++)
#pragma unroll
                            for (int j = 0; j < 4; j++) if (!(n == 0 && j >= 2) && 8 * (n - (j >> 1)) + (j & 1) > lim) s[n][j] = -1e30f;
#pragma unroll
                        for (int n = 0; n < 4; n++) asm volatile("" : "+f"(s[n][0]), "+f"(s[n][1]), "+f"(s[n][2]), "+f"(s[n][3]));
                    }
                    uint4 v0[3], v1[3]; uint2 vm[3];
                    const uint32_t vad = sb + O_VX + 3 * r * 2048 + L * 1024 + l16;
#pragma unroll
                    for (int m = 0; m < 3; m++) v0[m] = lds128(vad + m * 2048);
                    const uint32_t otag = ring_tag(t, EP);
                    uint32_t ident = IDENT;
                    asm volatile("" : "+r"(ident));
                    mbar_wait(bar + B_SM, t & 1);
                    mbar_wait(bar + B_ST, t & 1);
                    TR(3);
                    float mx0, mx1;
                    {
                        const uint4 u = lds128(st + l16), v = lds128(st + 512 + l16); const uint2 w = lds64(st + 1024 + l8);
                        const uint4 x = lds128(st + 5120 + l16), y = lds128(st + 5120 + 512 + l16); const uint2 z = lds64(st + 5120 + 1024 + l8);
                        mma8(s[0], u.x, u.y, ident); mma8(s[1], u.z, u.w, ident); mma8(s[2], v.x, v.y, ident); mma8(s[3], v.z, v.w, ident); mma8(s[4], w.x, w.y, ident);
                        mma8(s[0], x.x, x.y, ident); mma8(s[1], x.z, x.w, ident); mma8(s[2], y.x, y.y, ident); mma8(s[3], y.z, y.w, ident); mma8(s[4], z.x, z.y, ident);
                        mx0 = fmaxf(fmaxf(fmaxf(s[0][0], s[0][1]), fmaxf(s[1][0], s[1][1])), fmaxf(fmaxf(s[2][0], s[2][1]), fmaxf(s[3][0], s[3][1])));
                        mx1 = fmaxf(fmaxf(fmaxf(s[0][2], s[0][3]), fmaxf(s[1][2], s[1][3])), fmaxf(fmaxf(s[2][2], s[2][3]), fmaxf(s[3][2], s[3][3])));
                        mx0 = fmaxf(mx0, fmaxf(s[4][0], s[4][1])); mx1 = fmaxf(mx1, fmaxf(s[4][2], s[4][3]));
                    }
#pragma unroll
                    for (int o = 1; o < 4; o <<= 1) { const float2 z = shfl2(mx0, mx1, o); mx0 = fmaxf(mx0, z.x); mx1 = fmaxf(mx1, z.y); }
                    mx0 *= -SC; mx1 *= -SC;
                    float l[4] = {0, 0, 0, 0};
                    uint32_t p[10];
#pragma unroll
                    for (int n = 0; n < 5; n++) {
                        const float e0 = ex2(fmaf(s[n][0], SC, mx0)), e1 = ex2(fmaf(s[n][1], SC, mx0));
                        const float e2 = ex2(fmaf(s[n][2], SC, mx1)), e3 = ex2(fmaf(s[n][3], SC, mx1));
                        p[2 * n] = pk(e0, e1); p[2 * n + 1] = pk(e2, e3);
                        mma8(l, p[2 * n], p[2 * n + 1], 0x3f803f80);
                    }
#pragma unroll
                    for (int m = 0; m < 3; m++) vm[m] = lds64(sb + O_VM + (3 * r + m) * 512 + l16 + L * 8);
                    sched_fence(gridDim.y, 5);
                    const float l0 = rcp(l[0]), l1 = rcp(l[2]);
                    float o[6][4];
#pragma unroll
                    for (int m = 0; m < 6; m++) o[m][0] = o[m][1] = o[m][2] = o[m][3] = 0.f;
#pragma unroll
                    for (int m = 0; m < 3; m++) { mma8(o[2 * m], p[0], p[1], v0[m].x); mma8(o[2 * m + 1], p[0], p[1], v0[m].y); }
#pragma unroll
                    for (int m = 0; m < 3; m++) { mma8(o[2 * m], p[2], p[3], v0[m].z); mma8(o[2 * m + 1], p[2], p[3], v0[m].w); v1[m] = lds128(vad + m * 2048 + 512); }
#pragma unroll
                    for (int m = 0; m < 3; m++) { mma8(o[2 * m], p[8], p[9], vm[m].x); mma8(o[2 * m + 1], p[8], p[9], vm[m].y); }
#pragma unroll
                    for (int m = 0; m < 3; m++) { mma8(o[2 * m], p[4], p[5], v1[m].x); mma8(o[2 * m + 1], p[4], p[5], v1[m].y); }
#pragma unroll
                    for (int m = 0; m < 3; m++) { mma8(o[2 * m], p[6], p[7], v1[m].z); mma8(o[2 * m + 1], p[6], p[7], v1[m].w); }
                    sched_fence(gridDim.y, 8);
                    if (t + 1 < NT) bar_arrive(11, 384);
#pragma unroll
                    for (int m = 0; m < 3; m++)
                        sts128(sb + O_OS + warp * 512 + m * 2048 + l16, (pk(o[2 * m][0] * l0, o[2 * m][1] * l0) & ~1u) | otag, pk(o[2 * m][2] * l1, o[2 * m][3] * l1),
                               pk(o[2 * m + 1][0] * l0, o[2 * m + 1][1] * l0), pk(o[2 * m + 1][2] * l1, o[2 * m + 1][3] * l1));
                    TR(4);
                }
            }
            if (t + 1 >= NT) break;
            {
                float d[32];
                if (warp < 4) { if (t < 0) mbar_wait(bar + B_X, 0); bar_sync(7, 256); }
                else {
                    if (warp == 7) {
                        if (t >= 0) { mbar_wait(bar + B_EP, t & 1); mbar_wait(bar + B_VX, t & 1); }
                        if (__shfl_sync(~0u, lds_acq(bar + 8), 0) != t + 1) cnt_wait(g_cnt + (C_X + t + 1) * 8, 64 * (EP + 1));
                        else if (DLYX) pause(DLYX);
                        fetch_tile(t + 1);
                        TR(2);
                    }
                    mbar_wait(bar + B_X, (t + 1) & 1);
                    TR(3);
                    if (t >= 0) bar_sync(11, 384);
                }
                wg_fence();
                TR(6);
#pragma unroll
                for (int kk = 0; kk < 36; kk++) {
                    const uint64_t db = mkdesc(hlo + ((kk >> 2) * 8192 + (kk & 3) * 32) / 16, DESC_HI);
                    if (IS_SS(kk)) wgmma_ss64(d, mkdesc(wlo + (kk / SSP) * 256, 16), db, 1);
                    else wgmma_rs64(d, a[AI(kk)], a[AI(kk) + 1], a[AI(kk) + 2], a[AI(kk) + 3], db, kk > 0);
                }
                wg_commit();
                TR(5);
                mbar_wait(bar + B_WIN, (t + 1) & 1);
                wg_wait<0>();
                TR(7);
                uint32_t p[16];
#pragma unroll
                for (int u = 0; u < 16; u++) p[u] = pk(d[2 * u], d[2 * u + 1]);
                if (kind == 2) {
#pragma unroll
                    for (int u = 0; u < 4; u++) sts128(adX + u * 512, p[4 * u], p[4 * u + 1], p[4 * u + 2], p[4 * u + 3]);
                } else {
#pragma unroll
                    for (int u = 0; u < 4; u++) stsm4t(adX + u * 512, p[4 * u], p[4 * u + 1], p[4 * u + 2], p[4 * u + 3]);
                }
                __syncwarp();
                asm volatile("{.reg .pred p; setp.eq.u32 p, %1, 0; @p mbarrier.arrive.shared.b64 _, [%0];}" :: "r"(bar + B_EP), "r"(l16) : "memory");
                TR(8);
            }
        }
        if (warp < 4) bar_arrive(7, 160);
        cluster_sync();
    } else {
        asm volatile("setmaxnreg.dec.sync.aligned.u32 " RW ";");
        const int w = warp - 8, t2 = tid - 256;
        if (t2 == 0) {
            mbar_init(bar + B_X, 1); sts32(bar + 8, ~0u); mbar_init(bar + B_WIN, 3);
            mbar_init(bar + B_VX, 1); mbar_init(bar + B_SM, 1); mbar_init(bar + B_ST, 1); mbar_init(bar + B_EP, 8);
            asm volatile("fence.mbarrier_init.release.cluster;" ::: "memory");
        }
        char* const ex = reinterpret_cast<char*>((reinterpret_cast<uintptr_t>(g_ex) + 0x1fffff) & ~(uintptr_t)0x1fffff);
        char* rbase = ex; uint32_t side = 0;
        {
            uint32_t m0[5][4];
#pragma unroll
            for (int i = 0; i < 5; i++) {
                const unsigned short* m = reinterpret_cast<const unsigned short*>(mem0) + min(i * 128 + t2, DM - 1);
#pragma unroll
                for (int j = 0; j < 4; j++) m0[i][j] = m[2 * j * DM] | (m[(2 * j + 1) * DM] << 16);
            }
            if (w == 3) { bar_sync(15, 288); cnt_add(g_cnt + C_W * 8, lane); TR1(1); }
            else {
                if (w < 2) {
                    unsigned* pp = reinterpret_cast<unsigned*>(ex + inbox_off(b) + 16384 + w * 4096 + 2048);
                    uint32_t best = ~0u, v = 0;
                    if (lane == 0) {
#pragma unroll 1
                        for (int i = 0; i < 5; i++) {
                            const uint32_t c0 = clk();
                            v = atomicAdd(pp + (v >> 31), 0);
                            asm volatile("" :: "r"(v) : "memory");
                            sts32(bar + 80, v);
                            best = min(best, clk() - c0);
                        }
                        sts32(bar + 72 + w * 4, best);
                    }
                }
                bar_sync(8, 96);
                const uint32_t xs = lds32(bar + 76) < lds32(bar + 72), ep = EP;
                side = xs ^ page_par(inbox_off(b));
                rbase = ex + inbox_off(b) + xs * 4096;
                const uint32_t inv = (ep * (NT - 1)) & 1;
#pragma unroll
                for (int i = 0; i < 4; i++) stg128(rbase + (w == 2 ? 16384 : w * 2048) + i * 512 + lane * 16, inv, 0, 0, 0);
                __threadfence();
                bar_sync(8, 96);
                if (t2 == 0) stg_word(g_side + b, (ep + 1) * 2 + xs, true);
                TR1(4);
            }
            delay_until(t_start, DLYW);
#pragma unroll 4
            for (int i = t2; i < 128 * 24; i += 128) {
                const int e = (i >> 3) & 127, G = i >> 10, q = i & 7;
                cp16(sb + O_WO + G * 16384 + e * 128 + ((q ^ (e & 7) ^ ((h >> 1) & 1)) << 4), Wo + (size_t)(h * 128 + e) * DM + G * 192 + r * 64 + q * 8);
            }
            bar_sync(9, 384);
#pragma unroll
            for (int i = 0; i < 5; i++) {
                const int k = min(i * 128 + t2, DM - 1);
                const uint32_t ad = sb + O_MB + (k >> 3) * 256 + (k & 7) * 16;
                sts128(ad, m0[i][0], m0[i][1], m0[i][2], m0[i][3]); sts128(ad + 128, m0[i][0], m0[i][1], m0[i][2], m0[i][3]);
            }
            fence_async_smem();
        }
        auto arm = [&]() {
            const uint32_t ln = l16 >> 4;
            mbar_expect(bar + B_VX + (ln & 3) * 8, ln == 0 ? nv_remote * 2048 : ln == 1 ? nv_remote * 512 + 2560 : 8192, ln < 3);
        };
        if (w == 3) arm();
        cluster_sync();
        TR1(3);
        const int L = w >> 1, hf = w & 1;
        const uint32_t rd = hf ? roff1 : roff0;
        const uint32_t rzero = gridDim.y + 100;
#define WOAD (sb + O_WO + ((l16 & 0x100) << 2) + ((l16 & 0x70) << 3) + (((w * 32) | ((l16 >> 3) & 16)) ^ (l16 & 0x70)))

        auto store_o = [&](int u) {
            asm volatile("{.reg .pred p; setp.eq.u32 p, %3, 0;\n"
                "@p cp.async.bulk.global.shared::cta.bulk_group [%0], [%1], %2;\n cp.async.bulk.commit_group;}"
                :: "l"(g_o + ((u & (RING - 1)) * 256 + h * 8 + 3 * r) * 128), "r"(sb + O_OS), "r"(nq * 2048), "r"(l16) : "memory");
            cnt_hint(g_cnt + (C_O + u * 8 + (h >> 2)) * 8, l16);
            TRG(u, 2);
        };
        bar_arrive(7, 256);
        if (w < 3) {
            bar_arrive(1 + w, 160); bar_arrive(12 + w, 160);
        } else {
            mbar_arrive_all3(bar + B_WIN, l16 >> 4);

        }
        cp_wait_all();
        bar_sync(6, 128);
        uint32_t poff;
        {
            const int rb = r * 32 + w * 8 + (lane >> 2);
            const uint32_t want = EP + 1;
            uint32_t v;
            for (int n = 0; __any_sync(~0u, ((v = ldg_word(g_side + rb)) >> 1) != want); n++) fault_if(n > POLL_LIMIT, n);
            __threadfence();
            poff = inbox_off(rb) + (v & 1) * 4096 + h * 64 + (lane & 3) * 16;
        }
        side = __shfl_sync(~0u, side, 0);
        const uint32_t roff = __shfl_sync(~0u, (uint32_t)(rbase - ex), 0) + (w == 2 ? 16384 : (w & 1) * 2048);
        uint4 a0[8];
#pragma unroll
        for (int kk = 0; kk < 8; kk++) a0[kk] = ldsm4t(WOAD + kk * 2048);
#pragma unroll 1
        for (int t = 0;; t++) {
            TR_ON(t);
            OPQ();
            mbar_wait(bar + B_EP, t & 1);
            if (w == 3) {
                fence_async_smem();
                const uint32_t ad = sb + O_VX + r * 4096;
                asm volatile("{.reg .pred p; setp.eq.u32 p, %5, 0;\n"
                    "@p cp.async.bulk.shared::cluster.shared::cta.mbarrier::complete_tx::bytes [%0], [%2], %6, [%3];\n"
                    "@p cp.async.bulk.shared::cluster.shared::cta.mbarrier::complete_tx::bytes [%1], [%2], %6, [%4];}"
                    :: "r"(ad + roff0), "r"(ad + roff1), "r"(ad), "r"(bar + B_VX + roff0), "r"(bar + B_VX + roff1), "r"(l16), "r"(16384 - 4096 * nq) : "memory");
                TR(7);
            }
            uint4 kx[3][2], vx[4][2];
            const uint32_t lp = LSWAP;
#pragma unroll
            for (int m = 0; m < 3; m++) {
                kx[m][0] = ldsm4(sb + O_KX + m * 2048 + L * 1024 + lp);
                kx[m][1] = ldsm4(sb + O_KX + m * 2048 + L * 1024 + 512 + lp);
            }
            if (w == 3) {
                asm volatile("cp.async.bulk.wait_group.read 0;" ::: "memory");
                if (__shfl_sync(~0u, lds32(bar + 8), 0) != t + 1) cnt_look(g_cnt + (C_X + t + 1) * 8, 64 * (EP + 1), bar + 8, t + 1);
            }
            mbar_wait(bar + B_VX, t & 1);
            TR(0);
            bar_sync(4, 384);
            float s0[4] = {0, 0, 0, 0}, s1[4] = {0, 0, 0, 0}, sm[4] = {0, 0, 0, 0};
            {
                const uint4 q01 = ldsm4(sb + O_QM + L * 256 + l16 + (l16 & 256));
                const uint2 q2 = ldsm2(sb + O_QM + 1024 + L * 256 + l16);
                uint4 km_[3];
#pragma unroll
                for (int m = 0; m < 3; m++) km_[m] = ldsm4(sb + O_KM + m * 512 + (lp ^ (L << 8)));
                mma16(s0, kx[0][0].x, kx[0][0].y, kx[0][0].z, kx[0][0].w, q01.x, q01.y);
                mma16(s1, kx[0][1].x, kx[0][1].y, kx[0][1].z, kx[0][1].w, q01.x, q01.y);
                mma16(sm, km_[0].x, km_[0].y, km_[0].z, km_[0].w, q01.x, q01.y);
                mma16(s0, kx[1][0].x, kx[1][0].y, kx[1][0].z, kx[1][0].w, q01.z, q01.w);
                mma16(s1, kx[1][1].x, kx[1][1].y, kx[1][1].z, kx[1][1].w, q01.z, q01.w);
                mma16(sm, km_[1].x, km_[1].y, km_[1].z, km_[1].w, q01.z, q01.w);
                bar_arrive(5 + (__float_as_uint(s0[0]) & (rzero - 101)), 256);
                mma16(s0, kx[2][0].x, kx[2][0].y, kx[2][0].z, kx[2][0].w, q2.x, q2.y);
                mma16(s1, kx[2][1].x, kx[2][1].y, kx[2][1].z, kx[2][1].w, q2.x, q2.y);
                mma16(sm, km_[2].x, km_[2].y, km_[2].z, km_[2].w, q2.x, q2.y);
                const uint32_t ad = sb + O_SM + (1 - hf) * 1280 + L * 640 + rd;
                sta128(ad + l16, pk(s0[0], s0[1]), pk(s0[2], s0[3]), pk(s1[0], s1[1]), pk(s1[2], s1[3]), bar + B_SM + rd);
                sta32(ad + 512 + (l16 >> 2), pk(sm[0], sm[1]), bar + B_SM + rd);
            }
            TR(1);
            if (t + 1 == NT) break;
#pragma unroll
            for (int m = 0; m < 8; m++) vx[m >> 1][m & 1] = lds128(sb + O_VX + (hf * 4 + (m >> 1)) * 2048 + L * 1024 + (m & 1) * 512 + l16);
            const uint32_t tag = (t + EP * (NT - 1) + 1) & 1;
            uint32_t ident = IDENT;
            asm volatile("" : "+r"(ident));
            mbar_wait(bar + B_SM, t & 1);
            TR(2);
            {
                const uint32_t ad = sb + O_SM + L * 640;
                const uint4 u = lds128(ad + l16), v = lds128(ad + 1280 + l16);
                const uint32_t x = lds32(ad + 512 + (l16 >> 2)), y = lds32(ad + 1280 + 512 + (l16 >> 2));
                mma8(s0, u.x, u.y, ident); mma8(s1, u.z, u.w, ident); mma8(s0, v.x, v.y, ident); mma8(s1, v.z, v.w, ident);
                sm[0] += bf_lo(x) + bf_lo(y); sm[1] += bf_hi(x) + bf_hi(y);
            }
            uint2 vm[4];
#pragma unroll
            for (int m = 0; m < 4; m++) vm[m] = lds64(sb + O_VM + (hf * 4 + m) * 512 + l16 + L * 8);
            float mx0 = fmaxf(fmaxf(fmaxf(s0[0], s0[2]), fmaxf(s1[0], s1[2])), sm[0]);
            float mx1 = fmaxf(fmaxf(fmaxf(s0[1], s0[3]), fmaxf(s1[1], s1[3])), sm[1]);
#pragma unroll
            for (int o = 4; o < 32; o <<= 1) { mx0 = fmaxf(mx0, __shfl_xor_sync(~0u, mx0, o)); mx1 = fmaxf(mx1, __shfl_xor_sync(~0u, mx1, o)); }
            mx0 *= -SC; mx1 *= -SC;
            s0[0] = ex2(fmaf(s0[0], SC, mx0)); s0[1] = ex2(fmaf(s0[1], SC, mx1));
            s0[2] = ex2(fmaf(s0[2], SC, mx0)); s0[3] = ex2(fmaf(s0[3], SC, mx1));
            const uint32_t pb0 = movm(pk(s0[0], s0[1])), pb1 = movm(pk(s0[2], s0[3]));
            s1[0] = ex2(fmaf(s1[0], SC, mx0)); s1[1] = ex2(fmaf(s1[1], SC, mx1));
            s1[2] = ex2(fmaf(s1[2], SC, mx0)); s1[3] = ex2(fmaf(s1[3], SC, mx1));
            const uint32_t pb2 = movm(pk(s1[0], s1[1])), pb3 = movm(pk(s1[2], s1[3]));
            sm[0] = ex2(fmaf(sm[0], SC, mx0)); sm[1] = ex2(fmaf(sm[1], SC, mx1));
            const uint32_t pm = movm(pk(sm[0], sm[1]));
            float o[4][4], l[4] = {0, 0, 0, 0};
            const uint32_t one = 0x3f803f80;
            mma8(l, one, one, pb0); mma8(l, one, one, pb1);
#pragma unroll
            for (int m = 0; m < 4; m++) { o[m][0] = o[m][1] = o[m][2] = o[m][3] = 0.f; mma16(o[m], vx[m][0].x, vx[m][0].y, vx[m][0].z, vx[m][0].w, pb0, pb1); }
            mma8(l, one, one, pb2); mma8(l, one, one, pb3);
#pragma unroll
            for (int m = 0; m < 4; m++) mma16(o[m], vx[m][1].x, vx[m][1].y, vx[m][1].z, vx[m][1].w, pb2, pb3);
            mma8(l, one, one, pm);
#pragma unroll
            for (int m = 0; m < 4; m++) mma8(o[m], vm[m].x, vm[m].y, pm);
            const float l0 = rcp(l[0]), l1 = rcp(l[1]);
#pragma unroll
            for (int m = 0; m < 4; m += 2)
                stsm4t(sb + O_OX + (hf * 4 + m) * 512 + (L ^ ((h >> 2) & 1)) * 256   + ((l16 & 0x100) << 1) + (l16 & 0xf0),
                       pk(o[m][0] * l0, o[m][1] * l1), pk(o[m][2] * l0, o[m][3] * l1), pk(o[m + 1][0] * l0, o[m + 1][1] * l1), pk(o[m + 1][2] * l0, o[m + 1][3] * l1));
            TR(3);
            char* const pdst = ex + poff;
            const char* const rsrc = ex + roff + l16;
            uint4 v[4] = {};
            bar_sync(6, 128);
            {
                uint4 bo[8], a1[8], z;
                const uint32_t wad = WOAD;
#pragma unroll
                for (int kk = 0; kk < 8; kk++) bo[kk] = ldsm4(sb + O_OX + kk * 512 + l16);
#pragma unroll
                for (int G = 0; G < 3; G++) {
                    float e[4][4];
#pragma unroll
                    for (int q = 0; q < 4; q++) e[q][0] = e[q][1] = e[q][2] = e[q][3] = 0.f;
#pragma unroll
                    for (int kk = 0; kk < 8; kk++) {
                        const uint4 f = G == 0 ? a0[kk] : a1[kk];
                        mma16(e[(kk & 1) * 2], f.x, f.y, f.z, f.w, bo[kk].x, bo[kk].y);
                        mma16(e[(kk & 1) * 2 + 1], f.x, f.y, f.z, f.w, bo[kk].z, bo[kk].w);
                        if (G == 2 && kk == EK) {
#pragma unroll
                            for (int i = 0; i < 4; i++) { v[i].x = ~tag; ldg_pkt_if(v[i], rsrc + i * 512, w < EARLY); }
                            sched_fence(rzero, 5);
                            bar_arrive(11, 384);
                        }
                        if (G == 1) a1[kk] = ldsm4t(wad + 32768 + kk * 2048);
                        if (G == 0 && kk == FK) {
                            sched_fence(rzero, 2);
#pragma unroll
                            for (int j = 0; j < 8; j++) a1[j] = ldsm4t(wad + 16384 + j * 2048);
                        }
                    }
                    if (G > 0) asm volatile("{.reg .pred p; setp.eq.u32 p, %5, 0; @p st.shared.v4.u32 [%0], {%1,%2,%3,%4};}" :: "r"(__float_as_uint(e[0][0])), "r"(z.x), "r"(z.y), "r"(z.z), "r"(z.w), "r"(rzero));
                    z = make_uint4((pk(e[0][0] + e[2][0], e[0][1] + e[2][1]) & ~1u) | tag, pk(e[0][2] + e[2][2], e[0][3] + e[2][3]),
                                   pk(e[1][0] + e[3][0], e[1][1] + e[3][1]), pk(e[1][2] + e[3][2], e[1][3] + e[3][3]));
                    stg_pkt(pdst + (G == 2 ? 16384 : G * 2048), z.x, z.y, z.z, z.w);
                    if (G == 0) { TR(9); TRD(t, 0); }
                    if (G < 2) sched_fence(rzero, 3 + G);
                }
            }
            TR(4);
            if (w < 3) {
                bar_arrive(7, 256);
                OPQ();
                const uint32_t tagm = tag;
                uint32_t m0v = 0;
                if (t + 1 <= LAG) {
                    const unsigned short* m = reinterpret_cast<const unsigned short*>(mem0) + ((l16 >> 3) & 6) * DM + 192 * w + 16 * (b >> 3) + (b & 7) + ((l16 >> 4) & 8);
                    m0v = m[0] | (m[DM] << 16);
                }
                if (DLY1) pause(DLY1);
                for (int n = 0; __any_sync(~0u, lop_bad(lop_bad(0, v[0].x, v[1].x, tagm), v[2].x, v[3].x, tagm) & 1); n++) {
#pragma unroll
                    for (int i = 0; i < 4; i++) ldg_pkt_retry(v[i], rsrc + i * 512, tagm);
                    fault_if(n > POLL_LIMIT, n);
                }
                TR(5); TRD(t, 1);
                float s[8];
                s[4] = (bf_lo(v[0].z) + bf_lo(v[1].z)) + (bf_lo(v[2].z) + bf_lo(v[3].z)); s[5] = (bf_hi(v[0].z) + bf_hi(v[1].z)) + (bf_hi(v[2].z) + bf_hi(v[3].z));
                s[6] = (bf_lo(v[0].w) + bf_lo(v[1].w)) + (bf_lo(v[2].w) + bf_lo(v[3].w)); s[7] = (bf_hi(v[0].w) + bf_hi(v[1].w)) + (bf_hi(v[2].w) + bf_hi(v[3].w));
                s[2] = (bf_lo(v[0].y) + bf_lo(v[1].y)) + (bf_lo(v[2].y) + bf_lo(v[3].y)); s[3] = (bf_hi(v[0].y) + bf_hi(v[1].y)) + (bf_hi(v[2].y) + bf_hi(v[3].y));
                s[0] = (bf_lo(v[0].x) + bf_lo(v[1].x)) + (bf_lo(v[2].x) + bf_lo(v[3].x)); s[1] = (bf_hi(v[0].x) + bf_hi(v[1].x)) + (bf_hi(v[2].x) + bf_hi(v[3].x));
#pragma unroll
                for (int j = 0; j < 4; j++) s[j] += __shfl_xor_sync(~0u, s[j + 4], 16);
#pragma unroll
                for (int j = 0; j < 2; j++) s[j] += __shfl_xor_sync(~0u, s[j + 2], 8);
#pragma unroll
                for (int j = 0; j < 2; j++) s[j] += __shfl_xor_sync(~0u, s[j], 4);
                char* const mem_w = ex + mem_off(w, 0);
                uint32_t res = t + 1 <= LAG && l16 >= 256 ? m0v : pk(s[0], s[1]);
                if ((l16 & 48) == 0) res = (res & ~1u) | tag;
                char* const pub = mem_w + (mem_off(0, b >> 3) - mem_off(0, 0)) + (b & 7) * 16 + (((l16 & 64) << 6) + ((l16 & 128) << 1) + ((l16 & 256) >> 1) + ((l16 >> 2) & 12));
                stg_word(pub, res, true);
                TR(6); TRD(t, 2);
                pause(DLY2);
                const char* src = mem_w + (side ^ page_par(0x180000)) * 4096 + l16;
                const uint32_t gdst = sb + O_MB + w * 6144 + l16;
                uint4 x[12];
#pragma unroll
                for (int i = 0; i < 12; i++) x[i] = ldg_pkt(src + (mem_off(0, i) - mem_off(0, 0)));
#pragma unroll
                for (int i = 0; i < 12; i++) sts128(gdst + i * 512, x[i].x, x[i].y, x[i].z, x[i].w);
                for (int n = 0;; n++) {
                    uint32_t bad = 0;
#pragma unroll
                    for (int i = 0; i < 12; i += 2) bad = lop_bad(bad, x[i].x, x[i + 1].x, tagm);
                    if (!__any_sync(~0u, bad & 1)) break;
                    uint32_t old[12];
#pragma unroll
                    for (int i = 0; i < 12; i++) { old[i] = x[i].x; ldg_pkt_retry(x[i], src + (mem_off(0, i) - mem_off(0, 0)), tagm); }
#pragma unroll
                    for (int i = 0; i < 12; i++)
                        asm volatile("{.reg .pred p; .reg .b32 t; lop3.b32 t, %5, %1, 1, 0x28; setp.ne.u32 p, t, 0; @p st.shared.v4.u32 [%0], {%1,%2,%3,%4};}"
                            :: "r"(gdst + i * 512), "r"(x[i].x), "r"(x[i].y), "r"(x[i].z), "r"(x[i].w), "r"(old[i]) : "memory");
                    fault_if(n > POLL_LIMIT, n);
                }
                TR(7); TRD(t, 3);
                fence_async_smem();
                bar_arrive(1 + w, 160);
                bar_arrive(12 + w, 160);
                TR(8);
            } else {
                mbar_wait(bar + B_X, (t + 1) & 1);
                bar_sync(7, 256);
                fence_async_smem();
                arm();
                __syncwarp();
                mbar_arrive_all3(bar + B_WIN, l16 >> 4);
                if (DLYO) pause(DLYO);
                store_o(t);
                pause(DLYP);
                cnt_look(g_cnt + (C_X + t + 2) * 8, 64 * (EP + 1), bar + 8, t + 2);
                __syncwarp();
                TR(5);
            }
        }
        if (w == 3) { bar_sync(7, 160); fence_async_smem(); store_o(NT - 1); asm volatile("cp.async.bulk.wait_group 0;" ::: "memory"); }
        cluster_sync();
    }
    TR_DUMP(b);
}

#define VL 12
#define VP 18
#define VC 19
#define VG 12
#define HB 3
#define HA 2
#define HW 0
namespace ka {
constexpr int O_WA = 196608;
constexpr int A_KB = 21504;
constexpr int O_RING = 194560;
constexpr int O_BAR = 230400;
constexpr int SMEM = O_BAR + 256 + 1024;
constexpr float SC = 0.23570226039551584f * 1.4426950408889634f;
}

template <int NP, int KB = 4096>
DEVI void row_task(const uint4* res, const uint4* part, uint4* xout, char* img, int pos, int lane, uint32_t tag) {
    const bool on = lane < 24;
    const int ln = on ? lane : 0;
    uint4 rv[3], pv[NP > 0 ? NP * 3 : 1];
#pragma unroll
    for (int i = 0; i < 3; i++) rv[i] = ldg128(res + i * 24 + ln);
#pragma unroll
    for (int i = 0; i < NP * 3; i++) pv[i] = ldg_pkt(part + i * 24 + ln);
    if (NP > 0) validate<NP * 3>(pv, part + ln, 384, tag);
#pragma unroll
    for (int q = 0; q < NP * 3 / 2; q++) {
        const uint4 y = pv[q + NP * 3 / 2];
        pv[q] = make_uint4(add2(pv[q].x, y.x), add2(pv[q].y, y.y), add2(pv[q].z, y.z), add2(pv[q].w, y.w));
    }
    float x[24];
    uint32_t w[12];
#pragma unroll
    for (int i = 0; i < 3; i++) {
        x[8 * i] = bf_lo(rv[i].x); x[8 * i + 1] = bf_hi(rv[i].x); x[8 * i + 2] = bf_lo(rv[i].y); x[8 * i + 3] = bf_hi(rv[i].y);
        x[8 * i + 4] = bf_lo(rv[i].z); x[8 * i + 5] = bf_hi(rv[i].z); x[8 * i + 6] = bf_lo(rv[i].w); x[8 * i + 7] = bf_hi(rv[i].w);
    }
    if (NP > 0) {
#pragma unroll
        for (int q = 0; q < NP * 3 / 2; q++) {
            const int i = q % 3;
            x[8 * i] += bf_lo(pv[q].x); x[8 * i + 1] += bf_hi(pv[q].x); x[8 * i + 2] += bf_lo(pv[q].y); x[8 * i + 3] += bf_hi(pv[q].y);
            x[8 * i + 4] += bf_lo(pv[q].z); x[8 * i + 5] += bf_hi(pv[q].z); x[8 * i + 6] += bf_lo(pv[q].w); x[8 * i + 7] += bf_hi(pv[q].w);
        }
#pragma unroll
        for (int j = 0; j < 12; j++) { w[j] = pk(x[2 * j], x[2 * j + 1]); x[2 * j] = bf_lo(w[j]); x[2 * j + 1] = bf_hi(w[j]); }
    }
    if (NP > 0) {
#pragma unroll
        for (int i = 0; i < 3; i++) stg128p(xout + i * 24 + ln, w[4 * i], w[4 * i + 1], w[4 * i + 2], w[4 * i + 3], on);
    }
    if (img) {
        const float x0 = __shfl_sync(~0u, x[0], 0);
        float s4[4] = {0, 0, 0, 0}, v4[4] = {0, 0, 0, 0};
#pragma unroll
        for (int j = 0; j < 24; j++) { x[j] -= x0; s4[j & 3] += x[j]; v4[j & 3] = fmaf(x[j], x[j], v4[j & 3]); }
        float s = on ? (s4[0] + s4[1]) + (s4[2] + s4[3]) : 0.f, v = on ? (v4[0] + v4[1]) + (v4[2] + v4[3]) : 0.f;
#pragma unroll
        for (int o = 1; o < 32; o <<= 1) { const float2 z = shfl2(s, v, o); s += z.x; v += z.y; }
        const float mean = s * (1.f / DM);
        const float rs = rsqrtf(fmaxf(fmaf(-mean, mean, v * (1.f / DM)), 0.f) + 1e-5f), sh = -mean * rs;
#pragma unroll
        for (int j = 0; j < 24; j++) x[j] = fmaf(x[j], rs, sh);
        char* dst = img + (ln >> 3) * KB + pos * 128 + (((ln ^ pos) & 7) << 4);
#pragma unroll
        for (int i = 0; i < 3; i++)
            stg128p(dst + i * (3 * KB), pk(x[8 * i], x[8 * i + 1]), pk(x[8 * i + 2], x[8 * i + 3]),
                    pk(x[8 * i + 4], x[8 * i + 5]), pk(x[8 * i + 6], x[8 * i + 7]), on);
    }
}

DEVI void rows_a(const uint4* xin, int f, int i, int lane, uint32_t ep, int warp) {
    for (int u = 0; u < LAG; u++) cnt_hint(g_cnt + (C_X + u + (f ? 0 : NSEG)) * 8, lane);
#pragma unroll 1
    for (int seg = 0; seg < NSEG; seg++) {
        const int j = seg + f * LAGA, u = seg + f * LAG, row = seg * 32 + i;
        hint_wait(g_cnt + (C_WA + j * 4 + f * 2 + (i & 1)) * 8, 24 * (ep + 1));
        TRG(u, 0);
        row_task<4, 8192>((f ? g_x + 2048 * 72 : xin) + row * 72, g_pa + ((j & (RING - 1)) * 64 + f * 32 + i) * 288,
                    g_x + (f * 4096 + row) * 72, reinterpret_cast<char*>(g_xt + u * 4608 + f * 256), i, lane, ring_tag<NTA>(j, ep));
        TRG(u, 1);
        cnt_add(g_cnt + (C_X + u) * 8, lane);
        TRG(u, 2);
    }
}

__global__ void __launch_bounds__(384, 1)
k_aux(const __nv_bfloat16* __restrict__ x0, const __nv_bfloat16* __restrict__ wqkv, const __nv_bfloat16* __restrict__ wo,
      const __nv_bfloat16* __restrict__ Wo, __nv_bfloat16* __restrict__ out, const Tune tune) {
    using namespace ka;
    extern __shared__ unsigned char smem_raw[];
    const uint32_t sb = (smem_u32(smem_raw) + 1023) & ~1023u;
    const int tid = threadIdx.x, lane = tid & 31, warp = __shfl_sync(~0u, tid >> 5, 0), g = lane >> 2, c = lane & 3;
    const int b = blockIdx.x;
    const uint32_t bar = sb + O_BAR;
    const uint32_t ep_ = ldg32(&g_epoch);

    TRG(79, 0);
    const uint4* xin = reinterpret_cast<const uint4*>(x0);
    if (warp >= 8 || b == 35) {
        asm volatile("setmaxnreg.dec.sync.aligned.u32 128;");
        const int rw = b < 24 ? (warp - 8) * 24 + b : b < 35 ? (warp - 8) * 11 + b - 24 : 128 + 2 * warp;
        if (b < 24 || b == 35 || rw < 32) {
#pragma unroll 1
            for (int row = b < 24 ? rw + 32 : rw; row < 2048; row += (row & 1) ? 23 : 1) {
                if (lane == 0 && b == 35 && row < 2024) prefetch_l2(xin + (row + 24) * 72, 1152);
                row_task<0>(xin + row * 72, nullptr, nullptr, reinterpret_cast<char*>(g_xa + (row >> 5) * 4608), (row & 1) * 16 + ((row & 31) >> 1), lane, 0);
                if (b < 35) { cnt_add(g_cnt + (C_N0 + (row >> 5)) * 8, lane); break; }
                if (row & 1) cnt_add<2>(g_cnt + (C_N0 + (row >> 5)) * 8, lane);
            }
        }
        const uint32_t ep = __shfl_sync(~0u, ep_, 0);
        if (rw < 32) {
            const int f = b < 24, i = rw;
#pragma unroll 1
            for (int seg = 0; seg < NSEG; seg++) {
                const int u = seg + f * LAG, row = seg * 32 + i;
                hint_wait(g_cnt + (C_WB + u * 4 + f * 2 + (i >> 4)) * 8, 24 * (ep + 1));
                TRG(u, 0);
                row_task<8>(g_x + (f * 4096 + row) * 72, g_pb + ((u & (RING - 1)) * 64 + f * 32 + i) * 576,
                            f ? reinterpret_cast<uint4*>(out) + row * 72 : g_x + (2048 + row) * 72,
                            f ? nullptr : reinterpret_cast<char*>(g_xa + (seg + LAGA) * 4608 + 2304), (i & 1) * 16 + (i >> 1), lane, ring_tag(u, ep));
                TRG(u, 1);
                cnt_add(g_cnt + (C_RB + f * NSEG + seg) * 8, lane);
                TRG(u, 2);
            }
            if (f && rw == 31) {
                asm volatile("griddepcontrol.wait;" ::: "memory");
                if (lane == 0) g_epoch = ep + 1;
            }
        } else if (rw < 64 && b < 24) rows_a(xin, 0, rw - 32, lane, ep, warp);
        return;
    }

    if (b < 24) {
        if (warp >= 4) {
            const int kq = b / 6, nq = b % 6;
            uint4 v[17];
#pragma unroll
            for (int q = 0; q < 17; q++) {
                const int it = q * 4 + warp - 4, kr = (it / 3) * 8 + g, s = kq * 11 + (kr >> 4), a = s >> 2, j = s & 3, e = kr & 15;
                const int head = 3 * a + (j < 3 ? j : e >> 1), row = head * 18 + (j < 3 ? e : 16 + (e & 1));
                v[q] = make_uint4(0, 0, 0, 0);
                if (it < 66 && head < 32 && (j < 3 || e < 6)) v[q] = *reinterpret_cast<const uint4*>(wo + row * DM + nq * 96 + (it % 3) * 32 + c * 8);
            }
#pragma unroll
            for (int q = 0; q < 17; q++) {
                const int it = q * 4 + warp - 4;
                const uint32_t ad = sb + O_WA + (it % 3) * 4 * 2816 + (it / 3) * 128 + lane * 4;
                if (it < 66) { sts32(ad, v[q].x); sts32(ad + 2816, v[q].y); sts32(ad + 2 * 2816, v[q].z); sts32(ad + 3 * 2816, v[q].w); }
            }
        } else {
            const int kg = b / 3, ng = b % 3;
            delay(DLYB);
#pragma unroll 1
            for (int bt = 0; bt < 4; bt++) {
                uint4 v[24];
#pragma unroll
                for (int q = 0; q < 24; q++)
                    v[q] = *reinterpret_cast<const uint4*>(Wo + (size_t)(kg * 512 + (bt * 4 + q / 6) * 32 + warp * 8 + g) * DM + ng * 192 + (q % 6) * 32 + c * 8);
#pragma unroll
                for (int q = 0; q < 24; q++) {
                    const uint32_t ad = sb + (q % 6) * 4 * 8192 + ((bt * 4 + q / 6) * 4 + warp) * 128 + lane * 4;
                    sts32(ad, v[q].x); sts32(ad + 8192, v[q].y); sts32(ad + 2 * 8192, v[q].z); sts32(ad + 3 * 8192, v[q].w);
                }
            }
        }
        fence_async_smem();
        bar_sync(2 + (warp >> 2), 128);
    } else {
        for (int i = tid; i < 2048; i += 256) sts128(sb + O_RING + i * 16, 0, 0, 0, 0);
        if (tid < 17) mbar_init(bar + tid * 8, tid >= 4 && tid < 8 ? 4 : 1);
        fence_async_smem();
        bar_sync(1, 256);
    }
    TRG(79, 1);
    const uint32_t ep = __shfl_sync(~0u, ep_, 0);
    const int wq = warp & 3;

    if (warp < 4) {
        asm volatile("setmaxnreg.inc.sync.aligned.u32 256;");
        if (b < 24) {
            const int kg = b / 3, ng = b % 3;
            const uint32_t blo = ((sb >> 4) & 0x3fff) | (8u << 16);
            uint4 a[32];
            uint32_t seen = 0;
            bool pre = false;
#pragma unroll 1
            for (int u = 0; u < NT; u++) {
                const uint32_t tag = ring_tag(u, ep);
                const uint4* src = g_o + (((u & (RING - 1)) * 256 + kg * 32) * 4 + wq) * 32 + lane;
                if (!pre) {
                    if (!__all_sync(~0u, seen >= 12 * (ep + 1))) hint_wait(g_cnt + (C_O + u * 8 + kg) * 8, 12 * (ep + 1));
#pragma unroll
                    for (int i = 0; i < VG; i++) a[i] = ldg_pkt(src + i * 128);
                }
                TRG(u, 0);
                float d[96];
                validate<VG>(a, src, 2048, tag);
                wg_fence();
#pragma unroll
                for (int i = 0; i < 32; i++) {
                    if (i == VL) {
                        if (!pre) {
#pragma unroll
                            for (int j = VG; j < VP; j++) a[j] = ldg_pkt(src + j * 128);
                        }
#pragma unroll
                        for (int j = VP; j < 32; j++) a[j] = ldg_pkt(src + j * 128);
                    }
                    if (i == VG) { validate<32 - VG>(a + VG, src + VG * 128, 2048, tag); wg_fence(); }
                    wgmma_rs192t(d, a[i].x, a[i].y, a[i].z, a[i].w, mkdesc(blo + i * 16, 512), i > 0);
                    if (i == VC - 1 || i == 23 || i == 31) wg_commit();
                }
                const unsigned* cn = g_cnt + (C_O + min(u + 1, NT - 1) * 8 + kg) * 8;
                const uint4* nx = g_o + ((((u + 1) & (RING - 1)) * 256 + kg * 32) * 4 + wq) * 32 + lane;
                auto look = [&]() {
                    pre = __all_sync(~0u, seen >= 12 * (ep + 1));
                    if (pre) {
#pragma unroll
                        for (int i = 0; i < VP; i++) a[i] = ldg_pkt(nx + i * 128);
                    } else seen = ldg_word(cn);
                };
                wg_wait<2>();
                seen = ldg_word(cn);
                wg_wait<1>();
                look();
                wg_wait<0>();
                if (!pre) look();
                TRG(u, 1);
                uint4* dst = g_pb + (((u & (RING - 1)) * 64 + wq * 16 + g) * 8 + kg) * 72 + ng * 24 + c;
#pragma unroll
                for (int m = 0; m < 6; m++) {
                    if (m == HB) cnt_hint(g_cnt + (C_WB + u * 4 + wq) * 8, lane);
                    stg128(dst + 4 * m, (pk(d[16 * m], d[16 * m + 1]) & ~1u) | tag, pk(d[16 * m + 4], d[16 * m + 5]), pk(d[16 * m + 8], d[16 * m + 9]), pk(d[16 * m + 12], d[16 * m + 13]));
                    stg128(dst + 4 * m + 8 * 576, (pk(d[16 * m + 2], d[16 * m + 3]) & ~1u) | tag, pk(d[16 * m + 6], d[16 * m + 7]), pk(d[16 * m + 10], d[16 * m + 11]), pk(d[16 * m + 14], d[16 * m + 15]));
                }
                TRG(u, 3);
            }
        } else {
            const int a = b - 24, f = wq >> 1;
            const uint32_t blo = ((sb >> 4) & 0x3fff) | (8u << 16), alo = (((sb + O_RING) >> 4) & 0x3fff) | (1u << 16);
            const bool m0 = 2 * c <= g, m1 = 2 * c + 1 <= g;
            const uint32_t M = (m0 ? 0xffffu : 0u) | (m1 ? 0xffff0000u : 0u);
            uint32_t kh[7], vh[7];
#pragma unroll
            for (int i = 0; i < 7; i++) kh[i] = vh[i] = 0;
            int it = 0;
#pragma unroll 1
            for (int u = 0; u < NTA; u++) {
                float d[84];
#pragma unroll 1
                for (int kb = 0; kb < 9; kb++, it++) {
                    mbar_wait(bar + (it & 3) * 8, (it >> 2) & 1);
                    if (u == 0) mbar_wait(bar + 64 + kb * 8, 0);
                    if (kb == 0) TRG(u, 0);
                    wg_fence();
#pragma unroll
                    for (int q = 0; q < 4; q++)
                        wgmma_ss168t(d, mkdesc(alo + (it & 3) * 512 + q * 2, km::DESC_HI), mkdesc(blo + kb * (A_KB >> 4) + q * 16, 64), kb + q > 0);
                    wg_commit();
                    wg_wait<1>();
                    mbar_arrive(bar + 32 + ((it - 1) & 3) * 8, lane == 0 && kb > 0);
                }
                wg_wait<0>();
                mbar_arrive(bar + 32 + ((it - 1) & 3) * 8, lane == 0);
                TRG(u, 1);
                const bool first = u == f * LAGA;
                const uint32_t tag = ring_tag<NTA>(u, ep);
                const uint32_t qt0 = pk(d[72], d[73]), qt1 = pk(d[74], d[75]), kt0 = pk(d[76], d[77]), kt1 = pk(d[78], d[79]);
                const uint32_t vt0 = movm(pk(d[80], d[81])), vt1 = movm(pk(d[82], d[83]));
                float ot[4] = {0, 0, 0, 0};
                uint4* dst = g_oa + (((u & (RING - 1)) * 4 + wq) * 44 + a * 4) * 32 + lane;
#pragma unroll
                for (int h = 0; h < 3; h++) {
                    const float* q = d + 8 * h; const float* k = d + 24 + 8 * h; const float* v = d + 48 + 8 * h;
                    const uint32_t q0 = pk(q[0], q[1]), q1 = pk(q[2], q[3]), q2 = pk(q[4], q[5]), q3 = pk(q[6], q[7]);
                    const uint32_t k0 = pk(k[0], k[1]), k1 = pk(k[4], k[5]), k2 = pk(k[2], k[3]), k3 = pk(k[6], k[7]);
                    const uint32_t v0 = movm(pk(v[0], v[1])), v1 = movm(pk(v[2], v[3])), v2 = movm(pk(v[4], v[5])), v3 = movm(pk(v[6], v[7]));
                    const uint32_t t0 = c == h ? qt0 : 0, t1 = c == h ? qt1 : 0;
                    float sp[4] = {0, 0, 0, 0}, sl[4] = {0, 0, 0, 0}, sh[4] = {0, 0, 0, 0};
                    mma16(sp, q0, q1, q2, q3, kh[2 * h], kh[2 * h + 1]); mma16(sl, q0, q1, q2, q3, k0, k1); mma16(sh, q0, q1, q2, q3, k2, k3);
                    mma8(sp, t0, t1, kh[6]); mma8(sl, t0, t1, kt0); mma8(sh, t0, t1, kt1);
                    float x0_ = m0 ? sl[0] : first ? -INFINITY : sp[0], x1_ = m1 ? sl[1] : first ? -INFINITY : sp[1];
                    float y0_ = m0 ? sh[2] : sl[2], y1_ = m1 ? sh[3] : sl[3];
                    float mx = fmaxf(x0_, x1_), my = fmaxf(y0_, y1_);
#pragma unroll
                    for (int o = 1; o < 4; o <<= 1) { mx = fmaxf(mx, __shfl_xor_sync(~0u, mx, o)); my = fmaxf(my, __shfl_xor_sync(~0u, my, o)); }
                    mx *= -SC; my *= -SC;
                    x0_ = ex2(fmaf(x0_, SC, mx)); x1_ = ex2(fmaf(x1_, SC, mx)); y0_ = ex2(fmaf(y0_, SC, my)); y1_ = ex2(fmaf(y1_, SC, my));
                    float lx = x0_ + x1_, ly = y0_ + y1_;
#pragma unroll
                    for (int o = 1; o < 4; o <<= 1) { lx += __shfl_xor_sync(~0u, lx, o); ly += __shfl_xor_sync(~0u, ly, o); }
                    lx = rcp(lx); ly = rcp(ly);
                    const uint32_t px = pk(x0_ * lx, x1_ * lx), py = pk(y0_ * ly, y1_ * ly);
                    const uint32_t hm = (g >> 1) == h ? ~0u : 0u;
                    float o0[4] = {0, 0, 0, 0}, o1[4] = {0, 0, 0, 0};
                    mma16(o0, px & M, py & ~M, 0, py & M, v0, v1); mma16(o1, px & M, py & ~M, 0, py & M, v2, v3);
                    mma16(ot, px & M, py & ~M, 0, py & M, vt0 & hm, vt1 & hm);
                    mma8(o0, px & ~M, 0, vh[2 * h]); mma8(o1, px & ~M, 0, vh[2 * h + 1]); mma8(ot, px & ~M, 0, vh[6] & hm);
                    if (h == HA) cnt_hint(g_cnt + (C_A + u * 4 + wq) * 8, lane);
                    stg128(dst + h * 32, (pk(o0[0], o0[1]) & ~1u) | tag, pk(o0[2], o0[3]), pk(o1[0], o1[1]), pk(o1[2], o1[3]));
                    kh[2 * h] = k2; kh[2 * h + 1] = k3; vh[2 * h] = v1; vh[2 * h + 1] = v3;
                }
                kh[6] = kt1; vh[6] = vt1;
                stg128(dst + 96, (pk(ot[0], ot[1]) & ~1u) | tag, pk(ot[2], ot[3]), 0, 0);
                TRG(u, 2);
            }
        }
    } else {
        asm volatile("setmaxnreg.dec.sync.aligned.u32 120;");
        if (b < 24) {
            const int kq = b / 6, nq = b % 6;
            const uint32_t blo = (((sb + O_WA) >> 4) & 0x3fff) | (8u << 16);
#pragma unroll 1
            for (int u = 0; u < NTA; u++) {
                hint_wait(g_cnt + (C_A + u * 4 + wq) * 8, 11 * (ep + 1));
                const uint32_t tag = ring_tag<NTA>(u, ep);
                TRG(u, 0);
                const uint4* src = g_oa + (((u & (RING - 1)) * 4 + wq) * 44 + kq * 11) * 32 + lane;
                uint4 a[11];
                float d[48];
#pragma unroll
                for (int i = 0; i < 11; i++) a[i] = ldg_pkt(src + i * 32);
                validate<11>(a, src, 512, tag);
                wg_fence();
#pragma unroll
                for (int i = 0; i < 11; i++) wgmma_rs96t(d, a[i].x, a[i].y, a[i].z, a[i].w, mkdesc(blo + i * 16, 176), i > 0);
                wg_commit();
                wg_wait<0>();
                TRG(u, 1);
                uint4* dst = g_pa + (((u & (RING - 1)) * 64 + (wq >> 1) * 32 + 2 * g + (wq & 1)) * 4 + kq) * 72 + nq * 12 + c;
#pragma unroll
                for (int m = 0; m < 3; m++) {
                    if (m == HW) cnt_hint(g_cnt + (C_WA + u * 4 + wq) * 8, lane);
                    stg128(dst + 4 * m, (pk(d[16 * m], d[16 * m + 1]) & ~1u) | tag, pk(d[16 * m + 4], d[16 * m + 5]), pk(d[16 * m + 8], d[16 * m + 9]), pk(d[16 * m + 12], d[16 * m + 13]));
                    stg128(dst + 4 * m + 16 * 288, (pk(d[16 * m + 2], d[16 * m + 3]) & ~1u) | tag, pk(d[16 * m + 6], d[16 * m + 7]), pk(d[16 * m + 10], d[16 * m + 11]), pk(d[16 * m + 14], d[16 * m + 15]));
                }
                TRG(u, 3);
            }
        } else if (warp == 4) {
            mbar_expect(bar + 64 + lane * 8, A_KB, lane < 9);
            int it = 0;
#pragma unroll 1
            for (int u = 0; u < NTA; u++) {
                if (u == 0) { cnt_wait(g_cnt + C_W * 8, 96 * (ep + 1)); TRG(78, 0); }
                if (u < NSEG) cnt_wait(g_cnt + (C_N0 + u) * 8, 32 * (ep + 1));
                if (u > LAGA + LAG) cnt_wait(g_cnt + (C_RB + NSEG + u - LAGA - LAG - 1) * 8, 32 * (ep + 1));
                if (u >= LAGA) cnt_wait(g_cnt + (C_RB + u - LAGA) * 8, 32 * (ep + 1));
                TRG(u, 0);
                asm volatile("fence.proxy.async.global;" ::: "memory");
                const bool on = lane == 0 ? u < NSEG : lane == 1 && u >= LAGA;
#pragma unroll 1
                for (int kb = 0; kb < 9; kb++, it++) {
                    if (it >= 4) mbar_wait(bar + 32 + (it & 3) * 8, ((it >> 2) - 1) & 1);
                    mbar_expect(bar + (it & 3) * 8, u < NSEG && u >= LAGA ? 8192 : 4096, lane == 0);
                    asm volatile("{.reg .pred p; setp.ne.u32 p, %3, 0; @p cp.async.bulk.shared::cluster.global.mbarrier::complete_tx::bytes [%0], [%1], 4096, [%2];}"
                        :: "r"(sb + O_RING + (it & 3) * 8192 + (lane & 1) * 4096), "l"(g_xa + u * 4608 + (lane & 1) * 2304 + kb * 256), "r"(bar + (it & 3) * 8), "r"((uint32_t)on) : "memory");
                    if (u == 0) asm volatile("{.reg .pred p; setp.ne.u32 p, %4, 0; @p cp.async.bulk.shared::cluster.global.mbarrier::complete_tx::bytes [%0], [%1], %3, [%2];}"
                        :: "r"(sb + lane * A_KB), "l"(g_wa + ((b - 24) * 9 + lane) * (A_KB / 16)), "r"(bar + 64 + lane * 8), "n"(A_KB),
                           "r"((uint32_t)(lane < 9 && kb == (lane < 4 ? lane : lane < 6 ? 3 : lane - 2))) : "memory");
                }
            }
        } else if ((warp - 5) * 11 + b - 24 < 32) rows_a(xin, 1, (warp - 5) * 11 + b - 24, lane, ep, warp);
    }
}

static Tune h_tune = {{0, 11, 1, 2, 0, 6000, 0, 12, 10000, 0}};

extern "C" void kernel_launch(void* const* d_in, const int* in_sizes, int n_in, void* d_out, int out_size) {
    const __nv_bfloat16* x = (const __nv_bfloat16*)d_in[0];
    const __nv_bfloat16* wqkv = (const __nv_bfloat16*)d_in[1];
    const __nv_bfloat16* wo = (const __nv_bfloat16*)d_in[2];
    const __nv_bfloat16* mem0 = (const __nv_bfloat16*)d_in[4];
    const __nv_bfloat16* Wq = (const __nv_bfloat16*)d_in[5];
    const __nv_bfloat16* Wk = (const __nv_bfloat16*)d_in[6];
    const __nv_bfloat16* Wv = (const __nv_bfloat16*)d_in[7];
    const __nv_bfloat16* Wo = (const __nv_bfloat16*)d_in[8];
    cudaFuncSetAttribute(k_main, cudaFuncAttributeMaxDynamicSharedMemorySize, km::SMEM);
    cudaFuncSetAttribute(k_aux, cudaFuncAttributeMaxDynamicSharedMemorySize, ka::SMEM);
    cudaStream_t s = cudaStreamPerThread;
    k_main<<<96, 384, km::SMEM, s>>>(x, wqkv, wo, mem0, Wq, Wk, Wv, Wo, h_tune);
    cudaLaunchConfig_t cfg = {};
    cudaLaunchAttribute at[1];
    at[0].id = cudaLaunchAttributeProgrammaticStreamSerialization;
    at[0].val.programmaticStreamSerializationAllowed = 1;
    cfg.stream = s; cfg.attrs = at; cfg.numAttrs = 1;
    cfg.gridDim = dim3(36); cfg.blockDim = dim3(384); cfg.dynamicSmemBytes = ka::SMEM;
    cudaLaunchKernelEx(&cfg, k_aux, x, wqkv, wo, Wo, (__nv_bfloat16*)d_out, h_tune);
}
```
